```python
import torch

def _softmax(x, axis=-1):
    return torch.softmax(x, dim=axis)
def _gelu(x):
    return torch.nn.functional.gelu(x, approximate="tanh")
def _silu(x):
    return torch.nn.functional.silu(x)
def _sigmoid(x):
    return torch.sigmoid(x)
def _layernorm(x, axis=-1, eps=1e-5):
    m = x.mean(dim=axis, keepdim=True)
    v = x.var(dim=axis, keepdim=True, unbiased=False)
    return (x - m) / torch.sqrt(v + eps)
def _scatter_add(tgt, idx, src, axis=0):
    return tgt.clone().index_add_(axis, idx, src)
def _segment_sum(src, seg, n):
    out = torch.zeros((n,) + src.shape[1:], dtype=src.dtype)
    return out.index_add_(0, seg, src)
def _pad(x, pw):
    flat = tuple(v for pair in reversed(pw) for v in pair)
    return torch.nn.functional.pad(x, flat)

kernel_name = 'concat_heads__grouped_kv_mqa__ssm_conv_s4d__prompt'

def setup_inputs():

    _w = (lambda a: (lambda t: t.to(torch.bfloat16) if t.is_floating_point() else t)(torch.as_tensor(a)))
    def _A_setup():
        B, S, D, H = 1, 2048, 512, 32
        Dh = D // H
        return {
            "x": _w((lambda *s: torch.randn(*s, dtype=torch.bfloat16) * 0.05)(B, S, D)),
            "wq": _w((lambda *s: torch.randn(*s, dtype=torch.bfloat16) * 0.8)(D, H * Dh)),
            "wk": _w((lambda *s: torch.randn(*s, dtype=torch.bfloat16) * 0.8)(D, Dh)),
            "wv": _w((lambda *s: torch.randn(*s, dtype=torch.bfloat16) * 0.05)(D, Dh)),
            "wo": _w((lambda *s: torch.randn(*s, dtype=torch.bfloat16) * 0.05)(H * Dh, D)),
        }
    _A_in = _A_setup()

    def _B_setup():
        Bsz, L, D, N = 1, 2048, 512, 128
        return {
            "u": _w((lambda *s: torch.randn(*s, dtype=torch.bfloat16) * 0.05)(Bsz, L, D)),
            "log_A_real": _w((lambda *s: torch.randn(*s, dtype=torch.bfloat16) * 6.4)(D, N) * 0.5),
            "A_imag": _w((lambda *s: torch.randn(*s, dtype=torch.bfloat16) * 0.05)(D, N) * 3.14),
            "C_real": _w((lambda *s: torch.randn(*s, dtype=torch.bfloat16) * 0.05)(D, N) / N ** 0.5),
            "C_imag": _w((lambda *s: torch.randn(*s, dtype=torch.bfloat16) * 0.05)(D, N) / N ** 0.5),
            "log_dt": _w((lambda *s: torch.randn(*s, dtype=torch.bfloat16) * 0.05)(D) * 0.5 - 4.0),
            "D_skip": _w((lambda *s: torch.randn(*s, dtype=torch.bfloat16) * 0.05)(D)),
        }
    _B_in = _B_setup()

    return {
        "A_x": _A_in["x"],
        "A_wq": _A_in["wq"],
        "A_wk": _A_in["wk"],
        "A_wv": _A_in["wv"],
        "A_wo": _A_in["wo"],
        "B_u": _B_in["u"],
        "B_log_A_real": _B_in["log_A_real"],
        "B_A_imag": _B_in["A_imag"],
        "B_C_real": _B_in["C_real"],
        "B_C_imag": _B_in["C_imag"],
        "B_log_dt": _B_in["log_dt"],
        "B_D_skip": _B_in["D_skip"],
    }

def reference(A_x, A_wq, A_wk, A_wv, A_wo, B_u, B_log_A_real, B_A_imag, B_C_real, B_C_imag, B_log_dt, B_D_skip):
    def _A_ref(x, wq, wk, wv, wo):
        B, S, D = x.shape
        H = 32
        Dh = D // H
        q = (lambda x, *d: x.permute(*d))((x @ wq).reshape(B, S, H, Dh), 0, 2, 1, 3)
        k = x @ wk
        v = x @ wv
        scores = torch.einsum("bhqd,bkd->bhqk", q, k) * (Dh ** -0.5)
        p = _softmax(scores, axis=-1)
        o = torch.einsum("bhqk,bkd->bhqd", p, v)
        return (lambda x, *d: x.permute(*d))(o, 0, 2, 1, 3).reshape(B, S, H * Dh) @ wo

    def _B_ref(u, log_A_real, A_imag, C_real, C_imag, log_dt, D_skip):
        L = u.shape[1]
        dt = torch.exp(log_dt)
        A = -torch.exp(log_A_real) + 1j * A_imag
        C = (C_real + 1j * C_imag) * dt[:, None]
        pos = (lambda x, dt: x.to(dt))(torch.arange(L), log_dt.dtype)
        P = torch.exp((A * dt[:, None])[:, :, None] * pos[None, None, :])
        K = 2.0 * torch.einsum("dn,dnl->dl", C, P).real
        L2 = 2 * L
        u_t = (lambda x, *d: x.permute(*d))(u, 0, 2, 1)
        Kf = (lambda x, *a, **k: torch.fft.rfft(x.float(), *a, **k))(K, L2)
        Uf = (lambda x, *a, **k: torch.fft.rfft(x.float(), *a, **k))(u_t, L2)
        y = (lambda x, *a, **k: torch.fft.irfft(x, *a, **k).to(torch.bfloat16))(Uf * Kf[None, :, :], L2)[:, :, :L]
        y = (lambda x, *d: x.permute(*d))(y, 0, 2, 1)
        return y + u * D_skip[None, None, :]

    a = _A_ref(A_x, A_wq, A_wk, A_wv, A_wo)
    b = _B_ref(B_u, B_log_A_real, B_A_imag, B_C_real, B_C_imag, B_log_dt, B_D_skip)
    return torch.concatenate([a, b], axis=-1)
```

```cpp
#include <cuda_runtime.h>
#include <cuda_bf16.h>
#include <cuda_fp16.h>
#include <cuda.h>
#include <stdint.h>

namespace {

constexpr int SEQ = 2048;
constexpr int NCTA = 128, NTHR = 512;

constexpr int SM_A = 0;
constexpr int SM_K = 0, SM_V = 65536;
constexpr int SM_B = 132096;
constexpr int SM_C = SM_B + 65536;
constexpr int SM_D = SM_C + 16384;
constexpr int SM_BAR = SM_D + 16384;
constexpr int SM_TOTAL = SM_BAR + 1024;
constexpr int SM_ALLOC = SM_TOTAL + 1024;

constexpr int PADU = 288, ULEN = PADU + 2048;
constexpr int WPAD = 16, W2LEN = WPAD + 1536, W3LEN = WPAD + 1024;
constexpr int S_U = 0;
constexpr int S_W3 = S_U + 4 * ULEN * 2;
constexpr int S_W5 = S_W3 + 4 * W2LEN * 2;
constexpr int S_W7 = S_W5 + 4 * W2LEN * 2;
constexpr int S_W9 = S_W7 + 4 * W3LEN * 2;
constexpr int S_TAB = S_W9 + 4 * W3LEN * 2;
constexpr int TABN = 2240;
constexpr int S_Y = S_TAB + 4 * TABN * 2;
static_assert(S_TAB + 4 * TABN * 2 <= SM_D - SM_B, "tables overlap Kc results");
static_assert(S_Y + 4 * 2048 * 2 <= SM_BAR - SM_B, "SSM working set too large");

constexpr int TD0 = 0, TD1 = 560, CD = 544;
constexpr int TE0 = 1120, TE1 = 1168, CE = 1056;
constexpr int T2B = 1216, T2S = 160, T2C = 80, C2 = 80;
constexpr int T3B = 1856, T3S = 192, T3C = 96, C3 = 144;

constexpr int rne8(int t) {
    if (t < 256) return t;
    int sh = 0;
    while ((t >> sh) >= 256) sh++;
    int q = t >> sh, rem = t & ((1 << sh) - 1), half = 1 << (sh - 1);
    if (rem > half || (rem == half && (q & 1))) q++;
    return q << sh;
}
constexpr int kcidx(int p) {
    if (p < 256) return (p >> 3) * 24 + (p & 7);
    if (p < 512) return ((p - 256) >> 3) * 24 + 8 + (((p - 256) & 7) >> 1);
    if (p < 1024) { int q = p - 512, hi = q >> 8, rem = q & 255; return (rem >> 3) * 24 + 12 + 2 * hi + ((rem & 7) >> 2); }
    if (p < 2048) { int q = p - 1024; return ((q & 255) >> 3) * 24 + 16 + (q >> 8); }
    return 20;
}
constexpr int KC_ZERO = 23;
constexpr int tab_dense(int t) { return (t >= 0 && t <= 514) ? kcidx(rne8(t)) : KC_ZERO; }
constexpr int tab_extra(int t) { return (t >= 1027 && t <= 1028) ? kcidx(1024) : KC_ZERO; }
constexpr int tab_2(int s, int lag) { return (lag >= 32 && lag <= 63) ? kcidx(s == 0 ? 16 * (lag + 1) : 16 * lag + 4 * s) : KC_ZERO; }
constexpr int tab_3(int s, int lag) { return (lag >= 64 && lag <= 127) ? kcidx(s == 0 ? 16 * (lag + 1) : 16 * lag + 8) : KC_ZERO; }
struct TabMap {
    uint16_t v[TABN];
    constexpr TabMap() : v{} {
        for (int i = 0; i < 560; i++) { v[TD0 + i] = tab_dense(CD - i); v[TD1 + i] = tab_dense(CD + 1 - i); }
        for (int i = 0; i < 48; i++) { v[TE0 + i] = tab_extra(CE - i); v[TE1 + i] = tab_extra(CE + 1 - i); }
        for (int s = 0; s < 4; s++)
            for (int i = 0; i < T2C; i++) { v[T2B + s * T2S + i] = tab_2(s, C2 - i); v[T2B + s * T2S + T2C + i] = tab_2(s, C2 + 1 - i); }
        for (int s = 0; s < 2; s++)
            for (int i = 0; i < T3C; i++) { v[T3B + s * T3S + i] = tab_3(s, C3 - i); v[T3B + s * T3S + T3C + i] = tab_3(s, C3 + 1 - i); }
    }
};
__device__ const __align__(16) TabMap g_tabmap = TabMap();

__device__ __align__(1024) uint8_t g_kimg[65536];
__device__ __align__(1024) uint8_t g_vimg[65536 + 256];
__device__ __align__(1024) uint8_t g_oimg[16 * 131072];
__device__ float g_stat[2][128];
__device__ unsigned g_flag_kv[64];
__device__ unsigned g_flag_o[128];
__device__ unsigned g_epoch;
__device__ unsigned g_done;

__device__ __forceinline__ uint32_t smem_u32(const void* p) { return (uint32_t)__cvta_generic_to_shared(p); }
__device__ __forceinline__ void mbar_init(uint32_t bar, uint32_t cnt) { asm volatile("mbarrier.init.shared::cta.b64 [%0], %1;" :: "r"(bar), "r"(cnt) : "memory"); }
__device__ __forceinline__ void mbar_expect_tx(uint32_t bar, uint32_t bytes) {
    asm volatile("mbarrier.arrive.expect_tx.shared::cta.b64 _, [%0], %1;" :: "r"(bar), "r"(bytes) : "memory"); }
__device__ __forceinline__ void mbar_wait(uint32_t bar, uint32_t parity) {
    uint32_t ok = 0;
    for (int it = 0; it < (1 << 22) && !ok; it++) {
        asm volatile("{ .reg .pred p; mbarrier.try_wait.parity.shared::cta.b64 p, [%1], %2; selp.u32 %0, 1, 0, p; }"
                     : "=r"(ok) : "r"(bar), "r"(parity) : "memory");
    }
}
__device__ __forceinline__ void tma_2d(uint32_t dst, const CUtensorMap* map, int c0, int c1, uint32_t bar) {
    asm volatile("cp.async.bulk.tensor.2d.shared::cluster.global.mbarrier::complete_tx::bytes [%0], [%1, {%3, %4}], [%2];"
                 :: "r"(dst), "l"((uint64_t)map), "r"(bar), "r"(c0), "r"(c1) : "memory");
}
__device__ __forceinline__ void bulk_g2s(uint32_t dst, const void* src, uint32_t bytes, uint32_t bar) {
    asm volatile("cp.async.bulk.shared::cluster.global.mbarrier::complete_tx::bytes [%0], [%1], %2, [%3];"
                 :: "r"(dst), "l"((uint64_t)src), "r"(bytes), "r"(bar) : "memory");
}
__device__ __forceinline__ void fence_async_all() { asm volatile("fence.proxy.async;" ::: "memory"); }
__device__ __forceinline__ void fence_async_smem() { asm volatile("fence.proxy.async.shared::cta;" ::: "memory"); }
__device__ __forceinline__ unsigned ld_acquire(const unsigned* p) {
    unsigned v; asm volatile("ld.acquire.gpu.global.u32 %0, [%1];" : "=r"(v) : "l"(p) : "memory"); return v; }
__device__ __forceinline__ void st_release(unsigned* p, unsigned v) { asm volatile("st.release.gpu.global.u32 [%0], %1;" :: "l"(p), "r"(v) : "memory"); }
__device__ __forceinline__ void wait_flag(const unsigned* p, unsigned epoch) {
    for (int it = 0; it < (1 << 22); it++) { if (ld_acquire(p) == epoch) break; }
}
__device__ __forceinline__ void bar_sync(int id, int n) { asm volatile("bar.sync %0, %1;" :: "r"(id), "r"(n) : "memory"); }

__device__ __forceinline__ uint64_t make_desc(uint32_t saddr, uint32_t lbo, uint32_t sbo, uint32_t swz) {
    uint64_t d = 0;
    d |= (uint64_t)((saddr & 0x3FFFF) >> 4);
    d |= (uint64_t)((lbo >> 4) & 0x3FFF) << 16;
    d |= (uint64_t)((sbo >> 4) & 0x3FFF) << 32;
    d |= (uint64_t)swz << 62;
    return d;
}
__device__ __forceinline__ void wg_fence() { asm volatile("wgmma.fence.sync.aligned;" ::: "memory"); }
__device__ __forceinline__ void wg_commit() { asm volatile("wgmma.commit_group.sync.aligned;" ::: "memory"); }
template<int N> __device__ __forceinline__ void wg_wait() { asm volatile("wgmma.wait_group.sync.aligned %0;" :: "n"(N) : "memory"); }
#define A4(d, o) "+f"(d[o + 0]), "+f"(d[o + 1]), "+f"(d[o + 2]), "+f"(d[o + 3])
#define A16(d, o) A4(d, o), A4(d, o + 4), A4(d, o + 8), A4(d, o + 12)

__device__ __forceinline__ void wg_pv(float* d, const uint32_t* a, uint64_t desc) {
    asm volatile("wgmma.mma_async.sync.aligned.m64n24k16.f32.bf16.bf16 {%0,%1,%2,%3,%4,%5,%6,%7,%8,%9,%10,%11}, {%12,%13,%14,%15}, %16, 1, 1, 1, 1;"
                 : A4(d, 0), A4(d, 4), A4(d, 8) : "r"(a[0]), "r"(a[1]), "r"(a[2]), "r"(a[3]), "l"(desc));
}
__device__ __forceinline__ void wg_qk(float* d, const uint32_t* a, uint64_t desc) {
    asm volatile("wgmma.mma_async.sync.aligned.m64n64k16.f32.bf16.bf16 {%0,%1,%2,%3,%4,%5,%6,%7,%8,%9,%10,%11,%12,%13,%14,%15,%16,%17,%18,%19,%20,%21,%22,%23,%24,%25,%26,%27,%28,%29,%30,%31}, {%32,%33,%34,%35}, %36, 0, 1, 1, 0;"
                 : A16(d, 0), A16(d, 16) : "r"(a[0]), "r"(a[1]), "r"(a[2]), "r"(a[3]), "l"(desc));
}
__device__ __forceinline__ void wg_ss32(float* d, uint64_t da, uint64_t db) {
    asm volatile("wgmma.mma_async.sync.aligned.m64n32k16.f32.bf16.bf16 {%0,%1,%2,%3,%4,%5,%6,%7,%8,%9,%10,%11,%12,%13,%14,%15}, %16, %17, 1, 1, 1, 0, 1;"
                 : A16(d, 0) : "l"(da), "l"(db));
}
__device__ __forceinline__ void wg_ss16(float* d, uint64_t da, uint64_t db) {
    asm volatile("wgmma.mma_async.sync.aligned.m64n16k16.f32.bf16.bf16 {%0,%1,%2,%3,%4,%5,%6,%7}, %8, %9, 1, 1, 1, 0, 1;"
                 : A4(d, 0), A4(d, 4) : "l"(da), "l"(db));
}
template<int N> __device__ __forceinline__ void fence_regs(float* r) {
    #pragma unroll
    for (int i = 0; i < N; i++) asm volatile("" : "+f"(r[i]) :: "memory");
}
__device__ __forceinline__ void mma_bf16(float* d, uint32_t a0, uint32_t a1, uint32_t a2, uint32_t a3, uint32_t b0, uint32_t b1) {
    asm volatile("mma.sync.aligned.m16n8k16.row.col.f32.bf16.bf16.f32 {%0,%1,%2,%3}, {%4,%5,%6,%7}, {%8,%9}, {%0,%1,%2,%3};"
                 : "+f"(d[0]), "+f"(d[1]), "+f"(d[2]), "+f"(d[3]) : "r"(a0), "r"(a1), "r"(a2), "r"(a3), "r"(b0), "r"(b1));
}
__device__ __forceinline__ void mma_f16(float* d, const uint32_t* a, uint32_t b0, uint32_t b1) {
    asm volatile("mma.sync.aligned.m16n8k16.row.col.f32.f16.f16.f32 {%0,%1,%2,%3}, {%4,%5,%6,%7}, {%8,%9}, {%0,%1,%2,%3};"
                 : "+f"(d[0]), "+f"(d[1]), "+f"(d[2]), "+f"(d[3]) : "r"(a[0]), "r"(a[1]), "r"(a[2]), "r"(a[3]), "r"(b0), "r"(b1));
}
__device__ __forceinline__ void ldsm4(uint32_t* r, uint32_t addr) {
    asm volatile("ldmatrix.sync.aligned.m8n8.x4.shared.b16 {%0,%1,%2,%3}, [%4];" : "=r"(r[0]), "=r"(r[1]), "=r"(r[2]), "=r"(r[3]) : "r"(addr) : "memory");
}
__device__ __forceinline__ void ldsm4t(uint32_t* r, uint32_t addr) {
    asm volatile("ldmatrix.sync.aligned.m8n8.x4.trans.shared.b16 {%0,%1,%2,%3}, [%4];" : "=r"(r[0]), "=r"(r[1]), "=r"(r[2]), "=r"(r[3]) : "r"(addr) : "memory");
}
__device__ __forceinline__ uint32_t lds32(uint32_t addr) { uint32_t v; asm volatile("ld.shared.u32 %0, [%1];" : "=r"(v) : "r"(addr) : "memory"); return v; }
__device__ __forceinline__ float ex2f(float x) { float r; asm("ex2.approx.ftz.f32 %0, %1;" : "=f"(r) : "f"(x)); return r; }
__device__ __forceinline__ uint32_t pack_bf16(float lo, float hi) { uint32_t r; asm("cvt.rn.bf16x2.f32 %0, %1, %2;" : "=r"(r) : "f"(hi), "f"(lo)); return r; }
__device__ __forceinline__ uint32_t pack_f16(float lo, float hi) { uint32_t r; asm("cvt.rn.f16x2.f32 %0, %1, %2;" : "=r"(r) : "f"(hi), "f"(lo)); return r; }
__device__ __forceinline__ float bf_lo(uint32_t v) { return __uint_as_float(v << 16); }
__device__ __forceinline__ float bf_hi(uint32_t v) { return __uint_as_float(v & 0xFFFF0000u); }
__device__ __forceinline__ float bf_round(float x) { return __bfloat162float(__float2bfloat16_rn(x)); }

__device__ __forceinline__ uint32_t exp_mufu(float x0, float x1) { return pack_bf16(ex2f(x0), ex2f(x1)); }
#define SW_MAGIC (256.0f + 127.0f - 0.598938f)
__device__ __forceinline__ uint32_t exp_sw(float x0, float x1, uint32_t cA, uint32_t cB) {
    float t0 = x0 + SW_MAGIC, t1 = x1 + SW_MAGIC;
    uint32_t L, mh, ec, r;
    asm("prmt.b32 %0, %1, %2, 0x6521;" : "=r"(L) : "r"(__float_as_uint(t0)), "r"(__float_as_uint(t1)));
    asm("lop3.b32 %0, %1, 0x007F007F, %2, 0xEA;" : "=r"(mh) : "r"(L), "r"(cA));
    asm("lop3.b32 %0, %1, 0x7F807F80, %2, 0xEA;" : "=r"(ec) : "r"(L), "r"(cB));
    asm("fma.rn.bf16x2 %0, %1, %2, %3;" : "=r"(r) : "r"(L), "r"(mh), "r"(ec));
    return r;
}
constexpr uint32_t MUFU_MASK = 0x4949;

struct cf { float x, y; };
__device__ __forceinline__ cf cmul(cf a, cf b) { cf r; r.x = a.x * b.x - a.y * b.y; r.y = a.x * b.y + a.y * b.x; return r; }
__device__ __forceinline__ cf cexp_p(float a2, float b, float p) {
    float e = ex2f(a2 * p);
    float ph = b * p;
    ph -= (ph + 12582912.0f) - 12582912.0f;
    float ang = ph * 6.283185307f;
    cf r; r.x = e * __cosf(ang); r.y = e * __sinf(ang);
    return r;
}
__device__ __forceinline__ uint32_t h2_cmul(uint32_t w, uint32_t wsw, uint32_t e) {
    __half2 hw = *(__half2*)&w, hs = *(__half2*)&wsw, he = *(__half2*)&e;
    __half2 r = __hfma2(hs, __high2half2(he), __hmul2(hw, __low2half2(he)));
    return *(uint32_t*)&r;
}

struct Params {
    const __nv_bfloat16 *u, *lar, *aim, *cre, *cim, *logdt, *dskip;
    __nv_bfloat16* out;
};

__global__ void __launch_bounds__(NTHR, 1)
fused_kernel(const __grid_constant__ CUtensorMap tm_x, const __grid_constant__ CUtensorMap tm_wq,
             const __grid_constant__ CUtensorMap tm_wo, const __grid_constant__ CUtensorMap tm_wk,
             const __grid_constant__ CUtensorMap tm_wv, const Params P) {
    extern __shared__ uint8_t smem_raw[];
    const uint32_t sb = (smem_u32(smem_raw) + 1023u) & ~1023u;
    uint8_t* sp = smem_raw + (sb - smem_u32(smem_raw));

    const int tid = threadIdx.x, warp = tid >> 5, lane = tid & 31, wg = tid >> 7, wiw = warp & 3;
    const int g = lane >> 2, t = lane & 3;
    const int qb = blockIdx.x >> 3, hg = blockIdx.x & 7;
    const int d0 = blockIdx.x * 4;
    const int rowhalf = wg & 1, nh = wg >> 1;
    const bool kv_cta = hg < 4;
    const int kv_sel = hg >> 1;
    const bool kv_wg = kv_cta && (wg == (hg & 1));

    const uint32_t bar_x = sb + SM_BAR, bar_kv = bar_x + 8, bar_wo = bar_x + 16, bar_o = bar_x + 32;
    float* s_misc = (float*)(sp + SM_BAR + 128);
    const unsigned epoch = *(volatile unsigned*)&g_epoch + 1u;

    if (tid == 0) {
        mbar_init(bar_x, 1); mbar_init(bar_kv, 1); mbar_init(bar_wo, 1);
        for (int i = 0; i < 8; i++) mbar_init(bar_o + 8 * i, 1);
        asm volatile("fence.mbarrier_init.release.cluster;" ::: "memory");
        fence_async_smem();
        mbar_expect_tx(bar_x, 131072 + 65536 + (kv_cta ? 16384 : 0));
        for (int b = 0; b < 8; b++) tma_2d(sb + SM_A + b * 16384, &tm_x, b * 64, qb * 128, bar_x);
        for (int b = 0; b < 2; b++) tma_2d(sb + SM_B + b * 32768, &tm_wq, hg * 64, b * 256, bar_x);
        if (kv_cta) {
            const CUtensorMap* m = kv_sel ? &tm_wv : &tm_wk;
            for (int b = 0; b < 4; b++) tma_2d(sb + SM_C + b * 4096, m, (b >> 1) * 8, (b & 1) * 256, bar_x);
        }
    }

    uint2 ureg[4];
    #pragma unroll
    for (int i = 0; i < 2; i++) {
        const int l = 2 * (tid + 512 * i);
        ureg[2 * i] = __ldg((const uint2*)(P.u + (size_t)l * 512 + d0));
        ureg[2 * i + 1] = __ldg((const uint2*)(P.u + (size_t)(l + 1) * 512 + d0));
    }

    {
        const int c = warp >> 2, d = d0 + c, n = (warp & 3) * 32 + lane;
        const float dt = bf_round(expf(__bfloat162float(P.logdt[d])));
        const float are = -bf_round(expf(__bfloat162float(P.lar[d * 128 + n]))) * dt;
        const float aim = __bfloat162float(P.aim[d * 128 + n]) * dt;
        float cr = 2.0f * (__bfloat162float(P.cre[d * 128 + n]) * dt);
        float ci = 2.0f * (__bfloat162float(P.cim[d * 128 + n]) * dt);
        const float a2 = are * 1.4426950408889634f, bb = aim * 0.15915494309189535f;
        float m = fmaxf(fabsf(cr), fabsf(ci));
        #pragma unroll
        for (int o = 16; o; o >>= 1) m = fmaxf(m, __shfl_xor_sync(0xffffffffu, m, o));
        int ebits = (__float_as_uint(m) >> 23) & 0xFF;
        ebits = min(max(ebits, 2), 250);
        const float scale = __uint_as_float((uint32_t)(ebits + 1) << 23);
        const float iscale = __uint_as_float((uint32_t)(253 - ebits) << 23);
        cf cc; cc.x = cr * iscale; cc.y = ci * iscale;

        const uint32_t stg = sb + SM_D + warp * 1024;
        uint4* stp = (uint4*)(sp + SM_D + warp * 1024 + lane * 32);
        const uint32_t fa = stg + t * 32 + g * 4;

        uint32_t af[4][2][4];
        cf E256;
        {
            const cf E8 = cexp_p(a2, bb, 8.0f);
            uint32_t w[8];
            cf cur; cur.x = 1.0f; cur.y = 0.0f;
            w[0] = pack_f16(1.0f, 0.0f);
            cur = E8; w[1] = pack_f16(cur.x, cur.y);
            #pragma unroll
            for (int i = 2; i < 8; i++) { cur = cmul(cur, E8); w[i] = pack_f16(cur.x, cur.y); }
            stp[0] = make_uint4(w[0], w[1], w[2], w[3]);
            stp[1] = make_uint4(w[4], w[5], w[6], w[7]);
            const cf E64 = cexp_p(a2, bb, 64.0f);
            const cf E128 = cmul(E64, E64), E192 = cmul(E128, E64);
            E256 = cexp_p(a2, bb, 256.0f);
            const uint32_t e1 = pack_f16(E64.x, E64.y), e2 = pack_f16(E128.x, E128.y), e3 = pack_f16(E192.x, E192.y);
            __syncwarp();
            #pragma unroll
            for (int s = 0; s < 4; s++) {
                #pragma unroll
                for (int hh = 0; hh < 2; hh++) {
                    const uint32_t w0 = lds32(fa + s * 256 + hh * 128);
                    const uint32_t wsw = __byte_perm(w0, 0, 0x1032) ^ 0x00008000u;
                    const int src = 8 * s + t + 4 * hh;
                    const uint32_t f1 = __shfl_sync(0xffffffffu, e1, src), f2 = __shfl_sync(0xffffffffu, e2, src), f3 = __shfl_sync(0xffffffffu, e3, src);
                    af[s][0][2 * hh] = w0;
                    af[s][0][2 * hh + 1] = h2_cmul(w0, wsw, f1);
                    af[s][1][2 * hh] = h2_cmul(w0, wsw, f2);
                    af[s][1][2 * hh + 1] = h2_cmul(w0, wsw, f3);
                }
            }
            __syncwarp();
        }
        float acc[2][3][4];
        #pragma unroll
        for (int i = 0; i < 24; i++) (&acc[0][0][0])[i] = 0.0f;
        const cf E1 = cexp_p(a2, bb, 1.0f);
        const cf E2 = cmul(E1, E1), E4 = cmul(E2, E2);
        cf X512;
        #pragma unroll
        for (int nt = 0; nt < 3; nt++) {
            uint32_t xv[8];
            if (nt == 0) {
                cf cur = cc;
                xv[0] = pack_f16(cur.x, -cur.y);
                #pragma unroll
                for (int i = 1; i < 8; i++) { cur = cmul(cur, E1); xv[i] = pack_f16(cur.x, -cur.y); }
            } else if (nt == 1) {
                cf cur = cmul(cc, E256);
                X512 = cmul(cur, E256);
                xv[0] = pack_f16(cur.x, -cur.y);
                #pragma unroll
                for (int i = 1; i < 4; i++) { cur = cmul(cur, E2); xv[i] = pack_f16(cur.x, -cur.y); }
                cur = cmul(X512, E4);
                xv[4] = pack_f16(X512.x, -X512.y); xv[5] = pack_f16(cur.x, -cur.y);
                X512 = cmul(X512, E256);
                cur = cmul(X512, E4);
                xv[6] = pack_f16(X512.x, -X512.y); xv[7] = pack_f16(cur.x, -cur.y);
            } else {
                cf cur = X512;
                #pragma unroll
                for (int i = 0; i < 5; i++) { cur = cmul(cur, E256); xv[i] = pack_f16(cur.x, -cur.y); }
                xv[5] = 0; xv[6] = 0; xv[7] = 0;
            }
            stp[0] = make_uint4(xv[0], xv[1], xv[2], xv[3]);
            stp[1] = make_uint4(xv[4], xv[5], xv[6], xv[7]);
            __syncwarp();
            #pragma unroll
            for (int s = 0; s < 4; s++) {
                const uint32_t b0 = lds32(fa + s * 256), b1 = lds32(fa + s * 256 + 128);
                mma_f16(acc[0][nt], af[s][0], b0, b1);
                mma_f16(acc[1][nt], af[s][1], b0, b1);
            }
            __syncwarp();
        }
        float* kc = (float*)(sp + SM_D + c * 4096);
        bar_sync(1 + c, 128);
        #pragma unroll 1
        for (int step = 0; step < 4; step++) {
            if ((warp & 3) == step) {
                #pragma unroll
                for (int mt = 0; mt < 2; mt++)
                    #pragma unroll
                    for (int nt = 0; nt < 3; nt++)
                        #pragma unroll
                        for (int hh = 0; hh < 2; hh++) {
                            float2* p = (float2*)(kc + (mt * 16 + hh * 8 + g) * 24 + nt * 8 + 2 * t);
                            float2 v = make_float2(acc[mt][nt][2 * hh] * scale, acc[mt][nt][2 * hh + 1] * scale);
                            if (step) { float2 o = *p; v.x += o.x; v.y += o.y; }
                            *p = v;
                        }
            }
            bar_sync(1 + c, 128);
        }
    }

    uint32_t q[2][4];
    {
        __syncthreads();
        mbar_wait(bar_x, 0);
        float acc[16], akv[8];
        #pragma unroll
        for (int i = 0; i < 16; i++) acc[i] = 0.0f;
        #pragma unroll
        for (int i = 0; i < 8; i++) akv[i] = 0.0f;
        const uint64_t dA = make_desc(sb + SM_A + rowhalf * 8192, 16, 1024, 1);
        const uint64_t dB = make_desc(sb + SM_B + nh * 64, 16, 1024, 1);
        const uint64_t dC = make_desc(sb + SM_C, 128, 8192, 0);
        fence_regs<16>(acc);
        fence_regs<8>(akv);
        if (kv_wg) {
            wg_fence();
            #pragma unroll
            for (int ks = 0; ks < 32; ks++) wg_ss16(akv, dA + (ks >> 2) * 1024 + (ks & 3) * 2, dC + ks * 16);
            wg_commit();
            wg_wait<0>();
            fence_regs<8>(akv);
            const int key = qb * 128 + rowhalf * 64 + wiw * 16 + g;
            uint32_t pk[4];
            #pragma unroll
            for (int i = 0; i < 4; i++) pk[i] = pack_bf16(akv[2 * i], akv[2 * i + 1]);
            float st;
            if (kv_sel == 0) {
                uint8_t* b = g_kimg + (key >> 3) * 256 + (key & 7) * 16 + 4 * t;
                *(uint32_t*)(b) = pk[0]; *(uint32_t*)(b + 256) = pk[1]; *(uint32_t*)(b + 128) = pk[2]; *(uint32_t*)(b + 384) = pk[3];
                float n0 = bf_lo(pk[0]) * bf_lo(pk[0]) + bf_hi(pk[0]) * bf_hi(pk[0]) + bf_lo(pk[2]) * bf_lo(pk[2]) + bf_hi(pk[2]) * bf_hi(pk[2]);
                float n1 = bf_lo(pk[1]) * bf_lo(pk[1]) + bf_hi(pk[1]) * bf_hi(pk[1]) + bf_lo(pk[3]) * bf_lo(pk[3]) + bf_hi(pk[3]) * bf_hi(pk[3]);
                n0 += __shfl_xor_sync(0xffffffffu, n0, 1); n0 += __shfl_xor_sync(0xffffffffu, n0, 2);
                n1 += __shfl_xor_sync(0xffffffffu, n1, 1); n1 += __shfl_xor_sync(0xffffffffu, n1, 2);
                st = (n0 != n0 || n1 != n1) ? __int_as_float(0x7f800000) : fmaxf(n0, n1);
            } else {
                const int s = key >> 4;
                uint8_t* lo = g_vimg + s * 256 + g * 16 + 4 * t;
                uint8_t* hi = g_vimg + 33024 + (127 - s) * 256 + g * 16 + 4 * t;
                *(uint32_t*)(lo) = pk[0]; *(uint32_t*)(lo + 128) = pk[1]; *(uint32_t*)(hi) = pk[2]; *(uint32_t*)(hi + 128) = pk[3];
                st = 0.0f;
                #pragma unroll
                for (int i = 0; i < 4; i++) {
                    float a = fabsf(bf_lo(pk[i])), b = fabsf(bf_hi(pk[i]));
                    st = (a != a || b != b) ? __int_as_float(0x7f800000) : fmaxf(st, fmaxf(a, b));
                }
            }
            #pragma unroll
            for (int o = 16; o; o >>= 1) st = fmaxf(st, __shfl_xor_sync(0xffffffffu, st, o));
            if (lane == 0) g_stat[kv_sel][(qb * 2 + rowhalf) * 4 + wiw] = st;
            __threadfence();
            bar_sync(5, 128);
            if ((tid & 127) == 0) st_release(&g_flag_kv[(qb * 2 + rowhalf) * 2 + kv_sel], epoch);
        }
        wg_fence();
        #pragma unroll
        for (int ks = 0; ks < 32; ks++) wg_ss32(acc, dA + (ks >> 2) * 1024 + (ks & 3) * 2, dB + ks * 128);
        wg_commit();
        wg_wait<0>();
        fence_regs<16>(acc);
        const float QS = 0.25f * 1.4426950408889634f;
        float qm = 0.0f;
        #pragma unroll
        for (int i = 0; i < 2; i++) {
            #pragma unroll
            for (int j = 0; j < 4; j++) q[i][j] = pack_bf16(acc[8 * i + 2 * j] * QS, acc[8 * i + 2 * j + 1] * QS);
            float n0 = bf_lo(q[i][0]) * bf_lo(q[i][0]) + bf_hi(q[i][0]) * bf_hi(q[i][0]) + bf_lo(q[i][2]) * bf_lo(q[i][2]) + bf_hi(q[i][2]) * bf_hi(q[i][2]);
            float n1 = bf_lo(q[i][1]) * bf_lo(q[i][1]) + bf_hi(q[i][1]) * bf_hi(q[i][1]) + bf_lo(q[i][3]) * bf_lo(q[i][3]) + bf_hi(q[i][3]) * bf_hi(q[i][3]);
            n0 += __shfl_xor_sync(0xffffffffu, n0, 1); n0 += __shfl_xor_sync(0xffffffffu, n0, 2);
            n1 += __shfl_xor_sync(0xffffffffu, n1, 1); n1 += __shfl_xor_sync(0xffffffffu, n1, 2);
            qm = (n0 != n0 || n1 != n1) ? __int_as_float(0x7f800000) : fmaxf(qm, fmaxf(n0, n1));
        }
        #pragma unroll
        for (int o = 16; o; o >>= 1) qm = fmaxf(qm, __shfl_xor_sync(0xffffffffu, qm, o));
        if (lane == 0) s_misc[warp] = qm;
    }
    __syncthreads();

    uint8_t* sB = sp + SM_B;
    const uint32_t sBa = sb + SM_B;
    {
        #pragma unroll
        for (int i = 0; i < 2; i++) {
            const int l = 2 * (tid + 512 * i);
            const uint2 r0 = ureg[2 * i], r1 = ureg[2 * i + 1];
            uint32_t* dst = (uint32_t*)(sB + S_U + (PADU + l) * 2);
            dst[0] = __byte_perm(r0.x, r1.x, 0x5410);
            dst[ULEN / 2] = __byte_perm(r0.x, r1.x, 0x7632);
            dst[ULEN] = __byte_perm(r0.y, r1.y, 0x5410);
            dst[3 * ULEN / 2] = __byte_perm(r0.y, r1.y, 0x7632);
        }
        if (tid < 4 * (PADU / 8)) {
            const int c = tid / (PADU / 8), i = tid % (PADU / 8);
            *(uint4*)(sB + S_U + c * ULEN * 2 + i * 16) = make_uint4(0, 0, 0, 0);
        }
        const int c = tid >> 7;
        const float* kc = (const float*)(sp + SM_D + c * 4096);
        uint32_t* tab = (uint32_t*)(sB + S_TAB + c * TABN * 2);
        const uint32_t* map = (const uint32_t*)g_tabmap.v;
        for (int w = tid & 127; w < TABN / 2; w += 128) {
            const uint32_t mp = __ldg(map + w);
            tab[w] = pack_bf16(kc[mp & 0xFFFF], kc[mp >> 16]);
        }
        if (tid < 64) *(uint32_t*)(sp + SM_V + 32768 + tid * 4) = 0x3F803F80u;
        fence_async_smem();
    }
    if (warp == 0) {
        wait_flag(&g_flag_kv[lane], epoch);
        wait_flag(&g_flag_kv[lane + 32], epoch);
        __syncwarp();
        if (lane == 0) {
            fence_async_all();
            mbar_expect_tx(bar_kv, 131072);
            for (int i = 0; i < 4; i++) bulk_g2s(sb + SM_K + i * 16384, g_kimg + i * 16384, 16384, bar_kv);
            for (int i = 0; i < 2; i++) bulk_g2s(sb + SM_V + i * 16384, g_vimg + i * 16384, 16384, bar_kv);
            for (int i = 0; i < 2; i++) bulk_g2s(sb + SM_V + 33024 + i * 16384, g_vimg + 33024 + i * 16384, 16384, bar_kv);
        }
        float km = 0.0f, vm = 0.0f;
        #pragma unroll
        for (int i = 0; i < 4; i++) {
            km = fmaxf(km, __ldcg(&g_stat[0][lane * 4 + i]));
            vm = fmaxf(vm, __ldcg(&g_stat[1][lane * 4 + i]));
        }
        #pragma unroll
        for (int o = 16; o; o >>= 1) { km = fmaxf(km, __shfl_xor_sync(0xffffffffu, km, o)); vm = fmaxf(vm, __shfl_xor_sync(0xffffffffu, vm, o)); }
        if (lane == 0) { s_misc[16] = km; s_misc[17] = vm; }
    }
    __syncthreads();
    for (int task = tid; task < 4 * 194; task += NTHR) {
        const int c = task / 194, i = task % 194;
        const int m0 = 8 * i - WPAD;
        const uint4* src = (const uint4*)(sB + S_U + c * ULEN * 2 + (PADU + m0 - 8) * 2);
        const uint4 v0 = src[0], v1 = src[1], v2 = src[2];
        float x[24];
        const uint32_t vv[12] = {v0.x, v0.y, v0.z, v0.w, v1.x, v1.y, v1.z, v1.w, v2.x, v2.y, v2.z, v2.w};
        #pragma unroll
        for (int k = 0; k < 12; k++) { x[2 * k] = bf_lo(vv[k]); x[2 * k + 1] = bf_hi(vv[k]); }
        float w3[12], w5[8];
        #pragma unroll
        for (int e = 0; e < 12; e++) w3[e] = (x[3 + e] + x[4 + e]) + x[5 + e];
        #pragma unroll
        for (int e = 0; e < 8; e++) w5[e] = w3[4 + e] + (x[6 + e] + x[10 + e]);
        *(uint4*)(sB + S_W3 + c * W2LEN * 2 + i * 16) = make_uint4(pack_bf16(w3[0], w3[1]), pack_bf16(w3[2], w3[3]), pack_bf16(w3[4], w3[5]), pack_bf16(w3[6], w3[7]));
        *(uint4*)(sB + S_W5 + c * W2LEN * 2 + i * 16) = make_uint4(pack_bf16(w5[0], w5[1]), pack_bf16(w5[2], w5[3]), pack_bf16(w5[4], w5[5]), pack_bf16(w5[6], w5[7]));
        if (i < 130) {
            float w7[8], w9[8];
            #pragma unroll
            for (int e = 0; e < 8; e++) { w7[e] = w5[e] + (x[5 + e] + x[11 + e]); w9[e] = w7[e] + (x[4 + e] + x[12 + e]); }
            *(uint4*)(sB + S_W7 + c * W3LEN * 2 + i * 16) = make_uint4(pack_bf16(w7[0], w7[1]), pack_bf16(w7[2], w7[3]), pack_bf16(w7[4], w7[5]), pack_bf16(w7[6], w7[7]));
            *(uint4*)(sB + S_W9 + c * W3LEN * 2 + i * 16) = make_uint4(pack_bf16(w9[0], w9[1]), pack_bf16(w9[2], w9[3]), pack_bf16(w9[4], w9[5]), pack_bf16(w9[6], w9[7]));
        }
    }
    __syncthreads();

    {
        const int c = warp >> 2, grp = (warp + c) & 3;
        float acc[4][4];
        #pragma unroll
        for (int i = 0; i < 16; i++) (&acc[0][0])[i] = 0.0f;
        const uint32_t tabc = sBa + S_TAB + c * TABN * 2;
        const int e2 = (g - 2 * t) * 2;
        const uint32_t tD = tabc + ((g & 1) ? (TD1 + CD + 1) : (TD0 + CD)) * 2 - e2;
        const uint32_t tE = tabc + ((g & 1) ? (TE1 + CE + 1) : (TE0 + CE)) * 2 - e2;
        const uint32_t t2 = tabc + (T2B + ((g & 1) ? (T2C + C2 + 1) : C2)) * 2 - e2;
        const uint32_t t3 = tabc + (T3B + ((g & 1) ? (T3C + C3 + 1) : C3)) * 2 - e2;
        const int mi = lane >> 3, r8 = lane & 7;
        const uint32_t ub = sBa + S_U + c * ULEN * 2 + (PADU + 16 * (8 * (mi >> 1) + r8) + 8 * (mi & 1)) * 2 + (4 * grp - 4) * 256;
        #pragma unroll 1
        for (int rho = 0; rho < 8; rho++) {
            uint32_t R[5][3];
            #pragma unroll
            for (int qq = 0; qq < 5; qq++) {
                if (qq < 4 || rho < 2) {
                    const uint32_t a = tD - 32 * (rho + 8 * qq);
                    R[qq][0] = lds32(a + 16); R[qq][1] = lds32(a); R[qq][2] = lds32(a - 16);
                } else { R[qq][0] = 0; R[qq][1] = 0; R[qq][2] = 0; }
            }
            #pragma unroll
            for (int jp = 0; jp < 4; jp++) {
                if (grp == 0 && (jp == 0 || (jp == 1 && rho > 0))) continue;
                if (jp == 0 && rho >= 2) {
                    uint32_t b[4];
                    ldsm4(b, ub + jp * 512 - rho * 32);
                    mma_bf16(acc[0], R[3][1], R[3][2], R[3][0], R[3][1], b[2], b[3]);
                    continue;
                }
                uint32_t b[4];
                ldsm4(b, ub + jp * 512 - rho * 32);
                #pragma unroll
                for (int hh = 0; hh < 2; hh++) {
                    #pragma unroll
                    for (int qq = 0; qq < 5; qq++) {
                        const int jr = 2 * jp + hh + qq - 4;
                        if (jr >= 0 && jr < 4) {
                            if (qq < 4 || rho < 2) mma_bf16(acc[jr], R[qq][1], R[qq][2], R[qq][0], R[qq][1], b[2 * hh], b[2 * hh + 1]);
                        }
                    }
                }
            }
        }
        if (grp >= 2) {
            uint32_t R[5];
            #pragma unroll
            for (int i = 0; i < 5; i++) R[i] = lds32(tE - 16 * (127 + i));
            #pragma unroll
            for (int kk = 0; kk < 2; kk++) {
                #pragma unroll
                for (int jp = 0; jp < 2; jp++) {
                    uint32_t b[4];
                    ldsm4(b, ub + (4 + 2 * jp) * 256 - (64 + kk) * 32);
                    mma_bf16(acc[2 * jp], R[2 * kk + 1], R[2 * kk + 2], R[2 * kk], R[2 * kk + 1], b[0], b[1]);
                    mma_bf16(acc[2 * jp + 1], R[2 * kk + 1], R[2 * kk + 2], R[2 * kk], R[2 * kk + 1], b[2], b[3]);
                }
            }
        }
        const uint32_t soff = (WPAD + 16 * (8 * (mi >> 1) + r8) + 8 * (mi & 1)) * 2 + grp * 1024;
        if (grp >= 1) {
            #pragma unroll 1
            for (int s = 0; s < 4; s++) {
                const uint32_t sig = sBa + ((s & 1) ? S_W3 : S_W5) + c * W2LEN * 2 + soff - ((s == 0) ? 32 : (s == 1) ? 0 : 16);
                uint32_t R[7];
                #pragma unroll
                for (int i = 0; i < 7; i++) R[i] = lds32(t2 + s * (T2S * 2) - 16 * (3 + i));
                #pragma unroll
                for (int bb = 1; bb <= 4; bb++) {
                    if (2 * grp - bb < 0) continue;
                    uint32_t a[4];
                    ldsm4t(a, sig - bb * 512);
                    #pragma unroll
                    for (int jj = 0; jj < 4; jj++) {
                        const int h = jj + 2 * bb;
                        if (h >= 4 && h <= 9) mma_bf16(acc[jj], a[0], a[1], a[2], a[3], R[h - 3], R[h - 4]);
                    }
                }
            }
        }
        if (grp >= 2) {
            #pragma unroll 1
            for (int s = 0; s < 2; s++) {
                const uint32_t sig = sBa + (s ? S_W7 : S_W9) + c * W3LEN * 2 + soff - (s ? 16 : 32);
                uint32_t R[9];
                #pragma unroll
                for (int i = 0; i < 9; i++) R[i] = lds32(t3 + s * (T3S * 2) - 16 * (7 + i));
                #pragma unroll
                for (int bb = 3; bb <= 6; bb++) {
                    if (2 * grp - bb < 0) continue;
                    uint32_t a[4];
                    ldsm4t(a, sig - bb * 512);
                    #pragma unroll
                    for (int jj = 0; jj < 4; jj++) {
                        const int h = jj + 2 * bb;
                        if (h >= 8 && h <= 15) mma_bf16(acc[jj], a[0], a[1], a[2], a[3], R[h - 7], R[h - 8]);
                    }
                }
            }
        }
        __nv_bfloat16* ys = (__nv_bfloat16*)(sB + S_Y + c * 4096);
        #pragma unroll
        for (int jj = 0; jj < 4; jj++) {
            const int A = 8 * (4 * grp + jj) + 2 * t;
            ys[16 * A + g] = __float2bfloat16_rn(acc[jj][0]);
            ys[16 * A + 16 + g] = __float2bfloat16_rn(acc[jj][1]);
            ys[16 * A + g + 8] = __float2bfloat16_rn(acc[jj][2]);
            ys[16 * A + 16 + g + 8] = __float2bfloat16_rn(acc[jj][3]);
        }
    }
    __syncthreads();
    {
        const uint2 dsk = __ldg((const uint2*)(P.dskip + d0));
        uint32_t dd[4] = {__byte_perm(dsk.x, 0, 0x1010), __byte_perm(dsk.x, 0, 0x3232), __byte_perm(dsk.y, 0, 0x1010), __byte_perm(dsk.y, 0, 0x3232)};
        #pragma unroll
        for (int i = 0; i < 2; i++) {
            const int l = 2 * (tid + 512 * i);
            uint32_t r[4];
            #pragma unroll
            for (int c = 0; c < 4; c++) {
                const uint32_t y2 = *(const uint32_t*)(sB + S_Y + c * 4096 + l * 2);
                const uint32_t u2 = *(const uint32_t*)(sB + S_U + c * ULEN * 2 + (PADU + l) * 2);
                __nv_bfloat162 pr = __hmul2(*(const __nv_bfloat162*)&u2, *(const __nv_bfloat162*)&dd[c]);
                __nv_bfloat162 sm = __hadd2(*(const __nv_bfloat162*)&y2, pr);
                r[c] = *(uint32_t*)&sm;
            }
            *(uint2*)(P.out + (size_t)l * 1024 + 512 + d0) = make_uint2(__byte_perm(r[0], r[1], 0x5410), __byte_perm(r[2], r[3], 0x5410));
            *(uint2*)(P.out + (size_t)(l + 1) * 1024 + 512 + d0) = make_uint2(__byte_perm(r[0], r[1], 0x7632), __byte_perm(r[2], r[3], 0x7632));
        }
    }
    __syncthreads();
    if (tid == 0) {
        fence_async_smem();
        mbar_expect_tx(bar_wo, 65536);
        for (int b = 0; b < 2; b++) tma_2d(sb + SM_B + b * 32768, &tm_wo, hg * 64, b * 256, bar_wo);
    }

    {
        float qm = 0.0f;
        #pragma unroll
        for (int i = 0; i < 16; i++) qm = fmaxf(qm, s_misc[i]);
        const float vm = s_misc[17];
        const bool fast = (qm * s_misc[16] <= 60.0f * 60.0f) && (vm <= 1.0e12f) && (vm >= 1.0e-12f || vm == 0.0f);

        mbar_wait(bar_kv, 0);
        const uint64_t dVstep = 16ull - (16ull << 32);
        uint64_t dK = make_desc(sb + SM_K, 128, 256, 0);
        uint64_t dV = make_desc(sb + SM_V, 128, 32768, 0);
        float o[2][12], s[32];
        uint32_t p[16];
        #pragma unroll
        for (int i = 0; i < 12; i++) { o[0][i] = 0.0f; o[1][i] = 0.0f; }
        #pragma unroll
        for (int i = 0; i < 32; i++) s[i] = 0.0f;
        if (fast) {
            uint32_t cA = 0xBF00BF00u, cB = 0x00030003u;
            asm volatile("" : "+r"(cA), "+r"(cB));
            #pragma unroll 1
            for (int c = 0; c < SEQ / 128; c++) {
                wg_fence();
                wg_qk(s, q[0], dK);
                wg_commit();
                #pragma unroll
                for (int u = 0; u < 4; u++) {
                    wg_wait<0>();
                    fence_regs<32>(s);
                    #pragma unroll
                    for (int i = 0; i < 16; i++) {
                        if ((MUFU_MASK >> i) & 1) p[i] = exp_mufu(s[2 * i], s[2 * i + 1]);
                        else p[i] = exp_sw(s[2 * i], s[2 * i + 1], cA, cB);
                    }
                    wg_fence();
                    if (u + 1 < 4) wg_qk(s, q[(u + 1) & 1], dK + ((u + 1) >> 1) * 128);
                    #pragma unroll
                    for (int kk = 0; kk < 4; kk++) wg_pv(o[u & 1], p + 4 * kk, dV + ((u >> 1) * 4 + kk) * dVstep);
                    wg_commit();
                }
                dK += 256;
                dV += 8 * dVstep;
            }
            wg_wait<0>();
        } else {
            float mx[2][2] = {{-INFINITY, -INFINITY}, {-INFINITY, -INFINITY}};
            #pragma unroll 1
            for (int c = 0; c < SEQ / 64; c++) {
                #pragma unroll
                for (int i = 0; i < 2; i++) {
                    wg_fence();
                    wg_qk(s, q[i], dK);
                    wg_commit();
                    wg_wait<0>();
                    fence_regs<32>(s);
                    fence_regs<12>(o[i]);
                    float m0 = mx[i][0], m1 = mx[i][1];
                    #pragma unroll
                    for (int j = 0; j < 8; j++) {
                        m0 = fmaxf(m0, fmaxf(s[4 * j], s[4 * j + 1]));
                        m1 = fmaxf(m1, fmaxf(s[4 * j + 2], s[4 * j + 3]));
                    }
                    m0 = fmaxf(m0, __shfl_xor_sync(0xffffffffu, m0, 1)); m0 = fmaxf(m0, __shfl_xor_sync(0xffffffffu, m0, 2));
                    m1 = fmaxf(m1, __shfl_xor_sync(0xffffffffu, m1, 1)); m1 = fmaxf(m1, __shfl_xor_sync(0xffffffffu, m1, 2));
                    const float c0 = ex2f(mx[i][0] - m0), c1 = ex2f(mx[i][1] - m1);
                    mx[i][0] = m0; mx[i][1] = m1;
                    #pragma unroll
                    for (int j = 0; j < 3; j++) { o[i][4 * j] *= c0; o[i][4 * j + 1] *= c0; o[i][4 * j + 2] *= c1; o[i][4 * j + 3] *= c1; }
                    #pragma unroll
                    for (int j = 0; j < 8; j++) {
                        p[2 * j] = exp_mufu(s[4 * j] - m0, s[4 * j + 1] - m0);
                        p[2 * j + 1] = exp_mufu(s[4 * j + 2] - m1, s[4 * j + 3] - m1);
                    }
                    wg_fence();
                    #pragma unroll
                    for (int kk = 0; kk < 4; kk++) wg_pv(o[i], p + 4 * kk, dV + kk * dVstep);
                    wg_commit();
                    wg_wait<0>();
                }
                dK += 128;
                dV += 4 * dVstep;
            }
        }
        fence_regs<12>(o[0]);
        fence_regs<12>(o[1]);
        uint8_t* ob = g_oimg + qb * 131072 + hg * 16384 + (rowhalf * 8 + wiw * 2) * 128 + g * 16 + 4 * t;
        #pragma unroll
        for (int i = 0; i < 2; i++) {
            const float i0 = 1.0f / o[i][4], i1 = 1.0f / o[i][6];
            uint8_t* b = ob + (nh * 2 + i) * 4096;
            *(uint32_t*)(b) = pack_bf16(o[i][0] * i0, o[i][1] * i0);
            *(uint32_t*)(b + 128) = pack_bf16(o[i][2] * i1, o[i][3] * i1);
            *(uint32_t*)(b + 2048) = pack_bf16(o[i][8] * i0, o[i][9] * i0);
            *(uint32_t*)(b + 2048 + 128) = pack_bf16(o[i][10] * i1, o[i][11] * i1);
        }
        __threadfence();
    }
    __syncthreads();
    if (warp == 0) {
        if (lane == 0) st_release(&g_flag_o[blockIdx.x], epoch);
        if (lane < 8) {
            wait_flag(&g_flag_o[qb * 8 + lane], epoch);
            fence_async_all();
            mbar_expect_tx(bar_o + 8 * lane, 16384);
            bulk_g2s(sb + SM_A + lane * 16384, g_oimg + qb * 131072 + lane * 16384, 16384, bar_o + 8 * lane);
        }
        __syncwarp();
    }

    {
        float acc[16];
        #pragma unroll
        for (int i = 0; i < 16; i++) acc[i] = 0.0f;
        const uint64_t dA = make_desc(sb + SM_A + rowhalf * 1024, 2048, 128, 0);
        const uint64_t dB = make_desc(sb + SM_B + nh * 64, 16, 1024, 1);
        mbar_wait(bar_wo, 0);
        #pragma unroll 1
        for (int i = 0; i < 8; i++) {
            const int src = (hg + i) & 7;
            mbar_wait(bar_o + 8 * src, 0);
            wg_fence();
            #pragma unroll
            for (int kk = 0; kk < 4; kk++) wg_ss32(acc, dA + src * 1024 + kk * 256, dB + (src * 4 + kk) * 128);
            wg_commit();
        }
        wg_wait<0>();
        fence_regs<16>(acc);
        const int row = qb * 128 + rowhalf * 64 + wiw * 16 + g;
        uint32_t* o32 = (uint32_t*)(P.out + (size_t)row * 1024 + hg * 64 + nh * 32 + 2 * t);
        #pragma unroll
        for (int j = 0; j < 4; j++) {
            o32[4 * j] = pack_bf16(acc[4 * j], acc[4 * j + 1]);
            o32[4 * j + 8 * 512] = pack_bf16(acc[4 * j + 2], acc[4 * j + 3]);
        }
    }
    if (tid == 0) {
        __threadfence();
        const unsigned prev = atomicAdd(&g_done, 1u);
        if (prev == NCTA - 1) {
            g_done = 0;
            __threadfence();
            *(volatile unsigned*)&g_epoch = epoch;
        }
    }
}

typedef CUresult (*EncodeFn)(CUtensorMap*, CUtensorMapDataType, cuuint32_t, void*, const cuuint64_t*, const cuuint64_t*,
                             const cuuint32_t*, const cuuint32_t*, CUtensorMapInterleave, CUtensorMapSwizzle,
                             CUtensorMapL2promotion, CUtensorMapFloatOOBfill);

void make_map(EncodeFn fn, CUtensorMap* m, const void* ptr, uint64_t inner, uint64_t outer, uint32_t box_in, uint32_t box_out, CUtensorMapSwizzle swz) {
    cuuint64_t dims[2] = {inner, outer};
    cuuint64_t strides[1] = {inner * 2};
    cuuint32_t box[2] = {box_in, box_out};
    cuuint32_t es[2] = {1, 1};
    fn(m, CU_TENSOR_MAP_DATA_TYPE_BFLOAT16, 2, const_cast<void*>(ptr), dims, strides, box, es, CU_TENSOR_MAP_INTERLEAVE_NONE, swz,
       CU_TENSOR_MAP_L2_PROMOTION_L2_128B, CU_TENSOR_MAP_FLOAT_OOB_FILL_NONE);
}

}

extern "C" void kernel_launch(void* const* d_in, const int* in_sizes, int n_in, void* d_out, int out_size) {
    (void)in_sizes; (void)n_in; (void)out_size;
    static EncodeFn fn = nullptr;
    if (!fn) {
        void* p = nullptr;
        cudaDriverEntryPointQueryResult qr;
        cudaGetDriverEntryPoint("cuTensorMapEncodeTiled", &p, cudaEnableDefault, &qr);
        fn = (EncodeFn)p;
        cudaFuncSetAttribute(fused_kernel, cudaFuncAttributeMaxDynamicSharedMemorySize, SM_ALLOC);
    }
    CUtensorMap tx, twq, two, twk, twv;
    make_map(fn, &tx, d_in[0], 512, 2048, 64, 128, CU_TENSOR_MAP_SWIZZLE_128B);
    make_map(fn, &twq, d_in[1], 512, 512, 64, 256, CU_TENSOR_MAP_SWIZZLE_128B);
    make_map(fn, &twk, d_in[2], 16, 512, 8, 256, CU_TENSOR_MAP_SWIZZLE_NONE);
    make_map(fn, &twv, d_in[3], 16, 512, 8, 256, CU_TENSOR_MAP_SWIZZLE_NONE);
    make_map(fn, &two, d_in[4], 512, 512, 64, 256, CU_TENSOR_MAP_SWIZZLE_128B);
    Params P;
    P.u = (const __nv_bfloat16*)d_in[5];
    P.lar = (const __nv_bfloat16*)d_in[6];
    P.aim = (const __nv_bfloat16*)d_in[7];
    P.cre = (const __nv_bfloat16*)d_in[8];
    P.cim = (const __nv_bfloat16*)d_in[9];
    P.logdt = (const __nv_bfloat16*)d_in[10];
    P.dskip = (const __nv_bfloat16*)d_in[11];
    P.out = (__nv_bfloat16*)d_out;
    fused_kernel<<<NCTA, NTHR, SM_ALLOC>>>(tx, twq, two, twk, twv, P);
}
```

```cpp
#include <cuda_runtime.h>
#include <cuda_bf16.h>
#include <cuda_fp16.h>
#include <cuda.h>
#include <stdint.h>

namespace {

constexpr int SEQ = 2048;
constexpr int NCTA = 128, NTHR = 640;

constexpr int SM_A = 0;
constexpr int STG = 26624;
constexpr int SM_K = 0, SM_V = 65536;
constexpr int SM_B = 5 * STG;
constexpr int SM_BAR = SM_B + 81920;
constexpr int SM_TOTAL = SM_BAR + 1024;
constexpr int SM_ALLOC = SM_TOTAL + 1024;

constexpr int PADU = 288, ULEN = PADU + 2048;
constexpr int WPAD = 16, W2LEN = WPAD + 1536, W3LEN = WPAD + 1024;
constexpr int TABN = 2240;
constexpr int S_U = 0;
constexpr int S_W3 = S_U + ULEN * 2;
constexpr int S_W5 = S_W3 + W2LEN * 2;
constexpr int S_W7 = S_W5 + W2LEN * 2;
constexpr int S_W9 = S_W7 + W3LEN * 2;
constexpr int S_TAB = S_W9 + W3LEN * 2;
constexpr int CHB = S_TAB + TABN * 2;
constexpr int S_STG = S_W3, S_KC = S_W3 + 1024, S_Y = S_W3;
static_assert(4 * CHB <= 81920 && CHB % 16 == 0, "SSM working set too large");
static_assert(SM_V + 65536 + 256 <= SM_B && SM_ALLOC <= 232448, "smem map");

constexpr int TD0 = 0, TD1 = 560, CD = 544;
constexpr int TE0 = 1120, TE1 = 1168, CE = 1056;
constexpr int T2B = 1216, T2S = 160, T2C = 80, C2 = 80;
constexpr int T3B = 1856, T3S = 192, T3C = 96, C3 = 144;

constexpr int rne8(int t) {
    if (t < 256) return t;
    int sh = 0;
    while ((t >> sh) >= 256) sh++;
    int q = t >> sh, rem = t & ((1 << sh) - 1), half = 1 << (sh - 1);
    if (rem > half || (rem == half && (q & 1))) q++;
    return q << sh;
}
constexpr int kcidx(int p) {
    if (p < 256) return (p >> 3) * 24 + (p & 7);
    if (p < 512) return ((p - 256) >> 3) * 24 + 8 + (((p - 256) & 7) >> 1);
    if (p < 1024) { int q = p - 512, hi = q >> 8, rem = q & 255; return (rem >> 3) * 24 + 12 + 2 * hi + ((rem & 7) >> 2); }
    if (p < 2048) { int q = p - 1024; return ((q & 255) >> 3) * 24 + 16 + (q >> 8); }
    return 20;
}
constexpr int KC_ZERO = 23;
constexpr int tab_dense(int t) { return (t >= 0 && t <= 514) ? kcidx(rne8(t)) : KC_ZERO; }
constexpr int tab_extra(int t) { return (t >= 1027 && t <= 1028) ? kcidx(1024) : KC_ZERO; }
constexpr int tab_2(int s, int lag) { return (lag >= 32 && lag <= 63) ? kcidx(s == 0 ? 16 * (lag + 1) : 16 * lag + 4 * s) : KC_ZERO; }
constexpr int tab_3(int s, int lag) { return (lag >= 64 && lag <= 127) ? kcidx(s == 0 ? 16 * (lag + 1) : 16 * lag + 8) : KC_ZERO; }
struct TabMap {
    uint16_t v[TABN];
    constexpr TabMap() : v{} {
        for (int i = 0; i < 560; i++) { v[TD0 + i] = tab_dense(CD - i); v[TD1 + i] = tab_dense(CD + 1 - i); }
        for (int i = 0; i < 48; i++) { v[TE0 + i] = tab_extra(CE - i); v[TE1 + i] = tab_extra(CE + 1 - i); }
        for (int s = 0; s < 4; s++)
            for (int i = 0; i < T2C; i++) { v[T2B + s * T2S + i] = tab_2(s, C2 - i); v[T2B + s * T2S + T2C + i] = tab_2(s, C2 + 1 - i); }
        for (int s = 0; s < 2; s++)
            for (int i = 0; i < T3C; i++) { v[T3B + s * T3S + i] = tab_3(s, C3 - i); v[T3B + s * T3S + T3C + i] = tab_3(s, C3 + 1 - i); }
    }
};
__device__ const __align__(16) TabMap g_tabmap = TabMap();

__device__ __align__(1024) uint8_t g_kimg[65536];
__device__ __align__(1024) uint8_t g_vimg[65536 + 256];
__device__ __align__(1024) uint8_t g_oimg[16 * 131072];
__device__ float g_stat[2][128];
__device__ unsigned g_flag_kv[64];
__device__ unsigned g_flag_o[128];
__device__ unsigned g_epoch;
__device__ unsigned g_done;

#define PROF(i) do {} while (0)
#define PROF2(i) do {} while (0)

__device__ __forceinline__ uint32_t smem_u32(const void* p) { return (uint32_t)__cvta_generic_to_shared(p); }
__device__ __forceinline__ void mbar_init(uint32_t bar, uint32_t cnt) { asm volatile("mbarrier.init.shared::cta.b64 [%0], %1;" :: "r"(bar), "r"(cnt) : "memory"); }
__device__ __forceinline__ void mbar_expect_tx(uint32_t bar, uint32_t bytes) {
    asm volatile("mbarrier.arrive.expect_tx.shared::cta.b64 _, [%0], %1;" :: "r"(bar), "r"(bytes) : "memory"); }
__device__ __forceinline__ void mbar_wait(uint32_t bar, uint32_t parity) {
    uint32_t ok = 0;
    for (int it = 0; it < (1 << 22) && !ok; it++) {
        asm volatile("{ .reg .pred p; mbarrier.try_wait.parity.shared::cta.b64 p, [%1], %2; selp.u32 %0, 1, 0, p; }"
                     : "=r"(ok) : "r"(bar), "r"(parity) : "memory");
    }
}
__device__ __forceinline__ void tma_2d(uint32_t dst, const CUtensorMap* map, int c0, int c1, uint32_t bar) {
    asm volatile("cp.async.bulk.tensor.2d.shared::cluster.global.mbarrier::complete_tx::bytes [%0], [%1, {%3, %4}], [%2];"
                 :: "r"(dst), "l"((uint64_t)map), "r"(bar), "r"(c0), "r"(c1) : "memory");
}
__device__ __forceinline__ void bulk_g2s(uint32_t dst, const void* src, uint32_t bytes, uint32_t bar) {
    asm volatile("cp.async.bulk.shared::cluster.global.mbarrier::complete_tx::bytes [%0], [%1], %2, [%3];"
                 :: "r"(dst), "l"((uint64_t)src), "r"(bytes), "r"(bar) : "memory");
}
__device__ __forceinline__ void fence_async_all() { asm volatile("fence.proxy.async;" ::: "memory"); }
__device__ __forceinline__ void fence_async_smem() { asm volatile("fence.proxy.async.shared::cta;" ::: "memory"); }
__device__ __forceinline__ unsigned ld_acquire(const unsigned* p) {
    unsigned v; asm volatile("ld.acquire.gpu.global.u32 %0, [%1];" : "=r"(v) : "l"(p) : "memory"); return v; }
__device__ __forceinline__ void st_release(unsigned* p, unsigned v) { asm volatile("st.release.gpu.global.u32 [%0], %1;" :: "l"(p), "r"(v) : "memory"); }
__device__ __forceinline__ void wait_flag(const unsigned* p, unsigned epoch) {
    for (int it = 0; it < (1 << 22); it++) { if (ld_acquire(p) == epoch) break; }
}
__device__ __forceinline__ void bar_sync(int id, int n) { asm volatile("bar.sync %0, %1;" :: "r"(id), "r"(n) : "memory"); }

__device__ __forceinline__ uint64_t make_desc(uint32_t saddr, uint32_t lbo, uint32_t sbo, uint32_t swz) {
    uint64_t d = 0;
    d |= (uint64_t)((saddr & 0x3FFFF) >> 4);
    d |= (uint64_t)((lbo >> 4) & 0x3FFF) << 16;
    d |= (uint64_t)((sbo >> 4) & 0x3FFF) << 32;
    d |= (uint64_t)swz << 62;
    return d;
}
__device__ __forceinline__ void wg_fence() { asm volatile("wgmma.fence.sync.aligned;" ::: "memory"); }
__device__ __forceinline__ void wg_commit() { asm volatile("wgmma.commit_group.sync.aligned;" ::: "memory"); }
template<int N> __device__ __forceinline__ void wg_wait() { asm volatile("wgmma.wait_group.sync.aligned %0;" :: "n"(N) : "memory"); }
#define A4(d, o) "+f"(d[o + 0]), "+f"(d[o + 1]), "+f"(d[o + 2]), "+f"(d[o + 3])
#define A16(d, o) A4(d, o), A4(d, o + 4), A4(d, o + 8), A4(d, o + 12)

__device__ __forceinline__ void wg_pv(float* d, const uint32_t* a, uint64_t desc) {
    asm volatile("wgmma.mma_async.sync.aligned.m64n24k16.f32.bf16.bf16 {%0,%1,%2,%3,%4,%5,%6,%7,%8,%9,%10,%11}, {%12,%13,%14,%15}, %16, 1, 1, 1, 1;"
                 : A4(d, 0), A4(d, 4), A4(d, 8) : "r"(a[0]), "r"(a[1]), "r"(a[2]), "r"(a[3]), "l"(desc));
}
__device__ __forceinline__ void wg_qk(float* d, const uint32_t* a, uint64_t desc) {
    asm volatile("wgmma.mma_async.sync.aligned.m64n64k16.f32.bf16.bf16 {%0,%1,%2,%3,%4,%5,%6,%7,%8,%9,%10,%11,%12,%13,%14,%15,%16,%17,%18,%19,%20,%21,%22,%23,%24,%25,%26,%27,%28,%29,%30,%31}, {%32,%33,%34,%35}, %36, 0, 1, 1, 0;"
                 : A16(d, 0), A16(d, 16) : "r"(a[0]), "r"(a[1]), "r"(a[2]), "r"(a[3]), "l"(desc));
}
__device__ __forceinline__ void wg_ss32(float* d, uint64_t da, uint64_t db) {
    asm volatile("wgmma.mma_async.sync.aligned.m64n32k16.f32.bf16.bf16 {%0,%1,%2,%3,%4,%5,%6,%7,%8,%9,%10,%11,%12,%13,%14,%15}, %16, %17, 1, 1, 1, 0, 1;"
                 : A16(d, 0) : "l"(da), "l"(db));
}
__device__ __forceinline__ void wg_ss16(float* d, uint64_t da, uint64_t db) {
    asm volatile("wgmma.mma_async.sync.aligned.m64n16k16.f32.bf16.bf16 {%0,%1,%2,%3,%4,%5,%6,%7}, %8, %9, 1, 1, 1, 0, 1;"
                 : A4(d, 0), A4(d, 4) : "l"(da), "l"(db));
}
template<int N> __device__ __forceinline__ void fence_regs(float* r) {
    #pragma unroll
    for (int i = 0; i < N; i++) asm volatile("" : "+f"(r[i]) :: "memory");
}
__device__ __forceinline__ void mma_bf16(float* d, uint32_t a0, uint32_t a1, uint32_t a2, uint32_t a3, uint32_t b0, uint32_t b1) {
    asm volatile("mma.sync.aligned.m16n8k16.row.col.f32.bf16.bf16.f32 {%0,%1,%2,%3}, {%4,%5,%6,%7}, {%8,%9}, {%0,%1,%2,%3};"
                 : "+f"(d[0]), "+f"(d[1]), "+f"(d[2]), "+f"(d[3]) : "r"(a0), "r"(a1), "r"(a2), "r"(a3), "r"(b0), "r"(b1));
}
__device__ __forceinline__ void mma_f16(float* d, const uint32_t* a, uint32_t b0, uint32_t b1) {
    asm volatile("mma.sync.aligned.m16n8k16.row.col.f32.f16.f16.f32 {%0,%1,%2,%3}, {%4,%5,%6,%7}, {%8,%9}, {%0,%1,%2,%3};"
                 : "+f"(d[0]), "+f"(d[1]), "+f"(d[2]), "+f"(d[3]) : "r"(a[0]), "r"(a[1]), "r"(a[2]), "r"(a[3]), "r"(b0), "r"(b1));
}
__device__ __forceinline__ void ldsm4(uint32_t* r, uint32_t addr) {
    asm volatile("ldmatrix.sync.aligned.m8n8.x4.shared.b16 {%0,%1,%2,%3}, [%4];" : "=r"(r[0]), "=r"(r[1]), "=r"(r[2]), "=r"(r[3]) : "r"(addr) : "memory");
}
__device__ __forceinline__ void ldsm4t(uint32_t* r, uint32_t addr) {
    asm volatile("ldmatrix.sync.aligned.m8n8.x4.trans.shared.b16 {%0,%1,%2,%3}, [%4];" : "=r"(r[0]), "=r"(r[1]), "=r"(r[2]), "=r"(r[3]) : "r"(addr) : "memory");
}
__device__ __forceinline__ uint32_t lds32(uint32_t addr) { uint32_t v; asm volatile("ld.shared.u32 %0, [%1];" : "=r"(v) : "r"(addr) : "memory"); return v; }
__device__ __forceinline__ float ex2f(float x) { float r; asm("ex2.approx.ftz.f32 %0, %1;" : "=f"(r) : "f"(x)); return r; }
__device__ __forceinline__ uint32_t pack_bf16(float lo, float hi) { uint32_t r; asm("cvt.rn.bf16x2.f32 %0, %1, %2;" : "=r"(r) : "f"(hi), "f"(lo)); return r; }
__device__ __forceinline__ uint32_t pack_f16(float lo, float hi) { uint32_t r; asm("cvt.rn.f16x2.f32 %0, %1, %2;" : "=r"(r) : "f"(hi), "f"(lo)); return r; }
__device__ __forceinline__ float bf_lo(uint32_t v) { return __uint_as_float(v << 16); }
__device__ __forceinline__ float bf_hi(uint32_t v) { return __uint_as_float(v & 0xFFFF0000u); }
__device__ __forceinline__ float bf_round(float x) { return __bfloat162float(__float2bfloat16_rn(x)); }

__device__ __forceinline__ uint32_t exp_mufu(float x0, float x1) { return pack_bf16(ex2f(x0), ex2f(x1)); }
#define SW_MAGIC (256.0f + 127.0f - 0.598938f)
__device__ __forceinline__ uint32_t exp_sw(float x0, float x1, uint32_t cA, uint32_t cB) {
    float t0 = x0 + SW_MAGIC, t1 = x1 + SW_MAGIC;
    uint32_t L, mh, ec, r;
    asm("prmt.b32 %0, %1, %2, 0x6521;" : "=r"(L) : "r"(__float_as_uint(t0)), "r"(__float_as_uint(t1)));
    asm("lop3.b32 %0, %1, 0x007F007F, %2, 0xEA;" : "=r"(mh) : "r"(L), "r"(cA));
    asm("lop3.b32 %0, %1, 0x7F807F80, %2, 0xEA;" : "=r"(ec) : "r"(L), "r"(cB));
    asm("fma.rn.bf16x2 %0, %1, %2, %3;" : "=r"(r) : "r"(L), "r"(mh), "r"(ec));
    return r;
}
constexpr uint32_t MUFU_MASK = 0x4949;

struct cf { float x, y; };
__device__ __forceinline__ cf cmul(cf a, cf b) { cf r; r.x = a.x * b.x - a.y * b.y; r.y = a.x * b.y + a.y * b.x; return r; }
__device__ __forceinline__ cf cexp_p(float a2, float b, float p) {
    float e = ex2f(a2 * p);
    float ph = b * p;
    ph -= (ph + 12582912.0f) - 12582912.0f;
    float ang = ph * 6.283185307f;
    cf r; r.x = e * __cosf(ang); r.y = e * __sinf(ang);
    return r;
}
__device__ __forceinline__ uint32_t h2_cmul(uint32_t w, uint32_t wsw, uint32_t e) {
    __half2 hw = *(__half2*)&w, hs = *(__half2*)&wsw, he = *(__half2*)&e;
    __half2 r = __hfma2(hs, __high2half2(he), __hmul2(hw, __low2half2(he)));
    return *(uint32_t*)&r;
}

template<bool B> struct BoolC { static constexpr bool value = B; };
struct Params {
    const __nv_bfloat16 *u, *lar, *aim, *cre, *cim, *logdt, *dskip;
    __nv_bfloat16* out;
};

__device__ __forceinline__ void ssm_role(const Params& P, uint8_t* sp, uint32_t sb, const CUtensorMap* tm_wo, uint32_t bar_wo) {
    const int tid = threadIdx.x & 127, c = tid >> 5, lane = tid & 31, g = lane >> 2, t = lane & 3;
    const int d0 = blockIdx.x * 4, d = d0 + c;
    uint8_t* sB = sp + SM_B;
    uint8_t* cb = sB + c * CHB;
    const uint32_t cba = sb + SM_B + c * CHB;

    #pragma unroll 1
    for (int i = 0; i < 2; i++) {
        uint2 r[8];
        #pragma unroll
        for (int k = 0; k < 4; k++) {
            const int l = 2 * (tid + 128 * (4 * i + k));
            r[2 * k] = __ldg((const uint2*)(P.u + (size_t)l * 512 + d0));
            r[2 * k + 1] = __ldg((const uint2*)(P.u + (size_t)(l + 1) * 512 + d0));
        }
        #pragma unroll
        for (int k = 0; k < 4; k++) {
            const int l = 2 * (tid + 128 * (4 * i + k));
            uint8_t* dst = sB + S_U + (PADU + l) * 2;
            *(uint32_t*)(dst) = __byte_perm(r[2 * k].x, r[2 * k + 1].x, 0x5410);
            *(uint32_t*)(dst + CHB) = __byte_perm(r[2 * k].x, r[2 * k + 1].x, 0x7632);
            *(uint32_t*)(dst + 2 * CHB) = __byte_perm(r[2 * k].y, r[2 * k + 1].y, 0x5410);
            *(uint32_t*)(dst + 3 * CHB) = __byte_perm(r[2 * k].y, r[2 * k + 1].y, 0x7632);
        }
    }
    for (int i = lane; i < PADU / 8; i += 32) *(uint4*)(cb + S_U + i * 16) = make_uint4(0, 0, 0, 0);

    {
        const float dt = bf_round(expf(__bfloat162float(P.logdt[d])));
        const uint2 cr4 = __ldg((const uint2*)(P.cre + d * 128 + 4 * lane)), ci4 = __ldg((const uint2*)(P.cim + d * 128 + 4 * lane));
        float m = fmaxf(fmaxf(fmaxf(fabsf(bf_lo(cr4.x)), fabsf(bf_hi(cr4.x))), fmaxf(fabsf(bf_lo(cr4.y)), fabsf(bf_hi(cr4.y)))),
                        fmaxf(fmaxf(fabsf(bf_lo(ci4.x)), fabsf(bf_hi(ci4.x))), fmaxf(fabsf(bf_lo(ci4.y)), fabsf(bf_hi(ci4.y)))));
        #pragma unroll
        for (int o = 16; o; o >>= 1) m = fmaxf(m, __shfl_xor_sync(0xffffffffu, m, o));
        m *= 2.0f * dt;
        int ebits = (__float_as_uint(m) >> 23) & 0xFF;
        ebits = min(max(ebits, 2), 250);
        const float scale = __uint_as_float((uint32_t)(ebits + 1) << 23);
        const float iscale = __uint_as_float((uint32_t)(253 - ebits) << 23);

        uint4* stp = (uint4*)(cb + S_STG + lane * 32);
        const uint32_t fa = cba + S_STG + t * 32 + g * 4;
        float acc[2][3][4];
        #pragma unroll
        for (int i = 0; i < 24; i++) (&acc[0][0][0])[i] = 0.0f;
        #pragma unroll 1
        for (int mq = 0; mq < 4; mq++) {
            const int n = d * 128 + mq * 32 + lane;
            const float are = -bf_round(expf(__bfloat162float(P.lar[n]))) * dt;
            const float aim = __bfloat162float(P.aim[n]) * dt;
            const float a2 = are * 1.4426950408889634f, bb = aim * 0.15915494309189535f;
            cf cc;
            cc.x = 2.0f * (__bfloat162float(P.cre[n]) * dt) * iscale;
            cc.y = 2.0f * (__bfloat162float(P.cim[n]) * dt) * iscale;
            uint32_t af[4][2][4];
            {
                const cf E8 = cexp_p(a2, bb, 8.0f);
                uint32_t w[8];
                cf cur = E8;
                w[0] = pack_f16(1.0f, 0.0f);
                w[1] = pack_f16(cur.x, cur.y);
                #pragma unroll
                for (int i = 2; i < 8; i++) { cur = cmul(cur, E8); w[i] = pack_f16(cur.x, cur.y); }
                stp[0] = make_uint4(w[0], w[1], w[2], w[3]);
                stp[1] = make_uint4(w[4], w[5], w[6], w[7]);
                const cf E64 = cexp_p(a2, bb, 64.0f);
                const cf E128 = cmul(E64, E64), E192 = cmul(E128, E64);
                const uint32_t e1 = pack_f16(E64.x, E64.y), e2 = pack_f16(E128.x, E128.y), e3 = pack_f16(E192.x, E192.y);
                __syncwarp();
                #pragma unroll
                for (int s = 0; s < 4; s++) {
                    #pragma unroll
                    for (int hh = 0; hh < 2; hh++) {
                        const uint32_t w0 = lds32(fa + s * 256 + hh * 128);
                        const uint32_t wsw = __byte_perm(w0, 0, 0x1032) ^ 0x00008000u;
                        const int src = 8 * s + t + 4 * hh;
                        const uint32_t f1 = __shfl_sync(0xffffffffu, e1, src), f2 = __shfl_sync(0xffffffffu, e2, src), f3 = __shfl_sync(0xffffffffu, e3, src);
                        af[s][0][2 * hh] = w0;
                        af[s][0][2 * hh + 1] = h2_cmul(w0, wsw, f1);
                        af[s][1][2 * hh] = h2_cmul(w0, wsw, f2);
                        af[s][1][2 * hh + 1] = h2_cmul(w0, wsw, f3);
                    }
                }
                __syncwarp();
            }
            const cf E256 = cexp_p(a2, bb, 256.0f);
            const cf E1 = cexp_p(a2, bb, 1.0f);
            const cf E2 = cmul(E1, E1), E4 = cmul(E2, E2);
            cf X512;
            #pragma unroll
            for (int nt = 0; nt < 3; nt++) {
                uint32_t xv[8];
                if (nt == 0) {
                    cf cur = cc;
                    xv[0] = pack_f16(cur.x, -cur.y);
                    #pragma unroll
                    for (int i = 1; i < 8; i++) { cur = cmul(cur, E1); xv[i] = pack_f16(cur.x, -cur.y); }
                } else if (nt == 1) {
                    cf cur = cmul(cc, E256);
                    X512 = cmul(cur, E256);
                    xv[0] = pack_f16(cur.x, -cur.y);
                    #pragma unroll
                    for (int i = 1; i < 4; i++) { cur = cmul(cur, E2); xv[i] = pack_f16(cur.x, -cur.y); }
                    cur = cmul(X512, E4);
                    xv[4] = pack_f16(X512.x, -X512.y); xv[5] = pack_f16(cur.x, -cur.y);
                    X512 = cmul(X512, E256);
                    cur = cmul(X512, E4);
                    xv[6] = pack_f16(X512.x, -X512.y); xv[7] = pack_f16(cur.x, -cur.y);
                } else {
                    cf cur = X512;
                    #pragma unroll
                    for (int i = 0; i < 5; i++) { cur = cmul(cur, E256); xv[i] = pack_f16(cur.x, -cur.y); }
                    xv[5] = 0; xv[6] = 0; xv[7] = 0;
                }
                stp[0] = make_uint4(xv[0], xv[1], xv[2], xv[3]);
                stp[1] = make_uint4(xv[4], xv[5], xv[6], xv[7]);
                __syncwarp();
                #pragma unroll
                for (int s = 0; s < 4; s++) {
                    const uint32_t b0 = lds32(fa + s * 256), b1 = lds32(fa + s * 256 + 128);
                    mma_f16(acc[0][nt], af[s][0], b0, b1);
                    mma_f16(acc[1][nt], af[s][1], b0, b1);
                }
                __syncwarp();
            }
        }
        float* kc = (float*)(cb + S_KC);
        #pragma unroll
        for (int mt = 0; mt < 2; mt++)
            #pragma unroll
            for (int nt = 0; nt < 3; nt++)
                #pragma unroll
                for (int hh = 0; hh < 2; hh++)
                    *(float2*)(kc + (mt * 16 + hh * 8 + g) * 24 + nt * 8 + 2 * t) = make_float2(acc[mt][nt][2 * hh] * scale, acc[mt][nt][2 * hh + 1] * scale);
        __syncwarp();
        uint32_t* tab = (uint32_t*)(cb + S_TAB);
        const uint32_t* map = (const uint32_t*)g_tabmap.v;
        #pragma unroll 5
        for (int w = lane; w < TABN / 2; w += 32) {
            const uint32_t mp = __ldg(map + w);
            tab[w] = pack_bf16(kc[mp & 0xFFFF], kc[mp >> 16]);
        }
    }
    PROF2(1);
    bar_sync(2, 128);

    #pragma unroll 1
    for (int i = lane; i < 194; i += 32) {
        const uint4* src = (const uint4*)(cb + S_U + (PADU + 8 * i - WPAD - 8) * 2);
        const uint4 v0 = src[0], v1 = src[1], v2 = src[2];
        float x[24];
        const uint32_t vv[12] = {v0.x, v0.y, v0.z, v0.w, v1.x, v1.y, v1.z, v1.w, v2.x, v2.y, v2.z, v2.w};
        #pragma unroll
        for (int k = 0; k < 12; k++) { x[2 * k] = bf_lo(vv[k]); x[2 * k + 1] = bf_hi(vv[k]); }
        float w3[12], w5[8];
        #pragma unroll
        for (int e = 0; e < 12; e++) w3[e] = (x[3 + e] + x[4 + e]) + x[5 + e];
        #pragma unroll
        for (int e = 0; e < 8; e++) w5[e] = w3[4 + e] + (x[6 + e] + x[10 + e]);
        *(uint4*)(cb + S_W3 + i * 16) = make_uint4(pack_bf16(w3[0], w3[1]), pack_bf16(w3[2], w3[3]), pack_bf16(w3[4], w3[5]), pack_bf16(w3[6], w3[7]));
        *(uint4*)(cb + S_W5 + i * 16) = make_uint4(pack_bf16(w5[0], w5[1]), pack_bf16(w5[2], w5[3]), pack_bf16(w5[4], w5[5]), pack_bf16(w5[6], w5[7]));
        if (i < 130) {
            float w7[8], w9[8];
            #pragma unroll
            for (int e = 0; e < 8; e++) { w7[e] = w5[e] + (x[5 + e] + x[11 + e]); w9[e] = w7[e] + (x[4 + e] + x[12 + e]); }
            *(uint4*)(cb + S_W7 + i * 16) = make_uint4(pack_bf16(w7[0], w7[1]), pack_bf16(w7[2], w7[3]), pack_bf16(w7[4], w7[5]), pack_bf16(w7[6], w7[7]));
            *(uint4*)(cb + S_W9 + i * 16) = make_uint4(pack_bf16(w9[0], w9[1]), pack_bf16(w9[2], w9[3]), pack_bf16(w9[4], w9[5]), pack_bf16(w9[6], w9[7]));
        }
    }
    __syncwarp();
    PROF2(2);

    uint32_t ypk[2][8][2];
    {
        const uint32_t tabc = cba + S_TAB;
        const int e2 = (g - 2 * t) * 2;
        const int mi = lane >> 3, r8 = lane & 7;
        const uint32_t frag = (16 * (8 * (mi >> 1) + r8) + 8 * (mi & 1)) * 2;
        const uint32_t tD = tabc + ((g & 1) ? (TD1 + CD + 1) : (TD0 + CD)) * 2 - e2;
        const uint32_t t2 = tabc + (T2B + ((g & 1) ? (T2C + C2 + 1) : C2)) * 2 - e2;
        #pragma unroll
        for (int hf = 0; hf < 2; hf++) {
            float acc[8][4];
            #pragma unroll
            for (int i = 0; i < 32; i++) (&acc[0][0])[i] = 0.0f;
            const uint32_t ub = cba + S_U + PADU * 2 + frag + hf * 2048;
            #pragma unroll 1
            for (int rho = 0; rho < 8; rho++) {
                uint32_t R[5][3];
                #pragma unroll
                for (int qq = 0; qq < 5; qq++) {
                    const uint32_t a = tD - 32 * ((qq < 4 || rho < 2) ? rho + 8 * qq : 0);
                    R[qq][0] = lds32(a + 16); R[qq][1] = lds32(a); R[qq][2] = lds32(a - 16);
                }
                #pragma unroll
                for (int jp = -2; jp < 4; jp++) {
                    if (hf == 0 && jp == -2) continue;
                    if (hf == 0 && jp == -1 && rho > 0) continue;
                    uint32_t b[4];
                    ldsm4(b, ub + jp * 512 - rho * 32);
                    #pragma unroll
                    for (int hh = 0; hh < 2; hh++) {
                        #pragma unroll
                        for (int qq = 0; qq < 4; qq++) {
                            const int j = 2 * jp + hh + qq;
                            if (j >= 0 && j < 8 && !(hf == 0 && jp == -1 && hh == 0)) mma_bf16(acc[j], R[qq][1], R[qq][2], R[qq][0], R[qq][1], b[2 * hh], b[2 * hh + 1]);
                        }
                    }
                    if (rho < 2 && jp < 2) {
                        if (!(hf == 0 && jp == -1)) mma_bf16(acc[2 * jp + 4], R[4][1], R[4][2], R[4][0], R[4][1], b[0], b[1]);
                        mma_bf16(acc[2 * jp + 5], R[4][1], R[4][2], R[4][0], R[4][1], b[2], b[3]);
                    }
                }
            }
            #pragma unroll 1
            for (int s = 0; s < 4; s++) {
                const uint32_t sig = cba + ((s & 1) ? S_W3 : S_W5) + WPAD * 2 + frag - ((s == 0) ? 32 : (s == 1) ? 0 : 16);
                uint32_t R[7];
                #pragma unroll
                for (int i = 0; i < 7; i++) R[i] = lds32(t2 + s * (T2S * 2) - 16 * (3 + i));
                #pragma unroll
                for (int b = 0; b < 6; b++) {
                    if (hf == 0 && b > 1) continue;
                    uint32_t a[4];
                    ldsm4t(a, sig + b * 512);
                    #pragma unroll
                    for (int h = 4; h <= 9; h++) {
                        const int j = h + 2 * b - 8 * hf;
                        if (j >= 0 && j < 8) mma_bf16(acc[j], a[0], a[1], a[2], a[3], R[h - 3], R[h - 4]);
                    }
                }
            }
            if (hf == 1) {
                {
                    const uint32_t tE = tabc + ((g & 1) ? (TE1 + CE + 1) : (TE0 + CE)) * 2 - e2;
                    uint32_t R[5];
                    #pragma unroll
                    for (int i = 0; i < 5; i++) R[i] = lds32(tE - 16 * (127 + i));
                    #pragma unroll
                    for (int kk = 0; kk < 2; kk++) {
                        #pragma unroll
                        for (int jp = 0; jp < 4; jp++) {
                            uint32_t b[4];
                            ldsm4(b, ub - 2048 + jp * 512 - kk * 32);
                            mma_bf16(acc[2 * jp], R[2 * kk + 1], R[2 * kk + 2], R[2 * kk], R[2 * kk + 1], b[0], b[1]);
                            mma_bf16(acc[2 * jp + 1], R[2 * kk + 1], R[2 * kk + 2], R[2 * kk], R[2 * kk + 1], b[2], b[3]);
                        }
                    }
                }
                const uint32_t t3 = tabc + (T3B + ((g & 1) ? (T3C + C3 + 1) : C3)) * 2 - e2;
                #pragma unroll 1
                for (int s = 0; s < 2; s++) {
                    const uint32_t sig = cba + (s ? S_W7 : S_W9) + WPAD * 2 + frag - (s ? 16 : 32);
                    uint32_t R[9];
                    #pragma unroll
                    for (int i = 0; i < 9; i++) R[i] = lds32(t3 + s * (T3S * 2) - 16 * (7 + i));
                    #pragma unroll
                    for (int b = 0; b < 4; b++) {
                        uint32_t a[4];
                        ldsm4t(a, sig + b * 512);
                        #pragma unroll
                        for (int h = 8; h <= 15; h++)
                            if (h + 2 * b < 16) mma_bf16(acc[h + 2 * b - 8], a[0], a[1], a[2], a[3], R[h - 7], R[h - 8]);
                    }
                }
            }
            #pragma unroll
            for (int j = 0; j < 8; j++) { ypk[hf][j][0] = pack_bf16(acc[j][0], acc[j][1]); ypk[hf][j][1] = pack_bf16(acc[j][2], acc[j][3]); }
        }
        __syncwarp();
        uint16_t* ys = (uint16_t*)(cb + S_Y) + 32 * t + g;
        #pragma unroll
        for (int j = 0; j < 16; j++) {
            const uint32_t v0 = ypk[j >> 3][j & 7][0], v1 = ypk[j >> 3][j & 7][1];
            ys[128 * j] = (uint16_t)v0;
            ys[128 * j + 16] = (uint16_t)(v0 >> 16);
            ys[128 * j + 8] = (uint16_t)v1;
            ys[128 * j + 24] = (uint16_t)(v1 >> 16);
        }
    }
    PROF2(3);
    bar_sync(2, 128);
    {
        const uint2 dsk = __ldg((const uint2*)(P.dskip + d0));
        uint32_t dd[4] = {__byte_perm(dsk.x, 0, 0x1010), __byte_perm(dsk.x, 0, 0x3232), __byte_perm(dsk.y, 0, 0x1010), __byte_perm(dsk.y, 0, 0x3232)};
        #pragma unroll 2
        for (int i = 0; i < 8; i++) {
            const int l = 2 * (tid + 128 * i);
            uint32_t r[4];
            #pragma unroll
            for (int cc = 0; cc < 4; cc++) {
                const uint32_t y2 = *(const uint32_t*)(sB + cc * CHB + S_Y + l * 2);
                const uint32_t u2 = *(const uint32_t*)(sB + cc * CHB + S_U + (PADU + l) * 2);
                __nv_bfloat162 pr = __hmul2(*(const __nv_bfloat162*)&u2, *(const __nv_bfloat162*)&dd[cc]);
                __nv_bfloat162 sm = __hadd2(*(const __nv_bfloat162*)&y2, pr);
                r[cc] = *(uint32_t*)&sm;
            }
            *(uint2*)(P.out + (size_t)l * 1024 + 512 + d0) = make_uint2(__byte_perm(r[0], r[1], 0x5410), __byte_perm(r[2], r[3], 0x5410));
            *(uint2*)(P.out + (size_t)(l + 1) * 1024 + 512 + d0) = make_uint2(__byte_perm(r[0], r[1], 0x7632), __byte_perm(r[2], r[3], 0x7632));
        }
    }
    bar_sync(2, 128);
    if (tid == 0) {
        fence_async_smem();
        mbar_expect_tx(bar_wo, 65536);
        for (int b = 0; b < 2; b++) tma_2d(sb + SM_B + b * 32768, tm_wo, (blockIdx.x & 7) * 64, b * 256, bar_wo);
    }
    PROF2(4);
}

__global__ void __launch_bounds__(NTHR, 1)
fused_kernel(const __grid_constant__ CUtensorMap tm_x, const __grid_constant__ CUtensorMap tm_wq,
             const __grid_constant__ CUtensorMap tm_wo, const __grid_constant__ CUtensorMap tm_wk,
             const __grid_constant__ CUtensorMap tm_wv, const Params P) {
    extern __shared__ uint8_t smem_raw[];
    const uint32_t sb = (smem_u32(smem_raw) + 1023u) & ~1023u;
    uint8_t* sp = smem_raw + (sb - smem_u32(smem_raw));

    const int tid = threadIdx.x, warp = tid >> 5, lane = tid & 31, wg = tid >> 7, wiw = warp & 3;
    const int g = lane >> 2, t = lane & 3;
    const int qb = blockIdx.x >> 3, hg = blockIdx.x & 7;
    const int rowhalf = wg & 1, nh = wg >> 1;
    const bool kv_cta = hg < 4;
    const int kv_sel = hg >> 1;
    const bool kv_wg = kv_cta && (wg == (hg & 1));

    const uint32_t bar_x = sb + SM_BAR, bar_o = bar_x + 64, bar_kv = bar_x + 128, bar_wo = bar_x + 136;
    float* s_misc = (float*)(sp + SM_BAR + 256);
    const CUtensorMap* tm_kv = kv_sel ? &tm_wv : &tm_wk;

    PROF(0);
    auto issue_chunk = [&](int ch) {
        const uint32_t st = sb + SM_A + (ch % 5) * STG, bar = bar_x + 8 * ch;
        mbar_expect_tx(bar, 24576 + (kv_cta ? 2048 : 0));
        tma_2d(st, &tm_x, ch * 64, qb * 128, bar);
        tma_2d(st + 16384, &tm_wq, hg * 64, ch * 64, bar);
        if (kv_cta) { tma_2d(st + 24576, tm_kv, 0, ch * 64, bar); tma_2d(st + 25600, tm_kv, 8, ch * 64, bar); }
    };
    if (tid == 0) {
        for (int i = 0; i < 18; i++) mbar_init(bar_x + 8 * i, 1);
        asm volatile("fence.mbarrier_init.release.cluster;" ::: "memory");
        fence_async_smem();
        for (int ch = 0; ch < 5; ch++) issue_chunk(ch);
    }
    const unsigned epoch = *(volatile unsigned*)&g_epoch + 1u;
    __syncthreads();

    if (wg == 4) {
        ssm_role(P, sp, sb, &tm_wo, bar_wo);
    } else {
        uint32_t q[2][4];
        {
            float acc[16], akv[8];
            #pragma unroll
            for (int i = 0; i < 16; i++) acc[i] = 0.0f;
            #pragma unroll
            for (int i = 0; i < 8; i++) akv[i] = 0.0f;
            fence_regs<16>(acc);
            fence_regs<8>(akv);
            const uint64_t dA = make_desc(sb + SM_A + rowhalf * 8192, 16, 1024, 1);
            const uint64_t dB = make_desc(sb + SM_A + 16384 + nh * 64, 16, 1024, 1);
            const uint64_t dC = make_desc(sb + SM_A + 24576, 128, 1024, 0);
            auto proj_loop = [&](auto KV) {
                #pragma unroll 1
                for (int ch = 0; ch < 8; ch++) {
                    const uint32_t so = (ch % 5) * (STG / 16);
                    mbar_wait(bar_x + 8 * ch, 0);
                    if (ch == 0) PROF(2);
                    wg_fence();
                    if (decltype(KV)::value) {
                        #pragma unroll
                        for (int ks = 0; ks < 4; ks++) wg_ss16(akv, dA + so + ks * 2, dC + so + ks * 16);
                    }
                    #pragma unroll
                    for (int ks = 0; ks < 4; ks++) wg_ss32(acc, dA + so + ks * 2, dB + so + ks * 128);
                    wg_commit();
                    if (ch == 2) {
                        wg_wait<0>();
                        bar_sync(1, 512);
                        if (tid == 0) { for (int c2 = 5; c2 < 8; c2++) issue_chunk(c2); }
                    }
                }
                wg_wait<0>();
            };
            if (kv_wg) proj_loop(BoolC<true>()); else proj_loop(BoolC<false>());
            fence_regs<16>(acc);
            fence_regs<8>(akv);
            if (kv_wg) {
                const int key = qb * 128 + rowhalf * 64 + wiw * 16 + g;
                uint32_t pk[4];
                #pragma unroll
                for (int i = 0; i < 4; i++) pk[i] = pack_bf16(akv[2 * i], akv[2 * i + 1]);
                float st;
                if (kv_sel == 0) {
                    uint8_t* b = g_kimg + (key >> 3) * 256 + (key & 7) * 16 + 4 * t;
                    *(uint32_t*)(b) = pk[0]; *(uint32_t*)(b + 256) = pk[1]; *(uint32_t*)(b + 128) = pk[2]; *(uint32_t*)(b + 384) = pk[3];
                    float n0 = bf_lo(pk[0]) * bf_lo(pk[0]) + bf_hi(pk[0]) * bf_hi(pk[0]) + bf_lo(pk[2]) * bf_lo(pk[2]) + bf_hi(pk[2]) * bf_hi(pk[2]);
                    float n1 = bf_lo(pk[1]) * bf_lo(pk[1]) + bf_hi(pk[1]) * bf_hi(pk[1]) + bf_lo(pk[3]) * bf_lo(pk[3]) + bf_hi(pk[3]) * bf_hi(pk[3]);
                    n0 += __shfl_xor_sync(0xffffffffu, n0, 1); n0 += __shfl_xor_sync(0xffffffffu, n0, 2);
                    n1 += __shfl_xor_sync(0xffffffffu, n1, 1); n1 += __shfl_xor_sync(0xffffffffu, n1, 2);
                    st = (n0 != n0 || n1 != n1) ? __int_as_float(0x7f800000) : fmaxf(n0, n1);
                } else {
                    const int s = key >> 4;
                    uint8_t* lo = g_vimg + s * 256 + g * 16 + 4 * t;
                    uint8_t* hi = g_vimg + 33024 + (127 - s) * 256 + g * 16 + 4 * t;
                    *(uint32_t*)(lo) = pk[0]; *(uint32_t*)(lo + 128) = pk[1]; *(uint32_t*)(hi) = pk[2]; *(uint32_t*)(hi + 128) = pk[3];
                    st = 0.0f;
                    #pragma unroll
                    for (int i = 0; i < 4; i++) {
                        float a = fabsf(bf_lo(pk[i])), b = fabsf(bf_hi(pk[i]));
                        st = (a != a || b != b) ? __int_as_float(0x7f800000) : fmaxf(st, fmaxf(a, b));
                    }
                }
                #pragma unroll
                for (int o = 16; o; o >>= 1) st = fmaxf(st, __shfl_xor_sync(0xffffffffu, st, o));
                if (lane == 0) g_stat[kv_sel][(qb * 2 + rowhalf) * 4 + wiw] = st;
                __threadfence();
                bar_sync(3, 128);
                if ((tid & 127) == 0) st_release(&g_flag_kv[(qb * 2 + rowhalf) * 2 + kv_sel], epoch);
            }
            const float QS = 0.25f * 1.4426950408889634f;
            float qm = 0.0f;
            #pragma unroll
            for (int i = 0; i < 2; i++) {
                #pragma unroll
                for (int j = 0; j < 4; j++) q[i][j] = pack_bf16(acc[8 * i + 2 * j] * QS, acc[8 * i + 2 * j + 1] * QS);
                float n0 = bf_lo(q[i][0]) * bf_lo(q[i][0]) + bf_hi(q[i][0]) * bf_hi(q[i][0]) + bf_lo(q[i][2]) * bf_lo(q[i][2]) + bf_hi(q[i][2]) * bf_hi(q[i][2]);
                float n1 = bf_lo(q[i][1]) * bf_lo(q[i][1]) + bf_hi(q[i][1]) * bf_hi(q[i][1]) + bf_lo(q[i][3]) * bf_lo(q[i][3]) + bf_hi(q[i][3]) * bf_hi(q[i][3]);
                n0 += __shfl_xor_sync(0xffffffffu, n0, 1); n0 += __shfl_xor_sync(0xffffffffu, n0, 2);
                n1 += __shfl_xor_sync(0xffffffffu, n1, 1); n1 += __shfl_xor_sync(0xffffffffu, n1, 2);
                qm = (n0 != n0 || n1 != n1) ? __int_as_float(0x7f800000) : fmaxf(qm, fmaxf(n0, n1));
            }
            #pragma unroll
            for (int o = 16; o; o >>= 1) qm = fmaxf(qm, __shfl_xor_sync(0xffffffffu, qm, o));
            if (lane == 0) s_misc[warp] = qm;
        }
        bar_sync(1, 512);
        PROF(3);
        if (warp == 0) {
            wait_flag(&g_flag_kv[lane], epoch);
            wait_flag(&g_flag_kv[lane + 32], epoch);
            __syncwarp();
            PROF(5);
            if (lane == 0) {
                fence_async_all();
                mbar_expect_tx(bar_kv, 131072);
                for (int i = 0; i < 4; i++) bulk_g2s(sb + SM_K + i * 16384, g_kimg + i * 16384, 16384, bar_kv);
                for (int i = 0; i < 2; i++) bulk_g2s(sb + SM_V + i * 16384, g_vimg + i * 16384, 16384, bar_kv);
                for (int i = 0; i < 2; i++) bulk_g2s(sb + SM_V + 33024 + i * 16384, g_vimg + 33024 + i * 16384, 16384, bar_kv);
            }
            float km = 0.0f, vm = 0.0f;
            #pragma unroll
            for (int i = 0; i < 4; i++) {
                km = fmaxf(km, __ldcg(&g_stat[0][lane * 4 + i]));
                vm = fmaxf(vm, __ldcg(&g_stat[1][lane * 4 + i]));
            }
            #pragma unroll
            for (int o = 16; o; o >>= 1) { km = fmaxf(km, __shfl_xor_sync(0xffffffffu, km, o)); vm = fmaxf(vm, __shfl_xor_sync(0xffffffffu, vm, o)); }
            if (lane == 0) { s_misc[16] = km; s_misc[17] = vm; }
        } else if (warp < 3) {
            *(uint32_t*)(sp + SM_V + 32768 + (tid - 32) * 4) = 0x3F803F80u;
            fence_async_smem();
        }
        bar_sync(1, 512);

        {
            float qm = 0.0f;
            #pragma unroll
            for (int i = 0; i < 16; i++) qm = fmaxf(qm, s_misc[i]);
            const float vm = s_misc[17];
            const bool fast = (qm * s_misc[16] <= 60.0f * 60.0f) && (vm <= 1.0e12f) && (vm >= 1.0e-12f || vm == 0.0f);

            mbar_wait(bar_kv, 0);
            PROF(9);
            const uint64_t dVstep = 16ull - (16ull << 32);
            uint8_t* ob = g_oimg + qb * 131072 + hg * 16384 + nh * 8192 + (rowhalf * 8 + wiw * 2) * 128 + g * 16 + 4 * t;
            uint32_t cA = 0xBF00BF00u, cB = 0x00030003u;
            asm volatile("" : "+r"(cA), "+r"(cB));
            #pragma unroll 1
            for (int tile = 0; tile < 2; tile++) {
                uint64_t dK = make_desc(sb + SM_K, 128, 256, 0);
                uint64_t dV = make_desc(sb + SM_V, 128, 32768, 0);
                float o[12], s[32];
                uint32_t p[16], qq[4];
                #pragma unroll
                for (int i = 0; i < 4; i++) qq[i] = tile ? q[1][i] : q[0][i];
                #pragma unroll
                for (int i = 0; i < 12; i++) o[i] = 0.0f;
                #pragma unroll
                for (int i = 0; i < 32; i++) s[i] = 0.0f;
                fence_regs<12>(o);
                fence_regs<32>(s);
                if (fast) {
                    #pragma unroll 1
                    for (int c = 0; c < SEQ / 256; c++) {
                        wg_fence();
                        wg_qk(s, qq, dK);
                        wg_commit();
                        #pragma unroll
                        for (int u = 0; u < 4; u++) {
                            wg_wait<0>();
                            fence_regs<32>(s);
                            #pragma unroll
                            for (int i = 0; i < 16; i++) {
                                if ((MUFU_MASK >> i) & 1) p[i] = exp_mufu(s[2 * i], s[2 * i + 1]);
                                else p[i] = exp_sw(s[2 * i], s[2 * i + 1], cA, cB);
                            }
                            wg_fence();
                            if (u + 1 < 4) wg_qk(s, qq, dK + (u + 1) * 128);
                            #pragma unroll
                            for (int kk = 0; kk < 4; kk++) wg_pv(o, p + 4 * kk, dV + (u * 4 + kk) * dVstep);
                            wg_commit();
                        }
                        dK += 512;
                        dV += 16 * dVstep;
                    }
                    wg_wait<0>();
                } else {
                    float mx0 = -INFINITY, mx1 = -INFINITY;
                    #pragma unroll 1
                    for (int c = 0; c < SEQ / 64; c++) {
                        wg_fence();
                        wg_qk(s, qq, dK);
                        wg_commit();
                        wg_wait<0>();
                        fence_regs<32>(s);
                        fence_regs<12>(o);
                        float m0 = mx0, m1 = mx1;
                        #pragma unroll
                        for (int j = 0; j < 8; j++) {
                            m0 = fmaxf(m0, fmaxf(s[4 * j], s[4 * j + 1]));
                            m1 = fmaxf(m1, fmaxf(s[4 * j + 2], s[4 * j + 3]));
                        }
                        m0 = fmaxf(m0, __shfl_xor_sync(0xffffffffu, m0, 1)); m0 = fmaxf(m0, __shfl_xor_sync(0xffffffffu, m0, 2));
                        m1 = fmaxf(m1, __shfl_xor_sync(0xffffffffu, m1, 1)); m1 = fmaxf(m1, __shfl_xor_sync(0xffffffffu, m1, 2));
                        const float c0 = ex2f(mx0 - m0), c1 = ex2f(mx1 - m1);
                        mx0 = m0; mx1 = m1;
                        #pragma unroll
                        for (int j = 0; j < 3; j++) { o[4 * j] *= c0; o[4 * j + 1] *= c0; o[4 * j + 2] *= c1; o[4 * j + 3] *= c1; }
                        #pragma unroll
                        for (int j = 0; j < 8; j++) {
                            p[2 * j] = exp_mufu(s[4 * j] - m0, s[4 * j + 1] - m0);
                            p[2 * j + 1] = exp_mufu(s[4 * j + 2] - m1, s[4 * j + 3] - m1);
                        }
                        wg_fence();
                        #pragma unroll
                        for (int kk = 0; kk < 4; kk++) wg_pv(o, p + 4 * kk, dV + kk * dVstep);
                        wg_commit();
                        wg_wait<0>();
                        dK += 128;
                        dV += 4 * dVstep;
                    }
                }
                fence_regs<12>(o);
                const float i0 = 1.0f / o[4], i1 = 1.0f / o[6];
                uint8_t* b = ob + tile * 4096;
                *(uint32_t*)(b) = pack_bf16(o[0] * i0, o[1] * i0);
                *(uint32_t*)(b + 128) = pack_bf16(o[2] * i1, o[3] * i1);
                *(uint32_t*)(b + 2048) = pack_bf16(o[8] * i0, o[9] * i0);
                *(uint32_t*)(b + 2048 + 128) = pack_bf16(o[10] * i1, o[11] * i1);
            }
            __threadfence();
        }
        PROF(10);
        bar_sync(1, 512);
        PROF(11);
        if (warp == 0) {
            if (lane == 0) st_release(&g_flag_o[blockIdx.x], epoch);
            if (lane < 8) {
                wait_flag(&g_flag_o[qb * 8 + lane], epoch);
                fence_async_all();
                mbar_expect_tx(bar_o + 8 * lane, 16384);
                bulk_g2s(sb + SM_A + lane * 16384, g_oimg + qb * 131072 + lane * 16384, 16384, bar_o + 8 * lane);
            }
            __syncwarp();
        }

        {
            float acc[16];
            #pragma unroll
            for (int i = 0; i < 16; i++) acc[i] = 0.0f;
            fence_regs<16>(acc);
            const uint64_t dA = make_desc(sb + SM_A + rowhalf * 1024, 2048, 128, 0);
            const uint64_t dB = make_desc(sb + SM_B + nh * 64, 16, 1024, 1);
            mbar_wait(bar_wo, 0);
            #pragma unroll 1
            for (int i = 0; i < 8; i++) {
                const int src = (hg + i) & 7;
                mbar_wait(bar_o + 8 * src, 0);
                wg_fence();
                #pragma unroll
                for (int kk = 0; kk < 4; kk++) wg_ss32(acc, dA + src * 1024 + kk * 256, dB + (src * 4 + kk) * 128);
                wg_commit();
            }
            wg_wait<0>();
            fence_regs<16>(acc);
            PROF(12);
            const int row = qb * 128 + rowhalf * 64 + wiw * 16 + g;
            uint32_t* o32 = (uint32_t*)(P.out + (size_t)row * 1024 + hg * 64 + nh * 32 + 2 * t);
            #pragma unroll
            for (int j = 0; j < 4; j++) {
                o32[4 * j] = pack_bf16(acc[4 * j], acc[4 * j + 1]);
                o32[4 * j + 8 * 512] = pack_bf16(acc[4 * j + 2], acc[4 * j + 3]);
            }
        }
        PROF(13);
        if (tid == 0) {
            const unsigned prev = atomicAdd(&g_done, 1u);
            if (prev == NCTA - 1) {
                g_done = 0;
                __threadfence();
                *(volatile unsigned*)&g_epoch = epoch;
            }
        }
    }
}

typedef CUresult (*EncodeFn)(CUtensorMap*, CUtensorMapDataType, cuuint32_t, void*, const cuuint64_t*, const cuuint64_t*,
                             const cuuint32_t*, const cuuint32_t*, CUtensorMapInterleave, CUtensorMapSwizzle,
                             CUtensorMapL2promotion, CUtensorMapFloatOOBfill);

void make_map(EncodeFn fn, CUtensorMap* m, const void* ptr, uint64_t inner, uint64_t outer, uint32_t box_in, uint32_t box_out, CUtensorMapSwizzle swz) {
    cuuint64_t dims[2] = {inner, outer};
    cuuint64_t strides[1] = {inner * 2};
    cuuint32_t box[2] = {box_in, box_out};
    cuuint32_t es[2] = {1, 1};
    fn(m, CU_TENSOR_MAP_DATA_TYPE_BFLOAT16, 2, const_cast<void*>(ptr), dims, strides, box, es, CU_TENSOR_MAP_INTERLEAVE_NONE, swz,
       CU_TENSOR_MAP_L2_PROMOTION_L2_128B, CU_TENSOR_MAP_FLOAT_OOB_FILL_NONE);
}

}

extern "C" void kernel_launch(void* const* d_in, const int* in_sizes, int n_in, void* d_out, int out_size) {
    (void)in_sizes; (void)n_in; (void)out_size;
    static EncodeFn fn = nullptr;
    if (!fn) {
        void* p = nullptr;
        cudaDriverEntryPointQueryResult qr;
        cudaGetDriverEntryPoint("cuTensorMapEncodeTiled", &p, cudaEnableDefault, &qr);
        fn = (EncodeFn)p;
        cudaFuncSetAttribute(fused_kernel, cudaFuncAttributeMaxDynamicSharedMemorySize, SM_ALLOC);
    }
    CUtensorMap tx, twq, two, twk, twv;
    make_map(fn, &tx, d_in[0], 512, 2048, 64, 128, CU_TENSOR_MAP_SWIZZLE_128B);
    make_map(fn, &twq, d_in[1], 512, 512, 64, 64, CU_TENSOR_MAP_SWIZZLE_128B);
    make_map(fn, &twk, d_in[2], 16, 512, 8, 64, CU_TENSOR_MAP_SWIZZLE_NONE);
    make_map(fn, &twv, d_in[3], 16, 512, 8, 64, CU_TENSOR_MAP_SWIZZLE_NONE);
    make_map(fn, &two, d_in[4], 512, 512, 64, 256, CU_TENSOR_MAP_SWIZZLE_128B);
    Params P;
    P.u = (const __nv_bfloat16*)d_in[5];
    P.lar = (const __nv_bfloat16*)d_in[6];
    P.aim = (const __nv_bfloat16*)d_in[7];
    P.cre = (const __nv_bfloat16*)d_in[8];
    P.cim = (const __nv_bfloat16*)d_in[9];
    P.logdt = (const __nv_bfloat16*)d_in[10];
    P.dskip = (const __nv_bfloat16*)d_in[11];
    P.out = (__nv_bfloat16*)d_out;
    fused_kernel<<<NCTA, NTHR, SM_ALLOC>>>(tx, twq, two, twk, twv, P);
}
```

```cpp
#include <cuda_runtime.h>
#include <cuda_bf16.h>
#include <cuda_fp16.h>
#include <cuda.h>
#include <stdint.h>

namespace {

constexpr int SEQ = 2048;
constexpr int NCTA = 128, NTHR = 640;

constexpr int SM_A = 0;
constexpr int STG = 26624;
constexpr int SM_K = 0, SM_V = 65536;
constexpr int SM_B = 5 * STG;

constexpr int PADU = 288, ULEN = PADU + 2048;
constexpr int WPAD = 16, W2LEN = WPAD + 1536, W3LEN = WPAD + 1024;
constexpr int TABN = 2240;
constexpr int S_U = 0;
constexpr int S_W3 = S_U + 4 * ULEN * 2;
constexpr int S_W5 = S_W3 + 4 * W2LEN * 2;
constexpr int S_W7 = S_W5 + 4 * W2LEN * 2;
constexpr int S_W9 = S_W7 + 4 * W3LEN * 2;
constexpr int S_TAB = S_W9 + 4 * W3LEN * 2;
constexpr int S_KC = S_TAB + 4 * TABN * 2;
constexpr int S_END = S_KC + 16384;
constexpr int S_STG = S_TAB, S_Y = S_KC;
constexpr int SM_BAR = SM_B + S_END;
constexpr int SM_TOTAL = SM_BAR + 1024;
constexpr int SM_ALLOC = SM_TOTAL + 1024;
static_assert(SM_V + 65536 + 256 <= SM_B && SM_ALLOC <= 232448 && S_END >= 65536 && SM_BAR % 16 == 0, "smem map");

constexpr int TD0 = 0, TD1 = 560, CD = 544;
constexpr int TE0 = 1120, TE1 = 1168, CE = 1056;
constexpr int T2B = 1216, T2S = 160, T2C = 80, C2 = 80;
constexpr int T3B = 1856, T3S = 192, T3C = 96, C3 = 144;

constexpr int rne8(int t) {
    if (t < 256) return t;
    int sh = 0;
    while ((t >> sh) >= 256) sh++;
    int q = t >> sh, rem = t & ((1 << sh) - 1), half = 1 << (sh - 1);
    if (rem > half || (rem == half && (q & 1))) q++;
    return q << sh;
}
constexpr int kcidx(int p) {
    if (p < 256) return (p >> 3) * 24 + (p & 7);
    if (p < 512) return ((p - 256) >> 3) * 24 + 8 + (((p - 256) & 7) >> 1);
    if (p < 1024) { int q = p - 512, hi = q >> 8, rem = q & 255; return (rem >> 3) * 24 + 12 + 2 * hi + ((rem & 7) >> 2); }
    if (p < 2048) { int q = p - 1024; return ((q & 255) >> 3) * 24 + 16 + (q >> 8); }
    return 20;
}
constexpr int KC_ZERO = 23;
constexpr int tab_dense(int t) { return (t >= 0 && t <= 514) ? kcidx(rne8(t)) : KC_ZERO; }
constexpr int tab_extra(int t) { return (t >= 1027 && t <= 1028) ? kcidx(1024) : KC_ZERO; }
constexpr int tab_2(int s, int lag) { return (lag >= 32 && lag <= 63) ? kcidx(s == 0 ? 16 * (lag + 1) : 16 * lag + 4 * s) : KC_ZERO; }
constexpr int tab_3(int s, int lag) { return (lag >= 64 && lag <= 127) ? kcidx(s == 0 ? 16 * (lag + 1) : 16 * lag + 8) : KC_ZERO; }
struct TabMap {
    uint16_t v[TABN];
    constexpr TabMap() : v{} {
        for (int i = 0; i < 560; i++) { v[TD0 + i] = tab_dense(CD - i); v[TD1 + i] = tab_dense(CD + 1 - i); }
        for (int i = 0; i < 48; i++) { v[TE0 + i] = tab_extra(CE - i); v[TE1 + i] = tab_extra(CE + 1 - i); }
        for (int s = 0; s < 4; s++)
            for (int i = 0; i < T2C; i++) { v[T2B + s * T2S + i] = tab_2(s, C2 - i); v[T2B + s * T2S + T2C + i] = tab_2(s, C2 + 1 - i); }
        for (int s = 0; s < 2; s++)
            for (int i = 0; i < T3C; i++) { v[T3B + s * T3S + i] = tab_3(s, C3 - i); v[T3B + s * T3S + T3C + i] = tab_3(s, C3 + 1 - i); }
    }
};
__device__ const __align__(16) TabMap g_tabmap = TabMap();

__device__ __align__(1024) uint8_t g_kimg[65536];
__device__ __align__(1024) uint8_t g_vimg[65536 + 256];
__device__ __align__(1024) uint8_t g_oimg[16 * 131072];
__device__ float g_stat[2][128];
__device__ unsigned g_flag_kv[64];
__device__ unsigned g_flag_o[128];
__device__ unsigned g_epoch;
__device__ unsigned g_done;

#define PROF(i) do {} while (0)
#define PROF2(i) do {} while (0)

__device__ __forceinline__ uint32_t smem_u32(const void* p) { return (uint32_t)__cvta_generic_to_shared(p); }
__device__ __forceinline__ void mbar_init(uint32_t bar, uint32_t cnt) { asm volatile("mbarrier.init.shared::cta.b64 [%0], %1;" :: "r"(bar), "r"(cnt) : "memory"); }
__device__ __forceinline__ void mbar_expect_tx(uint32_t bar, uint32_t bytes) {
    asm volatile("mbarrier.arrive.expect_tx.shared::cta.b64 _, [%0], %1;" :: "r"(bar), "r"(bytes) : "memory"); }
__device__ __forceinline__ void mbar_wait(uint32_t bar, uint32_t parity) {
    uint32_t ok = 0;
    for (int it = 0; it < (1 << 22) && !ok; it++) {
        asm volatile("{ .reg .pred p; mbarrier.try_wait.parity.shared::cta.b64 p, [%1], %2; selp.u32 %0, 1, 0, p; }"
                     : "=r"(ok) : "r"(bar), "r"(parity) : "memory");
    }
}
__device__ __forceinline__ void tma_2d(uint32_t dst, const CUtensorMap* map, int c0, int c1, uint32_t bar) {
    asm volatile("cp.async.bulk.tensor.2d.shared::cluster.global.mbarrier::complete_tx::bytes [%0], [%1, {%3, %4}], [%2];"
                 :: "r"(dst), "l"((uint64_t)map), "r"(bar), "r"(c0), "r"(c1) : "memory");
}
__device__ __forceinline__ void bulk_g2s(uint32_t dst, const void* src, uint32_t bytes, uint32_t bar) {
    asm volatile("cp.async.bulk.shared::cluster.global.mbarrier::complete_tx::bytes [%0], [%1], %2, [%3];"
                 :: "r"(dst), "l"((uint64_t)src), "r"(bytes), "r"(bar) : "memory");
}
__device__ __forceinline__ void fence_async_all() { asm volatile("fence.proxy.async;" ::: "memory"); }
__device__ __forceinline__ void fence_async_smem() { asm volatile("fence.proxy.async.shared::cta;" ::: "memory"); }
__device__ __forceinline__ unsigned ld_acquire(const unsigned* p) {
    unsigned v; asm volatile("ld.acquire.gpu.global.u32 %0, [%1];" : "=r"(v) : "l"(p) : "memory"); return v; }
__device__ __forceinline__ void st_release(unsigned* p, unsigned v) { asm volatile("st.release.gpu.global.u32 [%0], %1;" :: "l"(p), "r"(v) : "memory"); }
__device__ __forceinline__ void wait_flag(const unsigned* p, unsigned epoch) {
    for (int it = 0; it < (1 << 22); it++) { if (ld_acquire(p) == epoch) break; }
}
__device__ __forceinline__ void bar_sync(int id, int n) { asm volatile("bar.sync %0, %1;" :: "r"(id), "r"(n) : "memory"); }
__device__ __forceinline__ void bar_arrive(int id, int n) { asm volatile("bar.arrive %0, %1;" :: "r"(id), "r"(n) : "memory"); }
__device__ __forceinline__ void mbar_arrive(uint32_t bar) { asm volatile("mbarrier.arrive.shared::cta.b64 _, [%0];" :: "r"(bar) : "memory"); }

__device__ __forceinline__ uint64_t make_desc(uint32_t saddr, uint32_t lbo, uint32_t sbo, uint32_t swz) {
    uint64_t d = 0;
    d |= (uint64_t)((saddr & 0x3FFFF) >> 4);
    d |= (uint64_t)((lbo >> 4) & 0x3FFF) << 16;
    d |= (uint64_t)((sbo >> 4) & 0x3FFF) << 32;
    d |= (uint64_t)swz << 62;
    return d;
}
__device__ __forceinline__ void wg_fence() { asm volatile("wgmma.fence.sync.aligned;" ::: "memory"); }
__device__ __forceinline__ void wg_commit() { asm volatile("wgmma.commit_group.sync.aligned;" ::: "memory"); }
template<int N> __device__ __forceinline__ void wg_wait() { asm volatile("wgmma.wait_group.sync.aligned %0;" :: "n"(N) : "memory"); }
#define A4(d, o) "+f"(d[o + 0]), "+f"(d[o + 1]), "+f"(d[o + 2]), "+f"(d[o + 3])
#define A16(d, o) A4(d, o), A4(d, o + 4), A4(d, o + 8), A4(d, o + 12)

__device__ __forceinline__ void wg_pv(float* d, const uint32_t* a, uint64_t desc) {
    asm volatile("wgmma.mma_async.sync.aligned.m64n24k16.f32.bf16.bf16 {%0,%1,%2,%3,%4,%5,%6,%7,%8,%9,%10,%11}, {%12,%13,%14,%15}, %16, 1, 1, 1, 1;"
                 : A4(d, 0), A4(d, 4), A4(d, 8) : "r"(a[0]), "r"(a[1]), "r"(a[2]), "r"(a[3]), "l"(desc));
}
__device__ __forceinline__ void wg_qk(float* d, const uint32_t* a, uint64_t desc) {
    asm volatile("wgmma.mma_async.sync.aligned.m64n64k16.f32.bf16.bf16 {%0,%1,%2,%3,%4,%5,%6,%7,%8,%9,%10,%11,%12,%13,%14,%15,%16,%17,%18,%19,%20,%21,%22,%23,%24,%25,%26,%27,%28,%29,%30,%31}, {%32,%33,%34,%35}, %36, 0, 1, 1, 0;"
                 : A16(d, 0), A16(d, 16) : "r"(a[0]), "r"(a[1]), "r"(a[2]), "r"(a[3]), "l"(desc));
}
__device__ __forceinline__ void wg_ss32(float* d, uint64_t da, uint64_t db) {
    asm volatile("wgmma.mma_async.sync.aligned.m64n32k16.f32.bf16.bf16 {%0,%1,%2,%3,%4,%5,%6,%7,%8,%9,%10,%11,%12,%13,%14,%15}, %16, %17, 1, 1, 1, 0, 1;"
                 : A16(d, 0) : "l"(da), "l"(db));
}
__device__ __forceinline__ void wg_ss16(float* d, uint64_t da, uint64_t db) {
    asm volatile("wgmma.mma_async.sync.aligned.m64n16k16.f32.bf16.bf16 {%0,%1,%2,%3,%4,%5,%6,%7}, %8, %9, 1, 1, 1, 0, 1;"
                 : A4(d, 0), A4(d, 4) : "l"(da), "l"(db));
}
template<int N> __device__ __forceinline__ void fence_regs(float* r) {
    #pragma unroll
    for (int i = 0; i < N; i++) asm volatile("" : "+f"(r[i]) :: "memory");
}
__device__ __forceinline__ void mma_bf16(float* d, uint32_t a0, uint32_t a1, uint32_t a2, uint32_t a3, uint32_t b0, uint32_t b1) {
    asm volatile("mma.sync.aligned.m16n8k16.row.col.f32.bf16.bf16.f32 {%0,%1,%2,%3}, {%4,%5,%6,%7}, {%8,%9}, {%0,%1,%2,%3};"
                 : "+f"(d[0]), "+f"(d[1]), "+f"(d[2]), "+f"(d[3]) : "r"(a0), "r"(a1), "r"(a2), "r"(a3), "r"(b0), "r"(b1));
}
__device__ __forceinline__ void mma_f16(float* d, const uint32_t* a, uint32_t b0, uint32_t b1) {
    asm volatile("mma.sync.aligned.m16n8k16.row.col.f32.f16.f16.f32 {%0,%1,%2,%3}, {%4,%5,%6,%7}, {%8,%9}, {%0,%1,%2,%3};"
                 : "+f"(d[0]), "+f"(d[1]), "+f"(d[2]), "+f"(d[3]) : "r"(a[0]), "r"(a[1]), "r"(a[2]), "r"(a[3]), "r"(b0), "r"(b1));
}
__device__ __forceinline__ void ldsm4(uint32_t* r, uint32_t addr) {
    asm volatile("ldmatrix.sync.aligned.m8n8.x4.shared.b16 {%0,%1,%2,%3}, [%4];" : "=r"(r[0]), "=r"(r[1]), "=r"(r[2]), "=r"(r[3]) : "r"(addr) : "memory");
}
__device__ __forceinline__ void ldsm4t(uint32_t* r, uint32_t addr) {
    asm volatile("ldmatrix.sync.aligned.m8n8.x4.trans.shared.b16 {%0,%1,%2,%3}, [%4];" : "=r"(r[0]), "=r"(r[1]), "=r"(r[2]), "=r"(r[3]) : "r"(addr) : "memory");
}
__device__ __forceinline__ uint32_t lds32(uint32_t addr) { uint32_t v; asm volatile("ld.shared.u32 %0, [%1];" : "=r"(v) : "r"(addr) : "memory"); return v; }
__device__ __forceinline__ float ex2f(float x) { float r; asm("ex2.approx.ftz.f32 %0, %1;" : "=f"(r) : "f"(x)); return r; }
__device__ __forceinline__ uint32_t pack_bf16(float lo, float hi) { uint32_t r; asm("cvt.rn.bf16x2.f32 %0, %1, %2;" : "=r"(r) : "f"(hi), "f"(lo)); return r; }
__device__ __forceinline__ uint32_t pack_f16(float lo, float hi) { uint32_t r; asm("cvt.rn.f16x2.f32 %0, %1, %2;" : "=r"(r) : "f"(hi), "f"(lo)); return r; }
__device__ __forceinline__ float bf_lo(uint32_t v) { return __uint_as_float(v << 16); }
__device__ __forceinline__ float bf_hi(uint32_t v) { return __uint_as_float(v & 0xFFFF0000u); }
__device__ __forceinline__ float bf_round(float x) { return __bfloat162float(__float2bfloat16_rn(x)); }

__device__ __forceinline__ uint32_t exp_mufu(float x0, float x1) { return pack_bf16(ex2f(x0), ex2f(x1)); }
#define SW_MAGIC (256.0f + 127.0f - 0.598938f)
__device__ __forceinline__ uint32_t exp_sw(float x0, float x1, uint32_t cA, uint32_t cB) {
    float t0 = x0 + SW_MAGIC, t1 = x1 + SW_MAGIC;
    uint32_t L, mh, ec, r;
    asm("prmt.b32 %0, %1, %2, 0x6521;" : "=r"(L) : "r"(__float_as_uint(t0)), "r"(__float_as_uint(t1)));
    asm("lop3.b32 %0, %1, 0x007F007F, %2, 0xEA;" : "=r"(mh) : "r"(L), "r"(cA));
    asm("lop3.b32 %0, %1, 0x7F807F80, %2, 0xEA;" : "=r"(ec) : "r"(L), "r"(cB));
    asm("fma.rn.bf16x2 %0, %1, %2, %3;" : "=r"(r) : "r"(L), "r"(mh), "r"(ec));
    return r;
}
constexpr uint32_t MUFU_MASK = 0x4949;

struct cf { float x, y; };
__device__ __forceinline__ cf cmul(cf a, cf b) { cf r; r.x = a.x * b.x - a.y * b.y; r.y = a.x * b.y + a.y * b.x; return r; }
__device__ __forceinline__ cf cexp_p(float a2, float b, float p) {
    float e = ex2f(a2 * p);
    float ph = b * p;
    ph -= (ph + 12582912.0f) - 12582912.0f;
    float ang = ph * 6.283185307f;
    cf r; r.x = e * __cosf(ang); r.y = e * __sinf(ang);
    return r;
}
__device__ __forceinline__ uint32_t h2_cmul(uint32_t w, uint32_t wsw, uint32_t e) {
    __half2 hw = *(__half2*)&w, hs = *(__half2*)&wsw, he = *(__half2*)&e;
    __half2 r = __hfma2(hs, __high2half2(he), __hmul2(hw, __low2half2(he)));
    return *(uint32_t*)&r;
}

template<bool B> struct BoolC { static constexpr bool value = B; };
struct Params {
    const __nv_bfloat16 *u, *lar, *aim, *cre, *cim, *logdt, *dskip;
    __nv_bfloat16* out;
};

__device__ __forceinline__ void aux_role(const Params& P, uint8_t* sp, uint32_t sb, const CUtensorMap* tm_wo,
                                         uint32_t bar_kv, uint32_t bar_wo, float* s_misc, unsigned epoch) {
    const int tid = threadIdx.x & 127, lane = tid & 31;
    const int d0 = blockIdx.x * 4;
    uint8_t* sB = sp + SM_B;
    {
        uint2 r[16];
        #pragma unroll
        for (int k = 0; k < 8; k++) {
            const int l = 2 * (tid + 128 * k);
            r[2 * k] = __ldg((const uint2*)(P.u + (size_t)l * 512 + d0));
            r[2 * k + 1] = __ldg((const uint2*)(P.u + (size_t)(l + 1) * 512 + d0));
        }
        for (int i = tid; i < 4 * (PADU / 8); i += 128)
            *(uint4*)(sB + S_U + (i / (PADU / 8)) * ULEN * 2 + (i % (PADU / 8)) * 16) = make_uint4(0, 0, 0, 0);
        #pragma unroll
        for (int k = 0; k < 8; k++) {
            const int l = 2 * (tid + 128 * k);
            uint32_t* dst = (uint32_t*)(sB + S_U + (PADU + l) * 2);
            dst[0] = __byte_perm(r[2 * k].x, r[2 * k + 1].x, 0x5410);
            dst[ULEN / 2] = __byte_perm(r[2 * k].x, r[2 * k + 1].x, 0x7632);
            dst[ULEN] = __byte_perm(r[2 * k].y, r[2 * k + 1].y, 0x5410);
            dst[3 * ULEN / 2] = __byte_perm(r[2 * k].y, r[2 * k + 1].y, 0x7632);
        }
    }
    const uint2 dsk = __ldg((const uint2*)(P.dskip + d0));
    bar_sync(2, 128);
    PROF2(1);
    #pragma unroll 1
    for (int task = tid; task < 4 * 194; task += 128) {
        const int c = task / 194, i = task % 194;
        const uint4* src = (const uint4*)(sB + S_U + c * ULEN * 2 + (PADU + 8 * i - WPAD - 8) * 2);
        const uint4 v0 = src[0], v1 = src[1], v2 = src[2];
        float x[24];
        const uint32_t vv[12] = {v0.x, v0.y, v0.z, v0.w, v1.x, v1.y, v1.z, v1.w, v2.x, v2.y, v2.z, v2.w};
        #pragma unroll
        for (int k = 0; k < 12; k++) { x[2 * k] = bf_lo(vv[k]); x[2 * k + 1] = bf_hi(vv[k]); }
        float w3[12], w5[8];
        #pragma unroll
        for (int e = 0; e < 12; e++) w3[e] = (x[3 + e] + x[4 + e]) + x[5 + e];
        #pragma unroll
        for (int e = 0; e < 8; e++) w5[e] = w3[4 + e] + (x[6 + e] + x[10 + e]);
        *(uint4*)(sB + S_W3 + c * W2LEN * 2 + i * 16) = make_uint4(pack_bf16(w3[0], w3[1]), pack_bf16(w3[2], w3[3]), pack_bf16(w3[4], w3[5]), pack_bf16(w3[6], w3[7]));
        *(uint4*)(sB + S_W5 + c * W2LEN * 2 + i * 16) = make_uint4(pack_bf16(w5[0], w5[1]), pack_bf16(w5[2], w5[3]), pack_bf16(w5[4], w5[5]), pack_bf16(w5[6], w5[7]));
        if (i < 130) {
            float w7[8], w9[8];
            #pragma unroll
            for (int e = 0; e < 8; e++) { w7[e] = w5[e] + (x[5 + e] + x[11 + e]); w9[e] = w7[e] + (x[4 + e] + x[12 + e]); }
            *(uint4*)(sB + S_W7 + c * W3LEN * 2 + i * 16) = make_uint4(pack_bf16(w7[0], w7[1]), pack_bf16(w7[2], w7[3]), pack_bf16(w7[4], w7[5]), pack_bf16(w7[6], w7[7]));
            *(uint4*)(sB + S_W9 + c * W3LEN * 2 + i * 16) = make_uint4(pack_bf16(w9[0], w9[1]), pack_bf16(w9[2], w9[3]), pack_bf16(w9[4], w9[5]), pack_bf16(w9[6], w9[7]));
        }
    }
    bar_arrive(9, 640);
    PROF2(2);
    bar_sync(8, 640);
    if (tid < 32) {
        wait_flag(&g_flag_kv[lane], epoch);
        wait_flag(&g_flag_kv[lane + 32], epoch);
        __syncwarp();
        if (lane == 0) {
            fence_async_all();
            mbar_expect_tx(bar_kv, 131072);
            for (int i = 0; i < 4; i++) bulk_g2s(sb + SM_K + i * 16384, g_kimg + i * 16384, 16384, bar_kv);
            for (int i = 0; i < 2; i++) bulk_g2s(sb + SM_V + i * 16384, g_vimg + i * 16384, 16384, bar_kv);
            for (int i = 0; i < 2; i++) bulk_g2s(sb + SM_V + 33024 + i * 16384, g_vimg + 33024 + i * 16384, 16384, bar_kv);
        }
        float km = 0.0f, vm = 0.0f;
        #pragma unroll
        for (int i = 0; i < 4; i++) {
            km = fmaxf(km, __ldcg(&g_stat[0][lane * 4 + i]));
            vm = fmaxf(vm, __ldcg(&g_stat[1][lane * 4 + i]));
        }
        #pragma unroll
        for (int o = 16; o; o >>= 1) { km = fmaxf(km, __shfl_xor_sync(0xffffffffu, km, o)); vm = fmaxf(vm, __shfl_xor_sync(0xffffffffu, vm, o)); }
        *(uint2*)(sp + SM_V + 32768 + lane * 8) = make_uint2(0x3F803F80u, 0x3F803F80u);
        fence_async_smem();
        __syncwarp();
        if (lane == 0) { s_misc[16] = km; s_misc[17] = vm; mbar_arrive(bar_kv); }
    }
    PROF2(3);
    bar_sync(10, 640);
    {
        uint32_t dd[4] = {__byte_perm(dsk.x, 0, 0x1010), __byte_perm(dsk.x, 0, 0x3232), __byte_perm(dsk.y, 0, 0x1010), __byte_perm(dsk.y, 0, 0x3232)};
        #pragma unroll 2
        for (int i = 0; i < 8; i++) {
            const int l = 2 * (tid + 128 * i);
            uint32_t r[4];
            #pragma unroll
            for (int cc = 0; cc < 4; cc++) {
                const uint32_t y2 = *(const uint32_t*)(sB + S_Y + cc * 4096 + l * 2);
                const uint32_t u2 = *(const uint32_t*)(sB + S_U + cc * ULEN * 2 + (PADU + l) * 2);
                __nv_bfloat162 pr = __hmul2(*(const __nv_bfloat162*)&u2, *(const __nv_bfloat162*)&dd[cc]);
                __nv_bfloat162 sm = __hadd2(*(const __nv_bfloat162*)&y2, pr);
                r[cc] = *(uint32_t*)&sm;
            }
            *(uint2*)(P.out + (size_t)l * 1024 + 512 + d0) = make_uint2(__byte_perm(r[0], r[1], 0x5410), __byte_perm(r[2], r[3], 0x5410));
            *(uint2*)(P.out + (size_t)(l + 1) * 1024 + 512 + d0) = make_uint2(__byte_perm(r[0], r[1], 0x7632), __byte_perm(r[2], r[3], 0x7632));
        }
    }
    bar_sync(2, 128);
    if (tid == 0) {
        fence_async_smem();
        mbar_expect_tx(bar_wo, 65536);
        for (int b = 0; b < 2; b++) tma_2d(sb + SM_B + b * 32768, tm_wo, (blockIdx.x & 7) * 64, b * 256, bar_wo);
    }
    PROF2(4);
}

__global__ void __launch_bounds__(NTHR, 1)
fused_kernel(const __grid_constant__ CUtensorMap tm_x, const __grid_constant__ CUtensorMap tm_wq,
             const __grid_constant__ CUtensorMap tm_wo, const __grid_constant__ CUtensorMap tm_wk,
             const __grid_constant__ CUtensorMap tm_wv, const Params P) {
    extern __shared__ uint8_t smem_raw[];
    const uint32_t sb = (smem_u32(smem_raw) + 1023u) & ~1023u;
    uint8_t* sp = smem_raw + (sb - smem_u32(smem_raw));

    const int tid = threadIdx.x, warp = tid >> 5, lane = tid & 31, wg = tid >> 7, wiw = warp & 3;
    const int g = lane >> 2, t = lane & 3;
    const int qb = blockIdx.x >> 3, hg = blockIdx.x & 7;
    const int rowhalf = wg & 1, nh = wg >> 1;
    const bool kv_cta = hg < 4;
    const int kv_sel = hg >> 1;
    const bool kv_wg = kv_cta && (wg == (hg & 1));

    const uint32_t bar_x = sb + SM_BAR, bar_o = bar_x + 64, bar_kv = bar_x + 128, bar_wo = bar_x + 136;
    float* s_misc = (float*)(sp + SM_BAR + 256);
    const CUtensorMap* tm_kv = kv_sel ? &tm_wv : &tm_wk;

    PROF(0);
    auto issue_chunk = [&](int ch) {
        const uint32_t st = sb + SM_A + (ch % 5) * STG, bar = bar_x + 8 * ch;
        mbar_expect_tx(bar, 24576 + (kv_cta ? 2048 : 0));
        tma_2d(st, &tm_x, ch * 64, qb * 128, bar);
        tma_2d(st + 16384, &tm_wq, hg * 64, ch * 64, bar);
        if (kv_cta) { tma_2d(st + 24576, tm_kv, 0, ch * 64, bar); tma_2d(st + 25600, tm_kv, 8, ch * 64, bar); }
    };
    if (tid == 0) {
        for (int i = 0; i < 18; i++) mbar_init(bar_x + 8 * i, i == 16 ? 2 : 1);
        asm volatile("fence.mbarrier_init.release.cluster;" ::: "memory");
        fence_async_smem();
        for (int ch = 0; ch < 5; ch++) issue_chunk(ch);
    }
    const unsigned epoch = *(volatile unsigned*)&g_epoch + 1u;
    __syncthreads();

    if (wg == 4) {
        aux_role(P, sp, sb, &tm_wo, bar_kv, bar_wo, s_misc, epoch);
    } else {
        const int d0 = blockIdx.x * 4;
        if (tid < TABN * 2 / 128 + 1) asm volatile("prefetch.global.L2 [%0];" :: "l"((const char*)g_tabmap.v + tid * 128));
        {
            const int c = warp >> 2, d = d0 + c, n = (warp & 3) * 32 + lane;
            const float dt = bf_round(expf(__bfloat162float(P.logdt[d])));
            const float are = -bf_round(expf(__bfloat162float(P.lar[d * 128 + n]))) * dt;
            const float aim = __bfloat162float(P.aim[d * 128 + n]) * dt;
            float cr = 2.0f * (__bfloat162float(P.cre[d * 128 + n]) * dt);
            float ci = 2.0f * (__bfloat162float(P.cim[d * 128 + n]) * dt);
            const float a2 = are * 1.4426950408889634f, bb = aim * 0.15915494309189535f;
            float m = fmaxf(fabsf(cr), fabsf(ci));
            #pragma unroll
            for (int o = 16; o; o >>= 1) m = fmaxf(m, __shfl_xor_sync(0xffffffffu, m, o));
            int ebits = (__float_as_uint(m) >> 23) & 0xFF;
            ebits = min(max(ebits, 2), 250);
            const float scale = __uint_as_float((uint32_t)(ebits + 1) << 23);
            const float iscale = __uint_as_float((uint32_t)(253 - ebits) << 23);
            cf cc; cc.x = cr * iscale; cc.y = ci * iscale;

            const uint32_t stg = sb + SM_B + S_STG + warp * 1024;
            uint4* stp = (uint4*)(sp + SM_B + S_STG + warp * 1024 + lane * 32);
            const uint32_t fa = stg + t * 32 + g * 4;

            uint32_t af[4][2][4];
            cf E256;
            {
                const cf E8 = cexp_p(a2, bb, 8.0f);
                uint32_t w[8];
                cf cur; cur.x = 1.0f; cur.y = 0.0f;
                w[0] = pack_f16(1.0f, 0.0f);
                cur = E8; w[1] = pack_f16(cur.x, cur.y);
                #pragma unroll
                for (int i = 2; i < 8; i++) { cur = cmul(cur, E8); w[i] = pack_f16(cur.x, cur.y); }
                stp[0] = make_uint4(w[0], w[1], w[2], w[3]);
                stp[1] = make_uint4(w[4], w[5], w[6], w[7]);
                const cf E64 = cexp_p(a2, bb, 64.0f);
                const cf E128 = cmul(E64, E64), E192 = cmul(E128, E64);
                E256 = cexp_p(a2, bb, 256.0f);
                const uint32_t e1 = pack_f16(E64.x, E64.y), e2 = pack_f16(E128.x, E128.y), e3 = pack_f16(E192.x, E192.y);
                __syncwarp();
                #pragma unroll
                for (int s = 0; s < 4; s++) {
                    #pragma unroll
                    for (int hh = 0; hh < 2; hh++) {
                        const uint32_t w0 = lds32(fa + s * 256 + hh * 128);
                        const uint32_t wsw = __byte_perm(w0, 0, 0x1032) ^ 0x00008000u;
                        const int src = 8 * s + t + 4 * hh;
                        const uint32_t f1 = __shfl_sync(0xffffffffu, e1, src), f2 = __shfl_sync(0xffffffffu, e2, src), f3 = __shfl_sync(0xffffffffu, e3, src);
                        af[s][0][2 * hh] = w0;
                        af[s][0][2 * hh + 1] = h2_cmul(w0, wsw, f1);
                        af[s][1][2 * hh] = h2_cmul(w0, wsw, f2);
                        af[s][1][2 * hh + 1] = h2_cmul(w0, wsw, f3);
                    }
                }
                __syncwarp();
            }
            float acc[2][3][4];
            #pragma unroll
            for (int i = 0; i < 24; i++) (&acc[0][0][0])[i] = 0.0f;
            const cf E1 = cexp_p(a2, bb, 1.0f);
            const cf E2 = cmul(E1, E1), E4 = cmul(E2, E2);
            cf X512;
            #pragma unroll
            for (int nt = 0; nt < 3; nt++) {
                uint32_t xv[8];
                if (nt == 0) {
                    cf cur = cc;
                    xv[0] = pack_f16(cur.x, -cur.y);
                    #pragma unroll
                    for (int i = 1; i < 8; i++) { cur = cmul(cur, E1); xv[i] = pack_f16(cur.x, -cur.y); }
                } else if (nt == 1) {
                    cf cur = cmul(cc, E256);
                    X512 = cmul(cur, E256);
                    xv[0] = pack_f16(cur.x, -cur.y);
                    #pragma unroll
                    for (int i = 1; i < 4; i++) { cur = cmul(cur, E2); xv[i] = pack_f16(cur.x, -cur.y); }
                    cur = cmul(X512, E4);
                    xv[4] = pack_f16(X512.x, -X512.y); xv[5] = pack_f16(cur.x, -cur.y);
                    X512 = cmul(X512, E256);
                    cur = cmul(X512, E4);
                    xv[6] = pack_f16(X512.x, -X512.y); xv[7] = pack_f16(cur.x, -cur.y);
                } else {
                    cf cur = X512;
                    #pragma unroll
                    for (int i = 0; i < 5; i++) { cur = cmul(cur, E256); xv[i] = pack_f16(cur.x, -cur.y); }
                    xv[5] = 0; xv[6] = 0; xv[7] = 0;
                }
                stp[0] = make_uint4(xv[0], xv[1], xv[2], xv[3]);
                stp[1] = make_uint4(xv[4], xv[5], xv[6], xv[7]);
                __syncwarp();
                #pragma unroll
                for (int s = 0; s < 4; s++) {
                    const uint32_t b0 = lds32(fa + s * 256), b1 = lds32(fa + s * 256 + 128);
                    mma_f16(acc[0][nt], af[s][0], b0, b1);
                    mma_f16(acc[1][nt], af[s][1], b0, b1);
                }
                __syncwarp();
            }
            float* kc = (float*)(sp + SM_B + S_KC + c * 4096);
            #pragma unroll 1
            for (int step = 0; step < 4; step++) {
                if ((warp & 3) == step) {
                    #pragma unroll
                    for (int mt = 0; mt < 2; mt++)
                        #pragma unroll
                        for (int nt = 0; nt < 3; nt++)
                            #pragma unroll
                            for (int hh = 0; hh < 2; hh++) {
                                float2* p = (float2*)(kc + (mt * 16 + hh * 8 + g) * 24 + nt * 8 + 2 * t);
                                float2 v = make_float2(acc[mt][nt][2 * hh] * scale, acc[mt][nt][2 * hh + 1] * scale);
                                if (step) { float2 o = *p; v.x += o.x; v.y += o.y; }
                                *p = v;
                            }
                }
                if (step < 3) bar_sync(4 + c, 128);
            }
        }

        PROF(1);
        uint32_t q[2][4];
        {
            float acc[16], akv[8];
            #pragma unroll
            for (int i = 0; i < 16; i++) acc[i] = 0.0f;
            #pragma unroll
            for (int i = 0; i < 8; i++) akv[i] = 0.0f;
            fence_regs<16>(acc);
            fence_regs<8>(akv);
            const uint64_t dA = make_desc(sb + SM_A + rowhalf * 8192, 16, 1024, 1);
            const uint64_t dB = make_desc(sb + SM_A + 16384 + nh * 64, 16, 1024, 1);
            const uint64_t dC = make_desc(sb + SM_A + 24576, 128, 1024, 0);
            auto proj_loop = [&](auto KV) {
                #pragma unroll 1
                for (int ch = 0; ch < 8; ch++) {
                    const uint32_t so = (ch % 5) * (STG / 16);
                    mbar_wait(bar_x + 8 * ch, 0);
                    if (ch == 0) PROF(2);
                    wg_fence();
                    if (decltype(KV)::value) {
                        #pragma unroll
                        for (int ks = 0; ks < 4; ks++) wg_ss16(akv, dA + so + ks * 2, dC + so + ks * 16);
                    }
                    #pragma unroll
                    for (int ks = 0; ks < 4; ks++) wg_ss32(acc, dA + so + ks * 2, dB + so + ks * 128);
                    wg_commit();
                    if (ch == 2) {
                        wg_wait<0>();
                        bar_sync(1, 512);
                        if (tid == 0) { for (int c2 = 5; c2 < 8; c2++) issue_chunk(c2); }
                    }
                }
                wg_wait<0>();
            };
            if (kv_wg) proj_loop(BoolC<true>()); else proj_loop(BoolC<false>());
            fence_regs<16>(acc);
            fence_regs<8>(akv);
            if (kv_wg) {
                const int key = qb * 128 + rowhalf * 64 + wiw * 16 + g;
                uint32_t pk[4];
                #pragma unroll
                for (int i = 0; i < 4; i++) pk[i] = pack_bf16(akv[2 * i], akv[2 * i + 1]);
                float st;
                if (kv_sel == 0) {
                    uint8_t* b = g_kimg + (key >> 3) * 256 + (key & 7) * 16 + 4 * t;
                    *(uint32_t*)(b) = pk[0]; *(uint32_t*)(b + 256) = pk[1]; *(uint32_t*)(b + 128) = pk[2]; *(uint32_t*)(b + 384) = pk[3];
                    float n0 = bf_lo(pk[0]) * bf_lo(pk[0]) + bf_hi(pk[0]) * bf_hi(pk[0]) + bf_lo(pk[2]) * bf_lo(pk[2]) + bf_hi(pk[2]) * bf_hi(pk[2]);
                    float n1 = bf_lo(pk[1]) * bf_lo(pk[1]) + bf_hi(pk[1]) * bf_hi(pk[1]) + bf_lo(pk[3]) * bf_lo(pk[3]) + bf_hi(pk[3]) * bf_hi(pk[3]);
                    n0 += __shfl_xor_sync(0xffffffffu, n0, 1); n0 += __shfl_xor_sync(0xffffffffu, n0, 2);
                    n1 += __shfl_xor_sync(0xffffffffu, n1, 1); n1 += __shfl_xor_sync(0xffffffffu, n1, 2);
                    st = (n0 != n0 || n1 != n1) ? __int_as_float(0x7f800000) : fmaxf(n0, n1);
                } else {
                    const int s = key >> 4;
                    uint8_t* lo = g_vimg + s * 256 + g * 16 + 4 * t;
                    uint8_t* hi = g_vimg + 33024 + (127 - s) * 256 + g * 16 + 4 * t;
                    *(uint32_t*)(lo) = pk[0]; *(uint32_t*)(lo + 128) = pk[1]; *(uint32_t*)(hi) = pk[2]; *(uint32_t*)(hi + 128) = pk[3];
                    st = 0.0f;
                    #pragma unroll
                    for (int i = 0; i < 4; i++) {
                        float a = fabsf(bf_lo(pk[i])), b = fabsf(bf_hi(pk[i]));
                        st = (a != a || b != b) ? __int_as_float(0x7f800000) : fmaxf(st, fmaxf(a, b));
                    }
                }
                #pragma unroll
                for (int o = 16; o; o >>= 1) st = fmaxf(st, __shfl_xor_sync(0xffffffffu, st, o));
                if (lane == 0) g_stat[kv_sel][(qb * 2 + rowhalf) * 4 + wiw] = st;
                __threadfence();
                bar_sync(3, 128);
                if ((tid & 127) == 0) st_release(&g_flag_kv[(qb * 2 + rowhalf) * 2 + kv_sel], epoch);
            }
            const float QS = 0.25f * 1.4426950408889634f;
            float qm = 0.0f;
            #pragma unroll
            for (int i = 0; i < 2; i++) {
                #pragma unroll
                for (int j = 0; j < 4; j++) q[i][j] = pack_bf16(acc[8 * i + 2 * j] * QS, acc[8 * i + 2 * j + 1] * QS);
                float n0 = bf_lo(q[i][0]) * bf_lo(q[i][0]) + bf_hi(q[i][0]) * bf_hi(q[i][0]) + bf_lo(q[i][2]) * bf_lo(q[i][2]) + bf_hi(q[i][2]) * bf_hi(q[i][2]);
                float n1 = bf_lo(q[i][1]) * bf_lo(q[i][1]) + bf_hi(q[i][1]) * bf_hi(q[i][1]) + bf_lo(q[i][3]) * bf_lo(q[i][3]) + bf_hi(q[i][3]) * bf_hi(q[i][3]);
                n0 += __shfl_xor_sync(0xffffffffu, n0, 1); n0 += __shfl_xor_sync(0xffffffffu, n0, 2);
                n1 += __shfl_xor_sync(0xffffffffu, n1, 1); n1 += __shfl_xor_sync(0xffffffffu, n1, 2);
                qm = (n0 != n0 || n1 != n1) ? __int_as_float(0x7f800000) : fmaxf(qm, fmaxf(n0, n1));
            }
            #pragma unroll
            for (int o = 16; o; o >>= 1) qm = fmaxf(qm, __shfl_xor_sync(0xffffffffu, qm, o));
            if (lane == 0) s_misc[warp] = qm;
        }
        bar_sync(1, 512);
        bar_arrive(8, 640);
        PROF(3);
        uint8_t* sB = sp + SM_B;
        const uint32_t sBa = sb + SM_B;
        {
            const int c = tid >> 7;
            const float* kc = (const float*)(sB + S_KC + c * 4096);
            uint32_t* tab = (uint32_t*)(sB + S_TAB + c * TABN * 2);
            const uint32_t* map = (const uint32_t*)g_tabmap.v;
            uint32_t mp[9];
            #pragma unroll
            for (int i = 0; i < 9; i++) { const int w = (tid & 127) + 128 * i; mp[i] = (w < TABN / 2) ? __ldg(map + w) : 0u; }
            #pragma unroll
            for (int i = 0; i < 9; i++) { const int w = (tid & 127) + 128 * i; if (w < TABN / 2) tab[w] = pack_bf16(kc[mp[i] & 0xFFFF], kc[mp[i] >> 16]); }
        }
        bar_sync(9, 640);
        PROF(6);
        {
            const int c = warp >> 2, grp = (warp + c) & 3;
            float acc[4][4];
            #pragma unroll
            for (int i = 0; i < 16; i++) (&acc[0][0])[i] = 0.0f;
            const uint32_t tabc = sBa + S_TAB + c * TABN * 2;
            const int e2 = (g - 2 * t) * 2;
            const uint32_t tD = tabc + ((g & 1) ? (TD1 + CD + 1) : (TD0 + CD)) * 2 - e2;
            const uint32_t tE = tabc + ((g & 1) ? (TE1 + CE + 1) : (TE0 + CE)) * 2 - e2;
            const uint32_t t2 = tabc + (T2B + ((g & 1) ? (T2C + C2 + 1) : C2)) * 2 - e2;
            const uint32_t t3 = tabc + (T3B + ((g & 1) ? (T3C + C3 + 1) : C3)) * 2 - e2;
            const int mi = lane >> 3, r8 = lane & 7;
            const uint32_t ub = sBa + S_U + c * ULEN * 2 + (PADU + 16 * (8 * (mi >> 1) + r8) + 8 * (mi & 1)) * 2 + (4 * grp - 4) * 256;
            #pragma unroll 1
            for (int rho = 0; rho < 8; rho++) {
                uint32_t R[5][3];
                #pragma unroll
                for (int qq = 0; qq < 5; qq++) {
                    if (qq < 4 || rho < 2) {
                        const uint32_t a = tD - 32 * (rho + 8 * qq);
                        R[qq][0] = lds32(a + 16); R[qq][1] = lds32(a); R[qq][2] = lds32(a - 16);
                    } else { R[qq][0] = 0; R[qq][1] = 0; R[qq][2] = 0; }
                }
                #pragma unroll
                for (int jp = 0; jp < 4; jp++) {
                    if (grp == 0 && (jp == 0 || (jp == 1 && rho > 0))) continue;
                    if (jp == 0 && rho >= 2) {
                        uint32_t b[4];
                        ldsm4(b, ub + jp * 512 - rho * 32);
                        mma_bf16(acc[0], R[3][1], R[3][2], R[3][0], R[3][1], b[2], b[3]);
                        continue;
                    }
                    uint32_t b[4];
                    ldsm4(b, ub + jp * 512 - rho * 32);
                    #pragma unroll
                    for (int hh = 0; hh < 2; hh++) {
                        #pragma unroll
                        for (int qq = 0; qq < 5; qq++) {
                            const int jr = 2 * jp + hh + qq - 4;
                            if (jr >= 0 && jr < 4) {
                                if (qq < 4 || rho < 2) mma_bf16(acc[jr], R[qq][1], R[qq][2], R[qq][0], R[qq][1], b[2 * hh], b[2 * hh + 1]);
                            }
                        }
                    }
                }
            }
            if (grp >= 2) {
                uint32_t R[5];
                #pragma unroll
                for (int i = 0; i < 5; i++) R[i] = lds32(tE - 16 * (127 + i));
                #pragma unroll
                for (int kk = 0; kk < 2; kk++) {
                    #pragma unroll
                    for (int jp = 0; jp < 2; jp++) {
                        uint32_t b[4];
                        ldsm4(b, ub + (4 + 2 * jp) * 256 - (64 + kk) * 32);
                        mma_bf16(acc[2 * jp], R[2 * kk + 1], R[2 * kk + 2], R[2 * kk], R[2 * kk + 1], b[0], b[1]);
                        mma_bf16(acc[2 * jp + 1], R[2 * kk + 1], R[2 * kk + 2], R[2 * kk], R[2 * kk + 1], b[2], b[3]);
                    }
                }
            }
            const uint32_t soff = (WPAD + 16 * (8 * (mi >> 1) + r8) + 8 * (mi & 1)) * 2 + grp * 1024;
            if (grp >= 1) {
                #pragma unroll 1
                for (int s = 0; s < 4; s++) {
                    const uint32_t sig = sBa + ((s & 1) ? S_W3 : S_W5) + c * W2LEN * 2 + soff - ((s == 0) ? 32 : (s == 1) ? 0 : 16);
                    uint32_t R[7];
                    #pragma unroll
                    for (int i = 0; i < 7; i++) R[i] = lds32(t2 + s * (T2S * 2) - 16 * (3 + i));
                    #pragma unroll
                    for (int bb = 1; bb <= 4; bb++) {
                        if (2 * grp - bb < 0) continue;
                        uint32_t a[4];
                        ldsm4t(a, sig - bb * 512);
                        #pragma unroll
                        for (int jj = 0; jj < 4; jj++) {
                            const int h = jj + 2 * bb;
                            if (h >= 4 && h <= 9) mma_bf16(acc[jj], a[0], a[1], a[2], a[3], R[h - 3], R[h - 4]);
                        }
                    }
                }
            }
            if (grp >= 2) {
                #pragma unroll 1
                for (int s = 0; s < 2; s++) {
                    const uint32_t sig = sBa + (s ? S_W7 : S_W9) + c * W3LEN * 2 + soff - (s ? 16 : 32);
                    uint32_t R[9];
                    #pragma unroll
                    for (int i = 0; i < 9; i++) R[i] = lds32(t3 + s * (T3S * 2) - 16 * (7 + i));
                    #pragma unroll
                    for (int bb = 3; bb <= 6; bb++) {
                        if (2 * grp - bb < 0) continue;
                        uint32_t a[4];
                        ldsm4t(a, sig - bb * 512);
                        #pragma unroll
                        for (int jj = 0; jj < 4; jj++) {
                            const int h = jj + 2 * bb;
                            if (h >= 8 && h <= 15) mma_bf16(acc[jj], a[0], a[1], a[2], a[3], R[h - 7], R[h - 8]);
                        }
                    }
                }
            }
            __nv_bfloat16* ys = (__nv_bfloat16*)(sB + S_Y + c * 4096);
            #pragma unroll
            for (int jj = 0; jj < 4; jj++) {
                const int A = 8 * (4 * grp + jj) + 2 * t;
                ys[16 * A + g] = __float2bfloat16_rn(acc[jj][0]);
                ys[16 * A + 16 + g] = __float2bfloat16_rn(acc[jj][1]);
                ys[16 * A + g + 8] = __float2bfloat16_rn(acc[jj][2]);
                ys[16 * A + 16 + g + 8] = __float2bfloat16_rn(acc[jj][3]);
            }
        }
        bar_arrive(10, 640);
        PROF(7);
        {
            mbar_wait(bar_kv, 0);
            PROF(9);
            float qm = 0.0f;
            #pragma unroll
            for (int i = 0; i < 16; i++) qm = fmaxf(qm, s_misc[i]);
            const float vm = s_misc[17];
            const bool fast = (qm * s_misc[16] <= 60.0f * 60.0f) && (vm <= 1.0e12f) && (vm >= 1.0e-12f || vm == 0.0f);
            const uint64_t dVstep = 16ull - (16ull << 32);
            uint8_t* ob = g_oimg + qb * 131072 + hg * 16384 + nh * 8192 + (rowhalf * 8 + wiw * 2) * 128 + g * 16 + 4 * t;
            uint32_t cA = 0xBF00BF00u, cB = 0x00030003u;
            asm volatile("" : "+r"(cA), "+r"(cB));
            #pragma unroll 1
            for (int tile = 0; tile < 2; tile++) {
                uint64_t dK = make_desc(sb + SM_K, 128, 256, 0);
                uint64_t dV = make_desc(sb + SM_V, 128, 32768, 0);
                float o[12], s[32];
                uint32_t p[16], qq[4];
                #pragma unroll
                for (int i = 0; i < 4; i++) qq[i] = tile ? q[1][i] : q[0][i];
                #pragma unroll
                for (int i = 0; i < 12; i++) o[i] = 0.0f;
                #pragma unroll
                for (int i = 0; i < 32; i++) s[i] = 0.0f;
                fence_regs<12>(o);
                fence_regs<32>(s);
                if (fast) {
                    #pragma unroll 1
                    for (int c = 0; c < SEQ / 256; c++) {
                        wg_fence();
                        wg_qk(s, qq, dK);
                        wg_commit();
                        #pragma unroll
                        for (int u = 0; u < 4; u++) {
                            wg_wait<0>();
                            fence_regs<32>(s);
                            #pragma unroll
                            for (int i = 0; i < 16; i++) {
                                if ((MUFU_MASK >> i) & 1) p[i] = exp_mufu(s[2 * i], s[2 * i + 1]);
                                else p[i] = exp_sw(s[2 * i], s[2 * i + 1], cA, cB);
                            }
                            wg_fence();
                            if (u + 1 < 4) wg_qk(s, qq, dK + (u + 1) * 128);
                            #pragma unroll
                            for (int kk = 0; kk < 4; kk++) wg_pv(o, p + 4 * kk, dV + (u * 4 + kk) * dVstep);
                            wg_commit();
                        }
                        dK += 512;
                        dV += 16 * dVstep;
                    }
                    wg_wait<0>();
                } else {
                    float mx0 = -INFINITY, mx1 = -INFINITY;
                    #pragma unroll 1
                    for (int c = 0; c < SEQ / 64; c++) {
                        wg_fence();
                        wg_qk(s, qq, dK);
                        wg_commit();
                        wg_wait<0>();
                        fence_regs<32>(s);
                        fence_regs<12>(o);
                        float m0 = mx0, m1 = mx1;
                        #pragma unroll
                        for (int j = 0; j < 8; j++) {
                            m0 = fmaxf(m0, fmaxf(s[4 * j], s[4 * j + 1]));
                            m1 = fmaxf(m1, fmaxf(s[4 * j + 2], s[4 * j + 3]));
                        }
                        m0 = fmaxf(m0, __shfl_xor_sync(0xffffffffu, m0, 1)); m0 = fmaxf(m0, __shfl_xor_sync(0xffffffffu, m0, 2));
                        m1 = fmaxf(m1, __shfl_xor_sync(0xffffffffu, m1, 1)); m1 = fmaxf(m1, __shfl_xor_sync(0xffffffffu, m1, 2));
                        const float c0 = ex2f(mx0 - m0), c1 = ex2f(mx1 - m1);
                        mx0 = m0; mx1 = m1;
                        #pragma unroll
                        for (int j = 0; j < 3; j++) { o[4 * j] *= c0; o[4 * j + 1] *= c0; o[4 * j + 2] *= c1; o[4 * j + 3] *= c1; }
                        #pragma unroll
                        for (int j = 0; j < 8; j++) {
                            p[2 * j] = exp_mufu(s[4 * j] - m0, s[4 * j + 1] - m0);
                            p[2 * j + 1] = exp_mufu(s[4 * j + 2] - m1, s[4 * j + 3] - m1);
                        }
                        wg_fence();
                        #pragma unroll
                        for (int kk = 0; kk < 4; kk++) wg_pv(o, p + 4 * kk, dV + kk * dVstep);
                        wg_commit();
                        wg_wait<0>();
                        dK += 128;
                        dV += 4 * dVstep;
                    }
                }
                fence_regs<12>(o);
                const float i0 = 1.0f / o[4], i1 = 1.0f / o[6];
                uint8_t* b = ob + tile * 4096;
                *(uint32_t*)(b) = pack_bf16(o[0] * i0, o[1] * i0);
                *(uint32_t*)(b + 128) = pack_bf16(o[2] * i1, o[3] * i1);
                *(uint32_t*)(b + 2048) = pack_bf16(o[8] * i0, o[9] * i0);
                *(uint32_t*)(b + 2048 + 128) = pack_bf16(o[10] * i1, o[11] * i1);
            }
            __threadfence();
        }
        PROF(10);
        bar_sync(1, 512);
        PROF(11);
        if (warp == 0) {
            if (lane == 0) st_release(&g_flag_o[blockIdx.x], epoch);
            if (lane < 8) {
                wait_flag(&g_flag_o[qb * 8 + lane], epoch);
                fence_async_all();
                mbar_expect_tx(bar_o + 8 * lane, 16384);
                bulk_g2s(sb + SM_A + lane * 16384, g_oimg + qb * 131072 + lane * 16384, 16384, bar_o + 8 * lane);
            }
            __syncwarp();
        }

        {
            float acc[16];
            #pragma unroll
            for (int i = 0; i < 16; i++) acc[i] = 0.0f;
            fence_regs<16>(acc);
            const uint64_t dA = make_desc(sb + SM_A + rowhalf * 1024, 2048, 128, 0);
            const uint64_t dB = make_desc(sb + SM_B + nh * 64, 16, 1024, 1);
            mbar_wait(bar_wo, 0);
            #pragma unroll 1
            for (int i = 0; i < 8; i++) {
                const int src = (hg + i) & 7;
                mbar_wait(bar_o + 8 * src, 0);
                wg_fence();
                #pragma unroll
                for (int kk = 0; kk < 4; kk++) wg_ss32(acc, dA + src * 1024 + kk * 256, dB + (src * 4 + kk) * 128);
                wg_commit();
            }
            wg_wait<0>();
            fence_regs<16>(acc);
            PROF(12);
            const int row = qb * 128 + rowhalf * 64 + wiw * 16 + g;
            uint32_t* o32 = (uint32_t*)(P.out + (size_t)row * 1024 + hg * 64 + nh * 32 + 2 * t);
            #pragma unroll
            for (int j = 0; j < 4; j++) {
                o32[4 * j] = pack_bf16(acc[4 * j], acc[4 * j + 1]);
                o32[4 * j + 8 * 512] = pack_bf16(acc[4 * j + 2], acc[4 * j + 3]);
            }
        }
        PROF(13);
        if (tid == 0) {
            const unsigned prev = atomicAdd(&g_done, 1u);
            if (prev == NCTA - 1) {
                g_done = 0;
                __threadfence();
                *(volatile unsigned*)&g_epoch = epoch;
            }
        }
    }
}

typedef CUresult (*EncodeFn)(CUtensorMap*, CUtensorMapDataType, cuuint32_t, void*, const cuuint64_t*, const cuuint64_t*,
                             const cuuint32_t*, const cuuint32_t*, CUtensorMapInterleave, CUtensorMapSwizzle,
                             CUtensorMapL2promotion, CUtensorMapFloatOOBfill);

void make_map(EncodeFn fn, CUtensorMap* m, const void* ptr, uint64_t inner, uint64_t outer, uint32_t box_in, uint32_t box_out, CUtensorMapSwizzle swz) {
    cuuint64_t dims[2] = {inner, outer};
    cuuint64_t strides[1] = {inner * 2};
    cuuint32_t box[2] = {box_in, box_out};
    cuuint32_t es[2] = {1, 1};
    fn(m, CU_TENSOR_MAP_DATA_TYPE_BFLOAT16, 2, const_cast<void*>(ptr), dims, strides, box, es, CU_TENSOR_MAP_INTERLEAVE_NONE, swz,
       CU_TENSOR_MAP_L2_PROMOTION_L2_128B, CU_TENSOR_MAP_FLOAT_OOB_FILL_NONE);
}

}

extern "C" void kernel_launch(void* const* d_in, const int* in_sizes, int n_in, void* d_out, int out_size) {
    (void)in_sizes; (void)n_in; (void)out_size;
    static EncodeFn fn = nullptr;
    if (!fn) {
        void* p = nullptr;
        cudaDriverEntryPointQueryResult qr;
        cudaGetDriverEntryPoint("cuTensorMapEncodeTiled", &p, cudaEnableDefault, &qr);
        fn = (EncodeFn)p;
        cudaFuncSetAttribute(fused_kernel, cudaFuncAttributeMaxDynamicSharedMemorySize, SM_ALLOC);
    }
    CUtensorMap tx, twq, two, twk, twv;
    make_map(fn, &tx, d_in[0], 512, 2048, 64, 128, CU_TENSOR_MAP_SWIZZLE_128B);
    make_map(fn, &twq, d_in[1], 512, 512, 64, 64, CU_TENSOR_MAP_SWIZZLE_128B);
    make_map(fn, &twk, d_in[2], 16, 512, 8, 64, CU_TENSOR_MAP_SWIZZLE_NONE);
    make_map(fn, &twv, d_in[3], 16, 512, 8, 64, CU_TENSOR_MAP_SWIZZLE_NONE);
    make_map(fn, &two, d_in[4], 512, 512, 64, 256, CU_TENSOR_MAP_SWIZZLE_128B);
    Params P;
    P.u = (const __nv_bfloat16*)d_in[5];
    P.lar = (const __nv_bfloat16*)d_in[6];
    P.aim = (const __nv_bfloat16*)d_in[7];
    P.cre = (const __nv_bfloat16*)d_in[8];
    P.cim = (const __nv_bfloat16*)d_in[9];
    P.logdt = (const __nv_bfloat16*)d_in[10];
    P.dskip = (const __nv_bfloat16*)d_in[11];
    P.out = (__nv_bfloat16*)d_out;
    fused_kernel<<<NCTA, NTHR, SM_ALLOC>>>(tx, twq, two, twk, twv, P);
}
```

```cpp
#include <cuda_runtime.h>
#include <cuda_bf16.h>
#include <cuda_fp16.h>
#include <cuda.h>
#include <stdint.h>

namespace {

constexpr int SEQ = 2048;
constexpr int NCTA = 128, NTHR = 640;

constexpr int SM_A = 0;
constexpr int STG = 26624;
constexpr int SM_K = 0, SM_V = 65536;
constexpr int SM_B = 5 * STG;

constexpr int PADU = 288, ULEN = PADU + 2048;
constexpr int WPAD = 16, W2LEN = WPAD + 1536, W3LEN = WPAD + 1024;
constexpr int TABN = 2240;
constexpr int S_U = 0;
constexpr int S_W3 = S_U + 4 * ULEN * 2;
constexpr int S_W5 = S_W3 + 4 * W2LEN * 2;
constexpr int S_W7 = S_W5 + 4 * W2LEN * 2;
constexpr int S_W9 = S_W7 + 4 * W3LEN * 2;
constexpr int S_TAB = S_W9 + 4 * W3LEN * 2;
constexpr int S_KC = S_TAB + 4 * TABN * 2;
constexpr int S_END = S_KC + 16384;
constexpr int S_Y = S_KC;
constexpr int SM_BAR = SM_B + S_END;
constexpr int SM_TOTAL = SM_BAR + 1024;
constexpr int SM_ALLOC = SM_TOTAL + 1024;
static_assert(SM_V + 65536 + 256 <= SM_B && SM_ALLOC <= 232448 && S_END >= 65536 && SM_BAR % 16 == 0, "smem map");

constexpr int TD0 = 0, TD1 = 560, CD = 544;
constexpr int TE0 = 1120, TE1 = 1168, CE = 1056;
constexpr int T2B = 1216, T2S = 160, T2C = 80, C2 = 80;
constexpr int T3B = 1856, T3S = 192, T3C = 96, C3 = 144;

constexpr int rne8(int t) {
    if (t < 256) return t;
    int sh = 0;
    while ((t >> sh) >= 256) sh++;
    int q = t >> sh, rem = t & ((1 << sh) - 1), half = 1 << (sh - 1);
    if (rem > half || (rem == half && (q & 1))) q++;
    return q << sh;
}
constexpr int kcidx(int p) {
    if (p < 256) return (p >> 3) * 24 + (p & 7);
    if (p < 512) return ((p - 256) >> 3) * 24 + 8 + (((p - 256) & 7) >> 1);
    if (p < 1024) { int q = p - 512, hi = q >> 8, rem = q & 255; return (rem >> 3) * 24 + 12 + 2 * hi + ((rem & 7) >> 2); }
    if (p < 2048) { int q = p - 1024; return ((q & 255) >> 3) * 24 + 16 + (q >> 8); }
    return 20;
}
constexpr int KC_ZERO = 23;
constexpr int tab_dense(int t) { return (t >= 0 && t <= 514) ? kcidx(rne8(t)) : KC_ZERO; }
constexpr int tab_extra(int t) { return (t >= 1027 && t <= 1028) ? kcidx(1024) : KC_ZERO; }
constexpr int tab_2(int s, int lag) { return (lag >= 32 && lag <= 63) ? kcidx(s == 0 ? 16 * (lag + 1) : 16 * lag + 4 * s) : KC_ZERO; }
constexpr int tab_3(int s, int lag) { return (lag >= 64 && lag <= 127) ? kcidx(s == 0 ? 16 * (lag + 1) : 16 * lag + 8) : KC_ZERO; }
struct TabMap {
    uint16_t v[TABN];
    constexpr TabMap() : v{} {
        for (int i = 0; i < 560; i++) { v[TD0 + i] = tab_dense(CD - i); v[TD1 + i] = tab_dense(CD + 1 - i); }
        for (int i = 0; i < 48; i++) { v[TE0 + i] = tab_extra(CE - i); v[TE1 + i] = tab_extra(CE + 1 - i); }
        for (int s = 0; s < 4; s++)
            for (int i = 0; i < T2C; i++) { v[T2B + s * T2S + i] = tab_2(s, C2 - i); v[T2B + s * T2S + T2C + i] = tab_2(s, C2 + 1 - i); }
        for (int s = 0; s < 2; s++)
            for (int i = 0; i < T3C; i++) { v[T3B + s * T3S + i] = tab_3(s, C3 - i); v[T3B + s * T3S + T3C + i] = tab_3(s, C3 + 1 - i); }
    }
};
__device__ const __align__(16) TabMap g_tabmap = TabMap();

__device__ __align__(1024) uint8_t g_kimg[65536];
__device__ __align__(1024) uint8_t g_vimg[65536 + 256];
__device__ __align__(1024) uint8_t g_oimg[16 * 131072];
__device__ float g_stat[2][128];
__device__ unsigned g_flag_kv[64];
__device__ unsigned g_flag_o[128];
__device__ unsigned g_epoch;
__device__ unsigned g_done;

#define PROF(i) do {} while (0)
#define PROF2(i) do {} while (0)

__device__ __forceinline__ uint32_t smem_u32(const void* p) { return (uint32_t)__cvta_generic_to_shared(p); }
__device__ __forceinline__ void mbar_init(uint32_t bar, uint32_t cnt) { asm volatile("mbarrier.init.shared::cta.b64 [%0], %1;" :: "r"(bar), "r"(cnt) : "memory"); }
__device__ __forceinline__ void mbar_expect_tx(uint32_t bar, uint32_t bytes) {
    asm volatile("mbarrier.arrive.expect_tx.shared::cta.b64 _, [%0], %1;" :: "r"(bar), "r"(bytes) : "memory"); }
__device__ __forceinline__ void mbar_wait(uint32_t bar, uint32_t parity) {
    uint32_t ok = 0;
    for (int it = 0; it < (1 << 22) && !ok; it++) {
        asm volatile("{ .reg .pred p; mbarrier.try_wait.parity.shared::cta.b64 p, [%1], %2; selp.u32 %0, 1, 0, p; }"
                     : "=r"(ok) : "r"(bar), "r"(parity) : "memory");
    }
}
__device__ __forceinline__ void tma_2d(uint32_t dst, const CUtensorMap* map, int c0, int c1, uint32_t bar) {
    asm volatile("cp.async.bulk.tensor.2d.shared::cluster.global.mbarrier::complete_tx::bytes [%0], [%1, {%3, %4}], [%2];"
                 :: "r"(dst), "l"((uint64_t)map), "r"(bar), "r"(c0), "r"(c1) : "memory");
}
__device__ __forceinline__ void bulk_g2s(uint32_t dst, const void* src, uint32_t bytes, uint32_t bar) {
    asm volatile("cp.async.bulk.shared::cluster.global.mbarrier::complete_tx::bytes [%0], [%1], %2, [%3];"
                 :: "r"(dst), "l"((uint64_t)src), "r"(bytes), "r"(bar) : "memory");
}
__device__ __forceinline__ void tma_2d_mc(uint32_t dst, const CUtensorMap* map, int c0, int c1, uint32_t bar) {
    asm volatile("cp.async.bulk.tensor.2d.shared::cluster.global.mbarrier::complete_tx::bytes.multicast::cluster [%0], [%1, {%3, %4}], [%2], %5;"
                 :: "r"(dst), "l"((uint64_t)map), "r"(bar), "r"(c0), "r"(c1), "h"((uint16_t)3) : "memory");
}
__device__ __forceinline__ void bulk_g2s_mc(uint32_t dst, const void* src, uint32_t bytes, uint32_t bar) {
    asm volatile("cp.async.bulk.shared::cluster.global.mbarrier::complete_tx::bytes.multicast::cluster [%0], [%1], %2, [%3], %4;"
                 :: "r"(dst), "l"((uint64_t)src), "r"(bytes), "r"(bar), "h"((uint16_t)3) : "memory");
}
__device__ __forceinline__ void pair_sync(uint32_t bar, uint32_t peer) {
    uint32_t ra;
    asm volatile("mapa.shared::cluster.u32 %0, %1, %2;" : "=r"(ra) : "r"(bar), "r"(peer));
    asm volatile("mbarrier.arrive.release.cluster.shared::cluster.b64 _, [%0];" :: "r"(ra) : "memory");
    asm volatile("mbarrier.arrive.release.cluster.shared::cta.b64 _, [%0];" :: "r"(bar) : "memory");
    uint32_t ok = 0;
    for (int it = 0; it < (1 << 22) && !ok; it++) {
        asm volatile("{ .reg .pred p; mbarrier.try_wait.parity.acquire.cluster.shared::cta.b64 p, [%1], 0; selp.u32 %0, 1, 0, p; }"
                     : "=r"(ok) : "r"(bar) : "memory");
    }
}
__device__ __forceinline__ void fence_async_all() { asm volatile("fence.proxy.async;" ::: "memory"); }
__device__ __forceinline__ void fence_async_smem() { asm volatile("fence.proxy.async.shared::cta;" ::: "memory"); }
__device__ __forceinline__ unsigned ld_acquire(const unsigned* p) {
    unsigned v; asm volatile("ld.acquire.gpu.global.u32 %0, [%1];" : "=r"(v) : "l"(p) : "memory"); return v; }
__device__ __forceinline__ void st_release(unsigned* p, unsigned v) { asm volatile("st.release.gpu.global.u32 [%0], %1;" :: "l"(p), "r"(v) : "memory"); }
__device__ __forceinline__ void wait_flag(const unsigned* p, unsigned epoch) {
    for (int it = 0; it < (1 << 22); it++) { if (ld_acquire(p) == epoch) break; }
}
__device__ __forceinline__ void bar_sync(int id, int n) { asm volatile("bar.sync %0, %1;" :: "r"(id), "r"(n) : "memory"); }
__device__ __forceinline__ void bar_arrive(int id, int n) { asm volatile("bar.arrive %0, %1;" :: "r"(id), "r"(n) : "memory"); }
__device__ __forceinline__ void mbar_arrive(uint32_t bar) { asm volatile("mbarrier.arrive.shared::cta.b64 _, [%0];" :: "r"(bar) : "memory"); }

__device__ __forceinline__ uint64_t make_desc(uint32_t saddr, uint32_t lbo, uint32_t sbo, uint32_t swz) {
    uint64_t d = 0;
    d |= (uint64_t)((saddr & 0x3FFFF) >> 4);
    d |= (uint64_t)((lbo >> 4) & 0x3FFF) << 16;
    d |= (uint64_t)((sbo >> 4) & 0x3FFF) << 32;
    d |= (uint64_t)swz << 62;
    return d;
}
__device__ __forceinline__ void wg_fence() { asm volatile("wgmma.fence.sync.aligned;" ::: "memory"); }
__device__ __forceinline__ void wg_commit() { asm volatile("wgmma.commit_group.sync.aligned;" ::: "memory"); }
template<int N> __device__ __forceinline__ void wg_wait() { asm volatile("wgmma.wait_group.sync.aligned %0;" :: "n"(N) : "memory"); }
#define A4(d, o) "+f"(d[o + 0]), "+f"(d[o + 1]), "+f"(d[o + 2]), "+f"(d[o + 3])
#define A16(d, o) A4(d, o), A4(d, o + 4), A4(d, o + 8), A4(d, o + 12)

__device__ __forceinline__ void wg_pv(float* d, const uint32_t* a, uint64_t desc) {
    asm volatile("wgmma.mma_async.sync.aligned.m64n24k16.f32.bf16.bf16 {%0,%1,%2,%3,%4,%5,%6,%7,%8,%9,%10,%11}, {%12,%13,%14,%15}, %16, 1, 1, 1, 1;"
                 : A4(d, 0), A4(d, 4), A4(d, 8) : "r"(a[0]), "r"(a[1]), "r"(a[2]), "r"(a[3]), "l"(desc));
}
__device__ __forceinline__ void wg_qk(float* d, const uint32_t* a, uint64_t desc) {
    asm volatile("wgmma.mma_async.sync.aligned.m64n64k16.f32.bf16.bf16 {%0,%1,%2,%3,%4,%5,%6,%7,%8,%9,%10,%11,%12,%13,%14,%15,%16,%17,%18,%19,%20,%21,%22,%23,%24,%25,%26,%27,%28,%29,%30,%31}, {%32,%33,%34,%35}, %36, 0, 1, 1, 0;"
                 : A16(d, 0), A16(d, 16) : "r"(a[0]), "r"(a[1]), "r"(a[2]), "r"(a[3]), "l"(desc));
}
__device__ __forceinline__ void wg_ss32(float* d, uint64_t da, uint64_t db) {
    asm volatile("wgmma.mma_async.sync.aligned.m64n32k16.f32.bf16.bf16 {%0,%1,%2,%3,%4,%5,%6,%7,%8,%9,%10,%11,%12,%13,%14,%15}, %16, %17, 1, 1, 1, 0, 1;"
                 : A16(d, 0) : "l"(da), "l"(db));
}
__device__ __forceinline__ void wg_ss16(float* d, uint64_t da, uint64_t db) {
    asm volatile("wgmma.mma_async.sync.aligned.m64n16k16.f32.bf16.bf16 {%0,%1,%2,%3,%4,%5,%6,%7}, %8, %9, 1, 1, 1, 0, 1;"
                 : A4(d, 0), A4(d, 4) : "l"(da), "l"(db));
}
template<int N> __device__ __forceinline__ void fence_regs(float* r) {
    #pragma unroll
    for (int i = 0; i < N; i++) asm volatile("" : "+f"(r[i]) :: "memory");
}
__device__ __forceinline__ void mma_bf16(float* d, uint32_t a0, uint32_t a1, uint32_t a2, uint32_t a3, uint32_t b0, uint32_t b1) {
    asm volatile("mma.sync.aligned.m16n8k16.row.col.f32.bf16.bf16.f32 {%0,%1,%2,%3}, {%4,%5,%6,%7}, {%8,%9}, {%0,%1,%2,%3};"
                 : "+f"(d[0]), "+f"(d[1]), "+f"(d[2]), "+f"(d[3]) : "r"(a0), "r"(a1), "r"(a2), "r"(a3), "r"(b0), "r"(b1));
}
__device__ __forceinline__ void mma_f16(float* d, const uint32_t* a, uint32_t b0, uint32_t b1) {
    asm volatile("mma.sync.aligned.m16n8k16.row.col.f32.f16.f16.f32 {%0,%1,%2,%3}, {%4,%5,%6,%7}, {%8,%9}, {%0,%1,%2,%3};"
                 : "+f"(d[0]), "+f"(d[1]), "+f"(d[2]), "+f"(d[3]) : "r"(a[0]), "r"(a[1]), "r"(a[2]), "r"(a[3]), "r"(b0), "r"(b1));
}
__device__ __forceinline__ void ldsm4(uint32_t* r, uint32_t addr) {
    asm volatile("ldmatrix.sync.aligned.m8n8.x4.shared.b16 {%0,%1,%2,%3}, [%4];" : "=r"(r[0]), "=r"(r[1]), "=r"(r[2]), "=r"(r[3]) : "r"(addr) : "memory");
}
__device__ __forceinline__ void ldsm4t(uint32_t* r, uint32_t addr) {
    asm volatile("ldmatrix.sync.aligned.m8n8.x4.trans.shared.b16 {%0,%1,%2,%3}, [%4];" : "=r"(r[0]), "=r"(r[1]), "=r"(r[2]), "=r"(r[3]) : "r"(addr) : "memory");
}
__device__ __forceinline__ uint32_t lds32(uint32_t addr) { uint32_t v; asm volatile("ld.shared.u32 %0, [%1];" : "=r"(v) : "r"(addr) : "memory"); return v; }
__device__ __forceinline__ float ex2f(float x) { float r; asm("ex2.approx.ftz.f32 %0, %1;" : "=f"(r) : "f"(x)); return r; }
__device__ __forceinline__ uint32_t pack_bf16(float lo, float hi) { uint32_t r; asm("cvt.rn.bf16x2.f32 %0, %1, %2;" : "=r"(r) : "f"(hi), "f"(lo)); return r; }
__device__ __forceinline__ uint32_t pack_f16(float lo, float hi) { uint32_t r; asm("cvt.rn.f16x2.f32 %0, %1, %2;" : "=r"(r) : "f"(hi), "f"(lo)); return r; }
__device__ __forceinline__ float bf_lo(uint32_t v) { return __uint_as_float(v << 16); }
__device__ __forceinline__ float bf_hi(uint32_t v) { return __uint_as_float(v & 0xFFFF0000u); }
__device__ __forceinline__ float bf_round(float x) { return __bfloat162float(__float2bfloat16_rn(x)); }

__device__ __forceinline__ uint32_t exp_mufu(float x0, float x1) { return pack_bf16(ex2f(x0), ex2f(x1)); }
#define SW_MAGIC (256.0f + 127.0f - 0.598938f)
__device__ __forceinline__ uint32_t exp_sw(float x0, float x1, uint32_t cA, uint32_t cB) {
    float t0 = x0 + SW_MAGIC, t1 = x1 + SW_MAGIC;
    uint32_t L, mh, ec, r;
    asm("prmt.b32 %0, %1, %2, 0x6521;" : "=r"(L) : "r"(__float_as_uint(t0)), "r"(__float_as_uint(t1)));
    asm("lop3.b32 %0, %1, 0x007F007F, %2, 0xEA;" : "=r"(mh) : "r"(L), "r"(cA));
    asm("lop3.b32 %0, %1, 0x7F807F80, %2, 0xEA;" : "=r"(ec) : "r"(L), "r"(cB));
    asm("fma.rn.bf16x2 %0, %1, %2, %3;" : "=r"(r) : "r"(L), "r"(mh), "r"(ec));
    return r;
}
constexpr uint32_t MUFU_MASK = 0x4949;

struct cf { float x, y; };
__device__ __forceinline__ cf cmul(cf a, cf b) { cf r; r.x = a.x * b.x - a.y * b.y; r.y = a.x * b.y + a.y * b.x; return r; }
__device__ __forceinline__ cf cexp_p(float a2, float b, float p) {
    float e = ex2f(a2 * p);
    float ph = b * p;
    ph -= (ph + 12582912.0f) - 12582912.0f;
    float ang = ph * 6.283185307f;
    cf r; r.x = e * __cosf(ang); r.y = e * __sinf(ang);
    return r;
}
__device__ __forceinline__ uint32_t h2_cmul(uint32_t w, uint32_t wsw, uint32_t e) {
    __half2 hw = *(__half2*)&w, hs = *(__half2*)&wsw, he = *(__half2*)&e;
    __half2 r = __hfma2(hs, __high2half2(he), __hmul2(hw, __low2half2(he)));
    return *(uint32_t*)&r;
}

template<bool B> struct BoolC { static constexpr bool value = B; };
struct Params {
    const __nv_bfloat16 *u, *lar, *aim, *cre, *cim, *logdt, *dskip;
    __nv_bfloat16* out;
};

constexpr int B_X = 0, B_O = 8, B_KV = 16, B_WO = 24, B_U = 25, B_ST = 26, B_H = 27, NBAR = 30;

__device__ __forceinline__ void aux_role(const Params& P, uint8_t* sp, uint32_t sb, const CUtensorMap* tm_wo, float* s_misc,
                                         const uint32_t (&par)[4][2], float logdt, uint2 dsk, unsigned epoch) {
    const int tid = threadIdx.x & 127, c = tid >> 5, lane = tid & 31, g = lane >> 2, t = lane & 3;
    const int d0 = blockIdx.x * 4;
    const uint32_t rank = blockIdx.x & 1;
    const uint32_t bars = sb + SM_BAR;
    uint8_t* sB = sp + SM_B;
    {
        uint8_t* kb = sB + S_KC + c * 4096;
        const uint32_t kba = sb + SM_B + S_KC + c * 4096;
        const float dt = bf_round(expf(logdt));
        float m = 0.0f;
        #pragma unroll
        for (int i = 0; i < 4; i++) m = fmaxf(m, fmaxf(fabsf(bf_lo(par[i][1])), fabsf(bf_hi(par[i][1]))));
        #pragma unroll
        for (int o = 16; o; o >>= 1) m = fmaxf(m, __shfl_xor_sync(0xffffffffu, m, o));
        m *= 2.0f * dt;
        int ebits = (__float_as_uint(m) >> 23) & 0xFF;
        ebits = min(max(ebits, 2), 250);
        const float scale = __uint_as_float((uint32_t)(ebits + 1) << 23);
        const float iscale = __uint_as_float((uint32_t)(253 - ebits) << 23);
        uint4* stp = (uint4*)(kb + 3072 + lane * 32);
        const uint32_t fa = kba + 3072 + t * 32 + g * 4;
        float acc[2][3][4];
        #pragma unroll
        for (int i = 0; i < 24; i++) (&acc[0][0][0])[i] = 0.0f;
        #pragma unroll 1
        for (int mq = 0; mq < 4; mq++) {
            const uint32_t pa = mq == 0 ? par[0][0] : mq == 1 ? par[1][0] : mq == 2 ? par[2][0] : par[3][0];
            const uint32_t pc = mq == 0 ? par[0][1] : mq == 1 ? par[1][1] : mq == 2 ? par[2][1] : par[3][1];
            const float are = -bf_round(expf(bf_lo(pa))) * dt;
            const float aim = bf_hi(pa) * dt;
            const float a2 = are * 1.4426950408889634f, bb = aim * 0.15915494309189535f;
            cf cc;
            cc.x = 2.0f * (bf_lo(pc) * dt) * iscale;
            cc.y = 2.0f * (bf_hi(pc) * dt) * iscale;
            uint32_t af[4][2][4];
            {
                const cf E8 = cexp_p(a2, bb, 8.0f);
                uint32_t w[8];
                cf cur = E8;
                w[0] = pack_f16(1.0f, 0.0f);
                w[1] = pack_f16(cur.x, cur.y);
                #pragma unroll
                for (int i = 2; i < 8; i++) { cur = cmul(cur, E8); w[i] = pack_f16(cur.x, cur.y); }
                stp[0] = make_uint4(w[0], w[1], w[2], w[3]);
                stp[1] = make_uint4(w[4], w[5], w[6], w[7]);
                const cf E64 = cexp_p(a2, bb, 64.0f);
                const cf E128 = cmul(E64, E64), E192 = cmul(E128, E64);
                const uint32_t e1 = pack_f16(E64.x, E64.y), e2 = pack_f16(E128.x, E128.y), e3 = pack_f16(E192.x, E192.y);
                __syncwarp();
                #pragma unroll
                for (int s = 0; s < 4; s++) {
                    #pragma unroll
                    for (int hh = 0; hh < 2; hh++) {
                        const uint32_t w0 = lds32(fa + s * 256 + hh * 128);
                        const uint32_t wsw = __byte_perm(w0, 0, 0x1032) ^ 0x00008000u;
                        const int src = 8 * s + t + 4 * hh;
                        const uint32_t f1 = __shfl_sync(0xffffffffu, e1, src), f2 = __shfl_sync(0xffffffffu, e2, src), f3 = __shfl_sync(0xffffffffu, e3, src);
                        af[s][0][2 * hh] = w0;
                        af[s][0][2 * hh + 1] = h2_cmul(w0, wsw, f1);
                        af[s][1][2 * hh] = h2_cmul(w0, wsw, f2);
                        af[s][1][2 * hh + 1] = h2_cmul(w0, wsw, f3);
                    }
                }
                __syncwarp();
            }
            const cf E256 = cexp_p(a2, bb, 256.0f);
            const cf E1 = cexp_p(a2, bb, 1.0f);
            const cf E2 = cmul(E1, E1), E4 = cmul(E2, E2);
            cf X512;
            #pragma unroll
            for (int nt = 0; nt < 3; nt++) {
                uint32_t xv[8];
                if (nt == 0) {
                    cf cur = cc;
                    xv[0] = pack_f16(cur.x, -cur.y);
                    #pragma unroll
                    for (int i = 1; i < 8; i++) { cur = cmul(cur, E1); xv[i] = pack_f16(cur.x, -cur.y); }
                } else if (nt == 1) {
                    cf cur = cmul(cc, E256);
                    X512 = cmul(cur, E256);
                    xv[0] = pack_f16(cur.x, -cur.y);
                    #pragma unroll
                    for (int i = 1; i < 4; i++) { cur = cmul(cur, E2); xv[i] = pack_f16(cur.x, -cur.y); }
                    cur = cmul(X512, E4);
                    xv[4] = pack_f16(X512.x, -X512.y); xv[5] = pack_f16(cur.x, -cur.y);
                    X512 = cmul(X512, E256);
                    cur = cmul(X512, E4);
                    xv[6] = pack_f16(X512.x, -X512.y); xv[7] = pack_f16(cur.x, -cur.y);
                } else {
                    cf cur = X512;
                    #pragma unroll
                    for (int i = 0; i < 5; i++) { cur = cmul(cur, E256); xv[i] = pack_f16(cur.x, -cur.y); }
                    xv[5] = 0; xv[6] = 0; xv[7] = 0;
                }
                stp[0] = make_uint4(xv[0], xv[1], xv[2], xv[3]);
                stp[1] = make_uint4(xv[4], xv[5], xv[6], xv[7]);
                __syncwarp();
                #pragma unroll
                for (int s = 0; s < 4; s++) {
                    const uint32_t b0 = lds32(fa + s * 256), b1 = lds32(fa + s * 256 + 128);
                    mma_f16(acc[0][nt], af[s][0], b0, b1);
                    mma_f16(acc[1][nt], af[s][1], b0, b1);
                }
                __syncwarp();
            }
        }
        float* kc = (float*)kb;
        #pragma unroll
        for (int mt = 0; mt < 2; mt++)
            #pragma unroll
            for (int nt = 0; nt < 3; nt++)
                #pragma unroll
                for (int hh = 0; hh < 2; hh++)
                    *(float2*)(kc + (mt * 16 + hh * 8 + g) * 24 + nt * 8 + 2 * t) = make_float2(acc[mt][nt][2 * hh] * scale, acc[mt][nt][2 * hh + 1] * scale);
    }
    bar_arrive(9, 640);
    PROF2(1);
    bar_sync(8, 640);
    if (tid < 32) {
        if (lane == 0) pair_sync(bars + 8 * (B_H + 1), rank ^ 1);
        wait_flag(&g_flag_kv[lane], epoch);
        wait_flag(&g_flag_kv[lane + 32], epoch);
        __syncwarp();
        PROF2(2);
        if (lane < 8) {
            fence_async_all();
            const uint32_t bar = bars + 8 * (B_KV + lane);
            if (rank == 0) bulk_g2s_mc(sb + SM_K + lane * 8192, g_kimg + lane * 8192, 8192, bar);
            else {
                bulk_g2s_mc(sb + SM_V + lane * 4096, g_vimg + lane * 4096, 4096, bar);
                bulk_g2s_mc(sb + SM_V + 33024 + (7 - lane) * 4096, g_vimg + 33024 + (7 - lane) * 4096, 4096, bar);
            }
        }
        float km = 0.0f, vm = 0.0f;
        #pragma unroll
        for (int i = 0; i < 4; i++) {
            km = fmaxf(km, __ldcg(&g_stat[0][lane * 4 + i]));
            vm = fmaxf(vm, __ldcg(&g_stat[1][lane * 4 + i]));
        }
        #pragma unroll
        for (int o = 16; o; o >>= 1) { km = fmaxf(km, __shfl_xor_sync(0xffffffffu, km, o)); vm = fmaxf(vm, __shfl_xor_sync(0xffffffffu, vm, o)); }
        *(uint2*)(sp + SM_V + 32768 + lane * 8) = make_uint2(0x3F803F80u, 0x3F803F80u);
        fence_async_smem();
        __syncwarp();
        if (lane == 0) { s_misc[16] = km; s_misc[17] = vm; mbar_arrive(bars + 8 * B_ST); }
    }
    PROF2(3);
    bar_sync(10, 640);
    {
        uint32_t dd[4] = {__byte_perm(dsk.x, 0, 0x1010), __byte_perm(dsk.x, 0, 0x3232), __byte_perm(dsk.y, 0, 0x1010), __byte_perm(dsk.y, 0, 0x3232)};
        #pragma unroll 2
        for (int i = 0; i < 8; i++) {
            const int l = 2 * (tid + 128 * i);
            uint32_t r[4];
            #pragma unroll
            for (int cc = 0; cc < 4; cc++) {
                const uint32_t y2 = *(const uint32_t*)(sB + S_Y + cc * 4096 + l * 2);
                const uint32_t u2 = *(const uint32_t*)(sB + S_U + cc * ULEN * 2 + (PADU + l) * 2);
                __nv_bfloat162 pr = __hmul2(*(const __nv_bfloat162*)&u2, *(const __nv_bfloat162*)&dd[cc]);
                __nv_bfloat162 sm = __hadd2(*(const __nv_bfloat162*)&y2, pr);
                r[cc] = *(uint32_t*)&sm;
            }
            *(uint2*)(P.out + (size_t)l * 1024 + 512 + d0) = make_uint2(__byte_perm(r[0], r[1], 0x5410), __byte_perm(r[2], r[3], 0x5410));
            *(uint2*)(P.out + (size_t)(l + 1) * 1024 + 512 + d0) = make_uint2(__byte_perm(r[0], r[1], 0x7632), __byte_perm(r[2], r[3], 0x7632));
        }
    }
    bar_sync(2, 128);
    if (tid == 0) {
        fence_async_smem();
        mbar_expect_tx(bars + 8 * B_WO, 65536);
        for (int b = 0; b < 2; b++) tma_2d(sb + SM_B + b * 32768, tm_wo, (blockIdx.x & 7) * 64, b * 256, bars + 8 * B_WO);
    }
    PROF2(4);
}

__global__ void __cluster_dims__(2, 1, 1) __launch_bounds__(NTHR, 1)
fused_kernel(const __grid_constant__ CUtensorMap tm_x, const __grid_constant__ CUtensorMap tm_wq,
             const __grid_constant__ CUtensorMap tm_wo, const __grid_constant__ CUtensorMap tm_wk,
             const __grid_constant__ CUtensorMap tm_wv, const __grid_constant__ CUtensorMap tm_u, const Params P) {
    extern __shared__ uint8_t smem_raw[];
    const uint32_t sb = (smem_u32(smem_raw) + 1023u) & ~1023u;
    uint8_t* sp = smem_raw + (sb - smem_u32(smem_raw));

    const int tid = threadIdx.x, warp = tid >> 5, lane = tid & 31, wg = tid >> 7, wiw = warp & 3;
    const int g = lane >> 2, t = lane & 3;
    const int qb = blockIdx.x >> 3, hg = blockIdx.x & 7;
    const uint32_t rank = blockIdx.x & 1;
    const int rowhalf = wg & 1, nh = wg >> 1;
    const bool kv_cta = hg < 4;
    const int kv_sel = hg >> 1;
    const bool kv_wg = kv_cta && (wg == (hg & 1));

    const uint32_t bars = sb + SM_BAR;
    float* s_misc = (float*)(sp + SM_BAR + 256);
    const CUtensorMap* tm_kv = kv_sel ? &tm_wv : &tm_wk;

    PROF(0);
    uint32_t par[4][2] = {};
    float logdt = 0.0f;
    uint2 dsk = make_uint2(0, 0);
    if (wg == 4) {
        const int d = blockIdx.x * 4 + wiw;
        const unsigned short* lar = (const unsigned short*)P.lar + d * 128 + lane;
        const unsigned short* aim = (const unsigned short*)P.aim + d * 128 + lane;
        const unsigned short* cre = (const unsigned short*)P.cre + d * 128 + lane;
        const unsigned short* cim = (const unsigned short*)P.cim + d * 128 + lane;
        #pragma unroll
        for (int i = 0; i < 4; i++) {
            par[i][0] = (uint32_t)__ldg(lar + 32 * i) | ((uint32_t)__ldg(aim + 32 * i) << 16);
            par[i][1] = (uint32_t)__ldg(cre + 32 * i) | ((uint32_t)__ldg(cim + 32 * i) << 16);
        }
        logdt = __bfloat162float(P.logdt[d]);
        dsk = __ldg((const uint2*)(P.dskip + blockIdx.x * 4));
    } else if (tid >= 32 && tid < 32 + TABN * 2 / 128) {
        asm volatile("prefetch.global.L2 [%0];" :: "l"((const char*)g_tabmap.v + (tid - 32) * 128));
    }
    auto issue_own = [&](int ch) {
        const uint32_t st = sb + SM_A + (ch % 5) * STG, bar = bars + 8 * (B_X + ch);
        tma_2d(st + 16384, &tm_wq, hg * 64, ch * 64, bar);
        if (kv_cta) { tma_2d(st + 24576, tm_kv, 0, ch * 64, bar); tma_2d(st + 25600, tm_kv, 8, ch * 64, bar); }
    };
    auto issue_x = [&](int ch) {
        tma_2d_mc(sb + SM_A + (ch % 5) * STG + rank * 8192, &tm_x, ch * 64, qb * 128 + rank * 64, bars + 8 * (B_X + ch));
    };
    if (tid == 0) {
        for (int i = 0; i < NBAR; i++) mbar_init(bars + 8 * i, i >= B_H ? 2 : 1);
        asm volatile("fence.mbarrier_init.release.cluster;" ::: "memory");
        fence_async_smem();
        for (int ch = 0; ch < 8; ch++) {
            mbar_expect_tx(bars + 8 * (B_X + ch), 24576 + (kv_cta ? 2048 : 0));
            mbar_expect_tx(bars + 8 * (B_KV + ch), 16384);
            mbar_expect_tx(bars + 8 * (B_O + ch), 16384);
        }
        mbar_expect_tx(bars + 8 * B_U, 32768);
        for (int ch = 0; ch < 5; ch++) issue_own(ch);
    }
    const unsigned epoch = *(volatile unsigned*)&g_epoch + 1u;
    asm volatile("barrier.cluster.arrive.release.aligned;" ::: "memory");
    asm volatile("barrier.cluster.wait.acquire.aligned;" ::: "memory");

    if (wg == 4) {
        aux_role(P, sp, sb, &tm_wo, s_misc, par, logdt, dsk, epoch);
    } else {
        uint8_t* sB = sp + SM_B;
        const uint32_t sBa = sb + SM_B;
        if (tid == 0) {
            for (int b = 0; b < 4; b++) tma_2d_mc(sBa + S_W3 + (rank * 4 + b) * 4096, &tm_u, (blockIdx.x >> 1) * 8, (rank * 4 + b) * 256, bars + 8 * B_U);
            for (int ch = 0; ch < 5; ch++) issue_x(ch);
        }
        if (tid < 4 * (PADU / 8)) *(uint4*)(sB + S_U + (tid / (PADU / 8)) * ULEN * 2 + (tid % (PADU / 8)) * 16) = make_uint4(0, 0, 0, 0);
        mbar_wait(bars + 8 * B_U, 0);
        #pragma unroll
        for (int i = 0; i < 2; i++) {
            const int l = 2 * (tid + 512 * i);
            const uint2 r0 = *(const uint2*)(sB + S_W3 + l * 16 + rank * 8), r1 = *(const uint2*)(sB + S_W3 + l * 16 + 16 + rank * 8);
            uint32_t* dst = (uint32_t*)(sB + S_U + (PADU + l) * 2);
            dst[0] = __byte_perm(r0.x, r1.x, 0x5410);
            dst[ULEN / 2] = __byte_perm(r0.x, r1.x, 0x7632);
            dst[ULEN] = __byte_perm(r0.y, r1.y, 0x5410);
            dst[3 * ULEN / 2] = __byte_perm(r0.y, r1.y, 0x7632);
        }
        bar_sync(1, 512);
        #pragma unroll 1
        for (int task = tid; task < 4 * 194; task += 512) {
            const int c = task / 194, i = task % 194;
            const uint4* src = (const uint4*)(sB + S_U + c * ULEN * 2 + (PADU + 8 * i - WPAD - 8) * 2);
            const uint4 v0 = src[0], v1 = src[1], v2 = src[2];
            float x[24];
            const uint32_t vv[12] = {v0.x, v0.y, v0.z, v0.w, v1.x, v1.y, v1.z, v1.w, v2.x, v2.y, v2.z, v2.w};
            #pragma unroll
            for (int k = 0; k < 12; k++) { x[2 * k] = bf_lo(vv[k]); x[2 * k + 1] = bf_hi(vv[k]); }
            float w3[12], w5[8];
            #pragma unroll
            for (int e = 0; e < 12; e++) w3[e] = (x[3 + e] + x[4 + e]) + x[5 + e];
            #pragma unroll
            for (int e = 0; e < 8; e++) w5[e] = w3[4 + e] + (x[6 + e] + x[10 + e]);
            *(uint4*)(sB + S_W3 + c * W2LEN * 2 + i * 16) = make_uint4(pack_bf16(w3[0], w3[1]), pack_bf16(w3[2], w3[3]), pack_bf16(w3[4], w3[5]), pack_bf16(w3[6], w3[7]));
            *(uint4*)(sB + S_W5 + c * W2LEN * 2 + i * 16) = make_uint4(pack_bf16(w5[0], w5[1]), pack_bf16(w5[2], w5[3]), pack_bf16(w5[4], w5[5]), pack_bf16(w5[6], w5[7]));
            if (i < 130) {
                float w7[8], w9[8];
                #pragma unroll
                for (int e = 0; e < 8; e++) { w7[e] = w5[e] + (x[5 + e] + x[11 + e]); w9[e] = w7[e] + (x[4 + e] + x[12 + e]); }
                *(uint4*)(sB + S_W7 + c * W3LEN * 2 + i * 16) = make_uint4(pack_bf16(w7[0], w7[1]), pack_bf16(w7[2], w7[3]), pack_bf16(w7[4], w7[5]), pack_bf16(w7[6], w7[7]));
                *(uint4*)(sB + S_W9 + c * W3LEN * 2 + i * 16) = make_uint4(pack_bf16(w9[0], w9[1]), pack_bf16(w9[2], w9[3]), pack_bf16(w9[4], w9[5]), pack_bf16(w9[6], w9[7]));
            }
        }
        PROF(1);
        uint32_t q[2][4];
        {
            float acc[16], akv[8];
            #pragma unroll
            for (int i = 0; i < 16; i++) acc[i] = 0.0f;
            #pragma unroll
            for (int i = 0; i < 8; i++) akv[i] = 0.0f;
            fence_regs<16>(acc);
            fence_regs<8>(akv);
            const uint64_t dA = make_desc(sb + SM_A + rowhalf * 8192, 16, 1024, 1);
            const uint64_t dB = make_desc(sb + SM_A + 16384 + nh * 64, 16, 1024, 1);
            const uint64_t dC = make_desc(sb + SM_A + 24576, 128, 1024, 0);
            auto proj_loop = [&](auto KV) {
                #pragma unroll 1
                for (int ch = 0; ch < 8; ch++) {
                    const uint32_t so = (ch % 5) * (STG / 16);
                    mbar_wait(bars + 8 * (B_X + ch), 0);
                    if (ch == 0) PROF(2);
                    wg_fence();
                    if (decltype(KV)::value) {
                        #pragma unroll
                        for (int ks = 0; ks < 4; ks++) wg_ss16(akv, dA + so + ks * 2, dC + so + ks * 16);
                    }
                    #pragma unroll
                    for (int ks = 0; ks < 4; ks++) wg_ss32(acc, dA + so + ks * 2, dB + so + ks * 128);
                    wg_commit();
                    if (ch == 2) {
                        wg_wait<0>();
                        bar_sync(1, 512);
                        if (tid == 0) {
                            for (int c2 = 5; c2 < 8; c2++) issue_own(c2);
                            pair_sync(bars + 8 * B_H, rank ^ 1);
                            for (int c2 = 5; c2 < 8; c2++) issue_x(c2);
                        }
                    }
                }
                wg_wait<0>();
            };
            if (kv_wg) proj_loop(BoolC<true>()); else proj_loop(BoolC<false>());
            fence_regs<16>(acc);
            fence_regs<8>(akv);
            if (kv_wg) {
                const int key = qb * 128 + rowhalf * 64 + wiw * 16 + g;
                uint32_t pk[4];
                #pragma unroll
                for (int i = 0; i < 4; i++) pk[i] = pack_bf16(akv[2 * i], akv[2 * i + 1]);
                float st;
                if (kv_sel == 0) {
                    uint8_t* b = g_kimg + (key >> 3) * 256 + (key & 7) * 16 + 4 * t;
                    *(uint32_t*)(b) = pk[0]; *(uint32_t*)(b + 256) = pk[1]; *(uint32_t*)(b + 128) = pk[2]; *(uint32_t*)(b + 384) = pk[3];
                    float n0 = bf_lo(pk[0]) * bf_lo(pk[0]) + bf_hi(pk[0]) * bf_hi(pk[0]) + bf_lo(pk[2]) * bf_lo(pk[2]) + bf_hi(pk[2]) * bf_hi(pk[2]);
                    float n1 = bf_lo(pk[1]) * bf_lo(pk[1]) + bf_hi(pk[1]) * bf_hi(pk[1]) + bf_lo(pk[3]) * bf_lo(pk[3]) + bf_hi(pk[3]) * bf_hi(pk[3]);
                    n0 += __shfl_xor_sync(0xffffffffu, n0, 1); n0 += __shfl_xor_sync(0xffffffffu, n0, 2);
                    n1 += __shfl_xor_sync(0xffffffffu, n1, 1); n1 += __shfl_xor_sync(0xffffffffu, n1, 2);
                    st = (n0 != n0 || n1 != n1) ? __int_as_float(0x7f800000) : fmaxf(n0, n1);
                } else {
                    const int s = key >> 4;
                    uint8_t* lo = g_vimg + s * 256 + g * 16 + 4 * t;
                    uint8_t* hi = g_vimg + 33024 + (127 - s) * 256 + g * 16 + 4 * t;
                    *(uint32_t*)(lo) = pk[0]; *(uint32_t*)(lo + 128) = pk[1]; *(uint32_t*)(hi) = pk[2]; *(uint32_t*)(hi + 128) = pk[3];
                    st = 0.0f;
                    #pragma unroll
                    for (int i = 0; i < 4; i++) {
                        float a = fabsf(bf_lo(pk[i])), b = fabsf(bf_hi(pk[i]));
                        st = (a != a || b != b) ? __int_as_float(0x7f800000) : fmaxf(st, fmaxf(a, b));
                    }
                }
                #pragma unroll
                for (int o = 16; o; o >>= 1) st = fmaxf(st, __shfl_xor_sync(0xffffffffu, st, o));
                if (lane == 0) g_stat[kv_sel][(qb * 2 + rowhalf) * 4 + wiw] = st;
                __threadfence();
                bar_sync(3, 128);
                if ((tid & 127) == 0) st_release(&g_flag_kv[(qb * 2 + rowhalf) * 2 + kv_sel], epoch);
            }
            const float QS = 0.25f * 1.4426950408889634f;
            float qm = 0.0f;
            #pragma unroll
            for (int i = 0; i < 2; i++) {
                #pragma unroll
                for (int j = 0; j < 4; j++) q[i][j] = pack_bf16(acc[8 * i + 2 * j] * QS, acc[8 * i + 2 * j + 1] * QS);
                float n0 = bf_lo(q[i][0]) * bf_lo(q[i][0]) + bf_hi(q[i][0]) * bf_hi(q[i][0]) + bf_lo(q[i][2]) * bf_lo(q[i][2]) + bf_hi(q[i][2]) * bf_hi(q[i][2]);
                float n1 = bf_lo(q[i][1]) * bf_lo(q[i][1]) + bf_hi(q[i][1]) * bf_hi(q[i][1]) + bf_lo(q[i][3]) * bf_lo(q[i][3]) + bf_hi(q[i][3]) * bf_hi(q[i][3]);
                n0 += __shfl_xor_sync(0xffffffffu, n0, 1); n0 += __shfl_xor_sync(0xffffffffu, n0, 2);
                n1 += __shfl_xor_sync(0xffffffffu, n1, 1); n1 += __shfl_xor_sync(0xffffffffu, n1, 2);
                qm = (n0 != n0 || n1 != n1) ? __int_as_float(0x7f800000) : fmaxf(qm, fmaxf(n0, n1));
            }
            #pragma unroll
            for (int o = 16; o; o >>= 1) qm = fmaxf(qm, __shfl_xor_sync(0xffffffffu, qm, o));
            if (lane == 0) s_misc[warp] = qm;
        }
        bar_arrive(8, 640);
        PROF(3);
        {
            const int c = tid >> 7;
            const float* kc = (const float*)(sB + S_KC + c * 4096);
            uint32_t* tab = (uint32_t*)(sB + S_TAB + c * TABN * 2);
            const uint32_t* map = (const uint32_t*)g_tabmap.v;
            uint32_t mp[9];
            #pragma unroll
            for (int i = 0; i < 9; i++) { const int w = (tid & 127) + 128 * i; mp[i] = (w < TABN / 2) ? __ldg(map + w) : 0u; }
            bar_sync(9, 640);
            PROF(4);
            #pragma unroll
            for (int i = 0; i < 9; i++) { const int w = (tid & 127) + 128 * i; if (w < TABN / 2) tab[w] = pack_bf16(kc[mp[i] & 0xFFFF], kc[mp[i] >> 16]); }
        }
        bar_sync(1, 512);
        PROF(6);
        {
            const int c = warp >> 2, grp = (warp + c) & 3;
            float acc[4][4];
            #pragma unroll
            for (int i = 0; i < 16; i++) (&acc[0][0])[i] = 0.0f;
            const uint32_t tabc = sBa + S_TAB + c * TABN * 2;
            const int e2 = (g - 2 * t) * 2;
            const uint32_t tD = tabc + ((g & 1) ? (TD1 + CD + 1) : (TD0 + CD)) * 2 - e2;
            const uint32_t tE = tabc + ((g & 1) ? (TE1 + CE + 1) : (TE0 + CE)) * 2 - e2;
            const uint32_t t2 = tabc + (T2B + ((g & 1) ? (T2C + C2 + 1) : C2)) * 2 - e2;
            const uint32_t t3 = tabc + (T3B + ((g & 1) ? (T3C + C3 + 1) : C3)) * 2 - e2;
            const int mi = lane >> 3, r8 = lane & 7;
            const uint32_t ub = sBa + S_U + c * ULEN * 2 + (PADU + 16 * (8 * (mi >> 1) + r8) + 8 * (mi & 1)) * 2 + (4 * grp - 4) * 256;
            #pragma unroll 1
            for (int rho = 0; rho < 8; rho++) {
                uint32_t R[5][3];
                #pragma unroll
                for (int qq = 0; qq < 5; qq++) {
                    if (qq < 4 || rho < 2) {
                        const uint32_t a = tD - 32 * (rho + 8 * qq);
                        R[qq][0] = lds32(a + 16); R[qq][1] = lds32(a); R[qq][2] = lds32(a - 16);
                    } else { R[qq][0] = 0; R[qq][1] = 0; R[qq][2] = 0; }
                }
                #pragma unroll
                for (int jp = 0; jp < 4; jp++) {
                    if (grp == 0 && (jp == 0 || (jp == 1 && rho > 0))) continue;
                    if (jp == 0 && rho >= 2) {
                        uint32_t b[4];
                        ldsm4(b, ub + jp * 512 - rho * 32);
                        mma_bf16(acc[0], R[3][1], R[3][2], R[3][0], R[3][1], b[2], b[3]);
                        continue;
                    }
                    uint32_t b[4];
                    ldsm4(b, ub + jp * 512 - rho * 32);
                    #pragma unroll
                    for (int hh = 0; hh < 2; hh++) {
                        #pragma unroll
                        for (int qq = 0; qq < 5; qq++) {
                            const int jr = 2 * jp + hh + qq - 4;
                            if (jr >= 0 && jr < 4) {
                                if (qq < 4 || rho < 2) mma_bf16(acc[jr], R[qq][1], R[qq][2], R[qq][0], R[qq][1], b[2 * hh], b[2 * hh + 1]);
                            }
                        }
                    }
                }
            }
            if (grp >= 2) {
                uint32_t R[5];
                #pragma unroll
                for (int i = 0; i < 5; i++) R[i] = lds32(tE - 16 * (127 + i));
                #pragma unroll
                for (int kk = 0; kk < 2; kk++) {
                    #pragma unroll
                    for (int jp = 0; jp < 2; jp++) {
                        uint32_t b[4];
                        ldsm4(b, ub + (4 + 2 * jp) * 256 - (64 + kk) * 32);
                        mma_bf16(acc[2 * jp], R[2 * kk + 1], R[2 * kk + 2], R[2 * kk], R[2 * kk + 1], b[0], b[1]);
                        mma_bf16(acc[2 * jp + 1], R[2 * kk + 1], R[2 * kk + 2], R[2 * kk], R[2 * kk + 1], b[2], b[3]);
                    }
                }
            }
            const uint32_t soff = (WPAD + 16 * (8 * (mi >> 1) + r8) + 8 * (mi & 1)) * 2 + grp * 1024;
            if (grp >= 1) {
                #pragma unroll 1
                for (int s = 0; s < 4; s++) {
                    const uint32_t sig = sBa + ((s & 1) ? S_W3 : S_W5) + c * W2LEN * 2 + soff - ((s == 0) ? 32 : (s == 1) ? 0 : 16);
                    uint32_t R[7];
                    #pragma unroll
                    for (int i = 0; i < 7; i++) R[i] = lds32(t2 + s * (T2S * 2) - 16 * (3 + i));
                    #pragma unroll
                    for (int bb = 1; bb <= 4; bb++) {
                        if (2 * grp - bb < 0) continue;
                        uint32_t a[4];
                        ldsm4t(a, sig - bb * 512);
                        #pragma unroll
                        for (int jj = 0; jj < 4; jj++) {
                            const int h = jj + 2 * bb;
                            if (h >= 4 && h <= 9) mma_bf16(acc[jj], a[0], a[1], a[2], a[3], R[h - 3], R[h - 4]);
                        }
                    }
                }
            }
            if (grp >= 2) {
                #pragma unroll 1
                for (int s = 0; s < 2; s++) {
                    const uint32_t sig = sBa + (s ? S_W7 : S_W9) + c * W3LEN * 2 + soff - (s ? 16 : 32);
                    uint32_t R[9];
                    #pragma unroll
                    for (int i = 0; i < 9; i++) R[i] = lds32(t3 + s * (T3S * 2) - 16 * (7 + i));
                    #pragma unroll
                    for (int bb = 3; bb <= 6; bb++) {
                        if (2 * grp - bb < 0) continue;
                        uint32_t a[4];
                        ldsm4t(a, sig - bb * 512);
                        #pragma unroll
                        for (int jj = 0; jj < 4; jj++) {
                            const int h = jj + 2 * bb;
                            if (h >= 8 && h <= 15) mma_bf16(acc[jj], a[0], a[1], a[2], a[3], R[h - 7], R[h - 8]);
                        }
                    }
                }
            }
            __nv_bfloat16* ys = (__nv_bfloat16*)(sB + S_Y + c * 4096);
            #pragma unroll
            for (int jj = 0; jj < 4; jj++) {
                const int A = 8 * (4 * grp + jj) + 2 * t;
                ys[16 * A + g] = __float2bfloat16_rn(acc[jj][0]);
                ys[16 * A + 16 + g] = __float2bfloat16_rn(acc[jj][1]);
                ys[16 * A + g + 8] = __float2bfloat16_rn(acc[jj][2]);
                ys[16 * A + 16 + g + 8] = __float2bfloat16_rn(acc[jj][3]);
            }
        }
        bar_arrive(10, 640);
        PROF(7);
        {
            mbar_wait(bars + 8 * B_ST, 0);
            PROF(9);
            float qm = 0.0f;
            #pragma unroll
            for (int i = 0; i < 16; i++) qm = fmaxf(qm, s_misc[i]);
            const float vm = s_misc[17];
            const bool fast = (qm * s_misc[16] <= 60.0f * 60.0f) && (vm <= 1.0e12f) && (vm >= 1.0e-12f || vm == 0.0f);
            const uint64_t dVstep = 16ull - (16ull << 32);
            uint8_t* ob = g_oimg + qb * 131072 + hg * 16384 + nh * 8192 + (rowhalf * 8 + wiw * 2) * 128 + g * 16 + 4 * t;
            uint32_t cA = 0xBF00BF00u, cB = 0x00030003u;
            asm volatile("" : "+r"(cA), "+r"(cB));
            #pragma unroll 1
            for (int tile = 0; tile < 2; tile++) {
                uint64_t dK = make_desc(sb + SM_K, 128, 256, 0);
                uint64_t dV = make_desc(sb + SM_V, 128, 32768, 0);
                float o[12], s[32];
                uint32_t p[16], qq[4];
                #pragma unroll
                for (int i = 0; i < 4; i++) qq[i] = tile ? q[1][i] : q[0][i];
                #pragma unroll
                for (int i = 0; i < 12; i++) o[i] = 0.0f;
                #pragma unroll
                for (int i = 0; i < 32; i++) s[i] = 0.0f;
                fence_regs<12>(o);
                fence_regs<32>(s);
                if (fast) {
                    #pragma unroll 1
                    for (int c = 0; c < SEQ / 256; c++) {
                        mbar_wait(bars + 8 * (B_KV + c), 0);
                        wg_fence();
                        wg_qk(s, qq, dK);
                        wg_commit();
                        #pragma unroll
                        for (int u = 0; u < 4; u++) {
                            wg_wait<0>();
                            fence_regs<32>(s);
                            #pragma unroll
                            for (int i = 0; i < 16; i++) {
                                if ((MUFU_MASK >> i) & 1) p[i] = exp_mufu(s[2 * i], s[2 * i + 1]);
                                else p[i] = exp_sw(s[2 * i], s[2 * i + 1], cA, cB);
                            }
                            wg_fence();
                            if (u + 1 < 4) wg_qk(s, qq, dK + (u + 1) * 128);
                            #pragma unroll
                            for (int kk = 0; kk < 4; kk++) wg_pv(o, p + 4 * kk, dV + (u * 4 + kk) * dVstep);
                            wg_commit();
                        }
                        dK += 512;
                        dV += 16 * dVstep;
                    }
                    wg_wait<0>();
                } else {
                    float mx0 = -INFINITY, mx1 = -INFINITY;
                    #pragma unroll 1
                    for (int c = 0; c < SEQ / 64; c++) {
                        mbar_wait(bars + 8 * (B_KV + (c >> 2)), 0);
                        wg_fence();
                        wg_qk(s, qq, dK);
                        wg_commit();
                        wg_wait<0>();
                        fence_regs<32>(s);
                        fence_regs<12>(o);
                        float m0 = mx0, m1 = mx1;
                        #pragma unroll
                        for (int j = 0; j < 8; j++) {
                            m0 = fmaxf(m0, fmaxf(s[4 * j], s[4 * j + 1]));
                            m1 = fmaxf(m1, fmaxf(s[4 * j + 2], s[4 * j + 3]));
                        }
                        m0 = fmaxf(m0, __shfl_xor_sync(0xffffffffu, m0, 1)); m0 = fmaxf(m0, __shfl_xor_sync(0xffffffffu, m0, 2));
                        m1 = fmaxf(m1, __shfl_xor_sync(0xffffffffu, m1, 1)); m1 = fmaxf(m1, __shfl_xor_sync(0xffffffffu, m1, 2));
                        const float c0 = ex2f(mx0 - m0), c1 = ex2f(mx1 - m1);
                        mx0 = m0; mx1 = m1;
                        #pragma unroll
                        for (int j = 0; j < 3; j++) { o[4 * j] *= c0; o[4 * j + 1] *= c0; o[4 * j + 2] *= c1; o[4 * j + 3] *= c1; }
                        #pragma unroll
                        for (int j = 0; j < 8; j++) {
                            p[2 * j] = exp_mufu(s[4 * j] - m0, s[4 * j + 1] - m0);
                            p[2 * j + 1] = exp_mufu(s[4 * j + 2] - m1, s[4 * j + 3] - m1);
                        }
                        wg_fence();
                        #pragma unroll
                        for (int kk = 0; kk < 4; kk++) wg_pv(o, p + 4 * kk, dV + kk * dVstep);
                        wg_commit();
                        wg_wait<0>();
                        dK += 128;
                        dV += 4 * dVstep;
                    }
                }
                fence_regs<12>(o);
                const float i0 = 1.0f / o[4], i1 = 1.0f / o[6];
                uint8_t* b = ob + tile * 4096;
                *(uint32_t*)(b) = pack_bf16(o[0] * i0, o[1] * i0);
                *(uint32_t*)(b + 128) = pack_bf16(o[2] * i1, o[3] * i1);
                *(uint32_t*)(b + 2048) = pack_bf16(o[8] * i0, o[9] * i0);
                *(uint32_t*)(b + 2048 + 128) = pack_bf16(o[10] * i1, o[11] * i1);
            }
            __threadfence();
        }
        PROF(10);
        bar_sync(1, 512);
        PROF(11);
        if (warp == 0) {
            if (lane == 0) {
                st_release(&g_flag_o[blockIdx.x], epoch);
                pair_sync(bars + 8 * (B_H + 2), rank ^ 1);
            }
            __syncwarp();
            if (lane < 4) {
                const int src = 2 * lane + rank;
                wait_flag(&g_flag_o[qb * 8 + src], epoch);
                fence_async_all();
                bulk_g2s_mc(sb + SM_A + src * 16384, g_oimg + qb * 131072 + src * 16384, 16384, bars + 8 * (B_O + src));
            }
            __syncwarp();
        }

        {
            float acc[16];
            #pragma unroll
            for (int i = 0; i < 16; i++) acc[i] = 0.0f;
            fence_regs<16>(acc);
            const uint64_t dA = make_desc(sb + SM_A + rowhalf * 1024, 2048, 128, 0);
            const uint64_t dB = make_desc(sb + SM_B + nh * 64, 16, 1024, 1);
            mbar_wait(bars + 8 * B_WO, 0);
            #pragma unroll 1
            for (int i = 0; i < 8; i++) {
                const int src = (hg + i) & 7;
                mbar_wait(bars + 8 * (B_O + src), 0);
                wg_fence();
                #pragma unroll
                for (int kk = 0; kk < 4; kk++) wg_ss32(acc, dA + src * 1024 + kk * 256, dB + (src * 4 + kk) * 128);
                wg_commit();
            }
            wg_wait<0>();
            fence_regs<16>(acc);
            PROF(12);
            const int row = qb * 128 + rowhalf * 64 + wiw * 16 + g;
            uint32_t* o32 = (uint32_t*)(P.out + (size_t)row * 1024 + hg * 64 + nh * 32 + 2 * t);
            #pragma unroll
            for (int j = 0; j < 4; j++) {
                o32[4 * j] = pack_bf16(acc[4 * j], acc[4 * j + 1]);
                o32[4 * j + 8 * 512] = pack_bf16(acc[4 * j + 2], acc[4 * j + 3]);
            }
        }
        PROF(13);
        if (tid == 0) {
            const unsigned prev = atomicAdd(&g_done, 1u);
            if (prev == NCTA - 1) {
                g_done = 0;
                __threadfence();
                *(volatile unsigned*)&g_epoch = epoch;
            }
        }
    }
}

typedef CUresult (*EncodeFn)(CUtensorMap*, CUtensorMapDataType, cuuint32_t, void*, const cuuint64_t*, const cuuint64_t*,
                             const cuuint32_t*, const cuuint32_t*, CUtensorMapInterleave, CUtensorMapSwizzle,
                             CUtensorMapL2promotion, CUtensorMapFloatOOBfill);

void make_map(EncodeFn fn, CUtensorMap* m, const void* ptr, uint64_t inner, uint64_t outer, uint32_t box_in, uint32_t box_out, CUtensorMapSwizzle swz) {
    cuuint64_t dims[2] = {inner, outer};
    cuuint64_t strides[1] = {inner * 2};
    cuuint32_t box[2] = {box_in, box_out};
    cuuint32_t es[2] = {1, 1};
    fn(m, CU_TENSOR_MAP_DATA_TYPE_BFLOAT16, 2, const_cast<void*>(ptr), dims, strides, box, es, CU_TENSOR_MAP_INTERLEAVE_NONE, swz,
       CU_TENSOR_MAP_L2_PROMOTION_L2_128B, CU_TENSOR_MAP_FLOAT_OOB_FILL_NONE);
}

}

extern "C" void kernel_launch(void* const* d_in, const int* in_sizes, int n_in, void* d_out, int out_size) {
    (void)in_sizes; (void)n_in; (void)out_size;
    static EncodeFn fn = nullptr;
    if (!fn) {
        void* p = nullptr;
        cudaDriverEntryPointQueryResult qr;
        cudaGetDriverEntryPoint("cuTensorMapEncodeTiled", &p, cudaEnableDefault, &qr);
        fn = (EncodeFn)p;
        cudaFuncSetAttribute(fused_kernel, cudaFuncAttributeMaxDynamicSharedMemorySize, SM_ALLOC);
    }
    CUtensorMap tx, twq, two, twk, twv, tu;
    make_map(fn, &tx, d_in[0], 512, 2048, 64, 64, CU_TENSOR_MAP_SWIZZLE_128B);
    make_map(fn, &tu, d_in[5], 512, 2048, 8, 256, CU_TENSOR_MAP_SWIZZLE_NONE);
    make_map(fn, &twq, d_in[1], 512, 512, 64, 64, CU_TENSOR_MAP_SWIZZLE_128B);
    make_map(fn, &twk, d_in[2], 16, 512, 8, 64, CU_TENSOR_MAP_SWIZZLE_NONE);
    make_map(fn, &twv, d_in[3], 16, 512, 8, 64, CU_TENSOR_MAP_SWIZZLE_NONE);
    make_map(fn, &two, d_in[4], 512, 512, 64, 256, CU_TENSOR_MAP_SWIZZLE_128B);
    Params P;
    P.u = (const __nv_bfloat16*)d_in[5];
    P.lar = (const __nv_bfloat16*)d_in[6];
    P.aim = (const __nv_bfloat16*)d_in[7];
    P.cre = (const __nv_bfloat16*)d_in[8];
    P.cim = (const __nv_bfloat16*)d_in[9];
    P.logdt = (const __nv_bfloat16*)d_in[10];
    P.dskip = (const __nv_bfloat16*)d_in[11];
    P.out = (__nv_bfloat16*)d_out;
    fused_kernel<<<NCTA, NTHR, SM_ALLOC>>>(tx, twq, two, twk, twv, tu, P);
}
```

```cpp
#include <cuda_runtime.h>
#include <cuda_bf16.h>
#include <cuda_fp16.h>
#include <cuda.h>
#include <stdint.h>

namespace {

constexpr int SEQ = 2048;
constexpr int NCTA = 128, NTHR = 640;

constexpr int SM_A = 0;
constexpr int SM_WQ = 131072;
constexpr int SM_WKV = SM_WQ + 65536;
constexpr int SM_K = 0, SM_V = 65536;
constexpr int SM_B = 132096;

constexpr int PADU = 288, ULEN = PADU + 2048;
constexpr int WPAD = 16, W2LEN = WPAD + 1536, W3LEN = WPAD + 1024;
constexpr int TABN = 2240;
constexpr int S_U = 0;
constexpr int S_W3 = S_U + 4 * ULEN * 2;
constexpr int S_W5 = S_W3 + 4 * W2LEN * 2;
constexpr int S_W7 = S_W5 + 4 * W2LEN * 2;
constexpr int S_W9 = S_W7 + 4 * W3LEN * 2;
constexpr int S_TAB = S_W9 + 4 * W3LEN * 2;
constexpr int S_KC = 214016 - SM_B;
constexpr int S_Y = S_KC;
constexpr int SM_BAR = SM_B + S_KC + 16384;
constexpr int SM_TOTAL = SM_BAR + 1024;
constexpr int SM_ALLOC = SM_TOTAL + 1024;
static_assert(SM_V + 65536 + 256 <= SM_B && SM_ALLOC <= 232448 && S_TAB + 4 * TABN * 2 <= S_KC && SM_WKV + 16384 <= SM_B + S_KC, "smem map");

constexpr int TD0 = 0, TD1 = 560, CD = 544;
constexpr int TE0 = 1120, TE1 = 1168, CE = 1056;
constexpr int T2B = 1216, T2S = 160, T2C = 80, C2 = 80;
constexpr int T3B = 1856, T3S = 192, T3C = 96, C3 = 144;

constexpr int rne8(int t) {
    if (t < 256) return t;
    int sh = 0;
    while ((t >> sh) >= 256) sh++;
    int q = t >> sh, rem = t & ((1 << sh) - 1), half = 1 << (sh - 1);
    if (rem > half || (rem == half && (q & 1))) q++;
    return q << sh;
}
constexpr int kcidx(int p) {
    if (p < 256) return (p >> 3) * 24 + (p & 7);
    if (p < 512) return ((p - 256) >> 3) * 24 + 8 + (((p - 256) & 7) >> 1);
    if (p < 1024) { int q = p - 512, hi = q >> 8, rem = q & 255; return (rem >> 3) * 24 + 12 + 2 * hi + ((rem & 7) >> 2); }
    if (p < 2048) { int q = p - 1024; return ((q & 255) >> 3) * 24 + 16 + (q >> 8); }
    return 20;
}
constexpr int KC_ZERO = 23;
constexpr int tab_dense(int t) { return (t >= 0 && t <= 514) ? kcidx(rne8(t)) : KC_ZERO; }
constexpr int tab_extra(int t) { return (t >= 1027 && t <= 1028) ? kcidx(1024) : KC_ZERO; }
constexpr int tab_2(int s, int lag) { return (lag >= 32 && lag <= 63) ? kcidx(s == 0 ? 16 * (lag + 1) : 16 * lag + 4 * s) : KC_ZERO; }
constexpr int tab_3(int s, int lag) { return (lag >= 64 && lag <= 127) ? kcidx(s == 0 ? 16 * (lag + 1) : 16 * lag + 8) : KC_ZERO; }
struct TabMap {
    uint16_t v[TABN];
    constexpr TabMap() : v{} {
        for (int i = 0; i < 560; i++) { v[TD0 + i] = tab_dense(CD - i); v[TD1 + i] = tab_dense(CD + 1 - i); }
        for (int i = 0; i < 48; i++) { v[TE0 + i] = tab_extra(CE - i); v[TE1 + i] = tab_extra(CE + 1 - i); }
        for (int s = 0; s < 4; s++)
            for (int i = 0; i < T2C; i++) { v[T2B + s * T2S + i] = tab_2(s, C2 - i); v[T2B + s * T2S + T2C + i] = tab_2(s, C2 + 1 - i); }
        for (int s = 0; s < 2; s++)
            for (int i = 0; i < T3C; i++) { v[T3B + s * T3S + i] = tab_3(s, C3 - i); v[T3B + s * T3S + T3C + i] = tab_3(s, C3 + 1 - i); }
    }
};
__device__ const __align__(16) TabMap g_tabmap = TabMap();

__device__ __align__(1024) uint8_t g_kimg[65536];
__device__ __align__(1024) uint8_t g_vimg[65536 + 256];
__device__ __align__(1024) uint8_t g_oimg[16 * 131072];
__device__ unsigned long long g_flag_kv[64];
__device__ unsigned g_flag_o[128];
__device__ unsigned g_epoch;
__device__ unsigned g_done;

#define PROF(i) do {} while (0)
#define PROF2(i) do {} while (0)
#define PROFC(i) do {} while (0)

__device__ __forceinline__ uint32_t smem_u32(const void* p) { return (uint32_t)__cvta_generic_to_shared(p); }
__device__ __forceinline__ void mbar_init(uint32_t bar, uint32_t cnt) { asm volatile("mbarrier.init.shared::cta.b64 [%0], %1;" :: "r"(bar), "r"(cnt) : "memory"); }
__device__ __forceinline__ void mbar_expect_tx(uint32_t bar, uint32_t bytes) {
    asm volatile("mbarrier.arrive.expect_tx.shared::cta.b64 _, [%0], %1;" :: "r"(bar), "r"(bytes) : "memory"); }
__device__ __forceinline__ void mbar_wait(uint32_t bar, uint32_t parity) {
    uint32_t ok = 0;
    for (int it = 0; it < (1 << 22) && !ok; it++) {
        asm volatile("{ .reg .pred p; mbarrier.try_wait.parity.shared::cta.b64 p, [%1], %2; selp.u32 %0, 1, 0, p; }"
                     : "=r"(ok) : "r"(bar), "r"(parity) : "memory");
    }
}
__device__ __forceinline__ void tma_2d(uint32_t dst, const CUtensorMap* map, int c0, int c1, uint32_t bar) {
    asm volatile("cp.async.bulk.tensor.2d.shared::cluster.global.mbarrier::complete_tx::bytes [%0], [%1, {%3, %4}], [%2];"
                 :: "r"(dst), "l"((uint64_t)map), "r"(bar), "r"(c0), "r"(c1) : "memory");
}
__device__ __forceinline__ void tma_2d_mc(uint32_t dst, const CUtensorMap* map, int c0, int c1, uint32_t bar) {
    asm volatile("cp.async.bulk.tensor.2d.shared::cluster.global.mbarrier::complete_tx::bytes.multicast::cluster [%0], [%1, {%3, %4}], [%2], %5;"
                 :: "r"(dst), "l"((uint64_t)map), "r"(bar), "r"(c0), "r"(c1), "h"((uint16_t)3) : "memory");
}
__device__ __forceinline__ void bulk_g2s_mc(uint32_t dst, const void* src, uint32_t bytes, uint32_t bar) {
    asm volatile("cp.async.bulk.shared::cluster.global.mbarrier::complete_tx::bytes.multicast::cluster [%0], [%1], %2, [%3], %4;"
                 :: "r"(dst), "l"((uint64_t)src), "r"(bytes), "r"(bar), "h"((uint16_t)3) : "memory");
}
__device__ __forceinline__ void pair_sync(uint32_t bar, uint32_t peer) {
    uint32_t ra;
    asm volatile("mapa.shared::cluster.u32 %0, %1, %2;" : "=r"(ra) : "r"(bar), "r"(peer));
    asm volatile("mbarrier.arrive.release.cluster.shared::cluster.b64 _, [%0];" :: "r"(ra) : "memory");
    asm volatile("mbarrier.arrive.release.cluster.shared::cta.b64 _, [%0];" :: "r"(bar) : "memory");
    uint32_t ok = 0;
    for (int it = 0; it < (1 << 22) && !ok; it++) {
        asm volatile("{ .reg .pred p; mbarrier.try_wait.parity.acquire.cluster.shared::cta.b64 p, [%1], 0; selp.u32 %0, 1, 0, p; }"
                     : "=r"(ok) : "r"(bar) : "memory");
    }
}
__device__ __forceinline__ void fence_async_all() { asm volatile("fence.proxy.async;" ::: "memory"); }
__device__ __forceinline__ void fence_async_smem() { asm volatile("fence.proxy.async.shared::cta;" ::: "memory"); }
__device__ __forceinline__ unsigned ld_acquire(const unsigned* p) {
    unsigned v; asm volatile("ld.acquire.gpu.global.u32 %0, [%1];" : "=r"(v) : "l"(p) : "memory"); return v; }
__device__ __forceinline__ void st_release(unsigned* p, unsigned v) { asm volatile("st.release.gpu.global.u32 [%0], %1;" :: "l"(p), "r"(v) : "memory"); }
__device__ __forceinline__ void wait_flag(const unsigned* p, unsigned epoch) {
    for (int it = 0; it < (1 << 22); it++) { if (ld_acquire(p) == epoch) break; }
}
__device__ __forceinline__ unsigned long long ld_acquire64(const unsigned long long* p) {
    unsigned long long v; asm volatile("ld.acquire.gpu.global.u64 %0, [%1];" : "=l"(v) : "l"(p) : "memory"); return v; }
__device__ __forceinline__ void st_release64(unsigned long long* p, unsigned long long v) { asm volatile("st.release.gpu.global.u64 [%0], %1;" :: "l"(p), "l"(v) : "memory"); }
__device__ __forceinline__ float wait_flag64(const unsigned long long* p, unsigned epoch) {
    unsigned long long v = 0;
    for (int it = 0; it < (1 << 22); it++) { v = ld_acquire64(p); if ((unsigned)(v >> 32) == epoch) break; }
    return __uint_as_float((unsigned)v);
}
__device__ __forceinline__ void tma_3d_mc(uint32_t dst, const CUtensorMap* map, int c0, int c1, int c2, uint32_t bar) {
    asm volatile("cp.async.bulk.tensor.3d.shared::cluster.global.mbarrier::complete_tx::bytes.multicast::cluster [%0], [%1, {%3, %4, %5}], [%2], %6;"
                 :: "r"(dst), "l"((uint64_t)map), "r"(bar), "r"(c0), "r"(c1), "r"(c2), "h"((uint16_t)3) : "memory");
}
__device__ __forceinline__ void bar_sync(int id, int n) { asm volatile("bar.sync %0, %1;" :: "r"(id), "r"(n) : "memory"); }
__device__ __forceinline__ void bar_arrive(int id, int n) { asm volatile("bar.arrive %0, %1;" :: "r"(id), "r"(n) : "memory"); }
__device__ __forceinline__ void mbar_arrive(uint32_t bar) { asm volatile("mbarrier.arrive.shared::cta.b64 _, [%0];" :: "r"(bar) : "memory"); }

__device__ __forceinline__ uint64_t make_desc(uint32_t saddr, uint32_t lbo, uint32_t sbo, uint32_t swz) {
    uint64_t d = 0;
    d |= (uint64_t)((saddr & 0x3FFFF) >> 4);
    d |= (uint64_t)((lbo >> 4) & 0x3FFF) << 16;
    d |= (uint64_t)((sbo >> 4) & 0x3FFF) << 32;
    d |= (uint64_t)swz << 62;
    return d;
}
__device__ __forceinline__ void wg_fence() { asm volatile("wgmma.fence.sync.aligned;" ::: "memory"); }
__device__ __forceinline__ void wg_commit() { asm volatile("wgmma.commit_group.sync.aligned;" ::: "memory"); }
template<int N> __device__ __forceinline__ void wg_wait() { asm volatile("wgmma.wait_group.sync.aligned %0;" :: "n"(N) : "memory"); }
#define A4(d, o) "+f"(d[o + 0]), "+f"(d[o + 1]), "+f"(d[o + 2]), "+f"(d[o + 3])
#define A16(d, o) A4(d, o), A4(d, o + 4), A4(d, o + 8), A4(d, o + 12)

__device__ __forceinline__ void wg_pv(float* d, const uint32_t* a, uint64_t desc) {
    asm volatile("wgmma.mma_async.sync.aligned.m64n24k16.f32.bf16.bf16 {%0,%1,%2,%3,%4,%5,%6,%7,%8,%9,%10,%11}, {%12,%13,%14,%15}, %16, 1, 1, 1, 1;"
                 : A4(d, 0), A4(d, 4), A4(d, 8) : "r"(a[0]), "r"(a[1]), "r"(a[2]), "r"(a[3]), "l"(desc));
}
__device__ __forceinline__ void wg_qk(float* d, const uint32_t* a, uint64_t desc) {
    asm volatile("wgmma.mma_async.sync.aligned.m64n64k16.f32.bf16.bf16 {%0,%1,%2,%3,%4,%5,%6,%7,%8,%9,%10,%11,%12,%13,%14,%15,%16,%17,%18,%19,%20,%21,%22,%23,%24,%25,%26,%27,%28,%29,%30,%31}, {%32,%33,%34,%35}, %36, 0, 1, 1, 0;"
                 : A16(d, 0), A16(d, 16) : "r"(a[0]), "r"(a[1]), "r"(a[2]), "r"(a[3]), "l"(desc));
}
__device__ __forceinline__ void wg_ss32(float* d, uint64_t da, uint64_t db) {
    asm volatile("wgmma.mma_async.sync.aligned.m64n32k16.f32.bf16.bf16 {%0,%1,%2,%3,%4,%5,%6,%7,%8,%9,%10,%11,%12,%13,%14,%15}, %16, %17, 1, 1, 1, 0, 1;"
                 : A16(d, 0) : "l"(da), "l"(db));
}
__device__ __forceinline__ void wg_ss16(float* d, uint64_t da, uint64_t db) {
    asm volatile("wgmma.mma_async.sync.aligned.m64n16k16.f32.bf16.bf16 {%0,%1,%2,%3,%4,%5,%6,%7}, %8, %9, 1, 1, 1, 0, 1;"
                 : A4(d, 0), A4(d, 4) : "l"(da), "l"(db));
}
template<int N> __device__ __forceinline__ void fence_regs(float* r) {
    #pragma unroll
    for (int i = 0; i < N; i++) asm volatile("" : "+f"(r[i]) :: "memory");
}
__device__ __forceinline__ void mma_bf16(float* d, uint32_t a0, uint32_t a1, uint32_t a2, uint32_t a3, uint32_t b0, uint32_t b1) {
    asm volatile("mma.sync.aligned.m16n8k16.row.col.f32.bf16.bf16.f32 {%0,%1,%2,%3}, {%4,%5,%6,%7}, {%8,%9}, {%0,%1,%2,%3};"
                 : "+f"(d[0]), "+f"(d[1]), "+f"(d[2]), "+f"(d[3]) : "r"(a0), "r"(a1), "r"(a2), "r"(a3), "r"(b0), "r"(b1));
}
__device__ __forceinline__ void mma_f16(float* d, const uint32_t* a, uint32_t b0, uint32_t b1) {
    asm volatile("mma.sync.aligned.m16n8k16.row.col.f32.f16.f16.f32 {%0,%1,%2,%3}, {%4,%5,%6,%7}, {%8,%9}, {%0,%1,%2,%3};"
                 : "+f"(d[0]), "+f"(d[1]), "+f"(d[2]), "+f"(d[3]) : "r"(a[0]), "r"(a[1]), "r"(a[2]), "r"(a[3]), "r"(b0), "r"(b1));
}
__device__ __forceinline__ void ldsm4(uint32_t* r, uint32_t addr) {
    asm volatile("ldmatrix.sync.aligned.m8n8.x4.shared.b16 {%0,%1,%2,%3}, [%4];" : "=r"(r[0]), "=r"(r[1]), "=r"(r[2]), "=r"(r[3]) : "r"(addr) : "memory");
}
__device__ __forceinline__ void ldsm4t(uint32_t* r, uint32_t addr) {
    asm volatile("ldmatrix.sync.aligned.m8n8.x4.trans.shared.b16 {%0,%1,%2,%3}, [%4];" : "=r"(r[0]), "=r"(r[1]), "=r"(r[2]), "=r"(r[3]) : "r"(addr) : "memory");
}
__device__ __forceinline__ uint32_t lds32(uint32_t addr) { uint32_t v; asm volatile("ld.shared.u32 %0, [%1];" : "=r"(v) : "r"(addr) : "memory"); return v; }
__device__ __forceinline__ float ex2f(float x) { float r; asm("ex2.approx.ftz.f32 %0, %1;" : "=f"(r) : "f"(x)); return r; }
__device__ __forceinline__ uint32_t pack_bf16(float lo, float hi) { uint32_t r; asm("cvt.rn.bf16x2.f32 %0, %1, %2;" : "=r"(r) : "f"(hi), "f"(lo)); return r; }
__device__ __forceinline__ uint32_t pack_f16(float lo, float hi) { uint32_t r; asm("cvt.rn.f16x2.f32 %0, %1, %2;" : "=r"(r) : "f"(hi), "f"(lo)); return r; }
__device__ __forceinline__ float bf_lo(uint32_t v) { return __uint_as_float(v << 16); }
__device__ __forceinline__ float bf_hi(uint32_t v) { return __uint_as_float(v & 0xFFFF0000u); }
__device__ __forceinline__ float bf_round(float x) { return __bfloat162float(__float2bfloat16_rn(x)); }

__device__ __forceinline__ uint32_t exp_mufu(float x0, float x1) { return pack_bf16(ex2f(x0), ex2f(x1)); }
#define SW_MAGIC (256.0f + 127.0f - 0.598938f)
__device__ __forceinline__ uint32_t exp_sw(float x0, float x1, uint32_t cA, uint32_t cB) {
    float t0 = x0 + SW_MAGIC, t1 = x1 + SW_MAGIC;
    uint32_t L, mh, ec, r;
    asm("prmt.b32 %0, %1, %2, 0x6521;" : "=r"(L) : "r"(__float_as_uint(t0)), "r"(__float_as_uint(t1)));
    asm("lop3.b32 %0, %1, 0x007F007F, %2, 0xEA;" : "=r"(mh) : "r"(L), "r"(cA));
    asm("lop3.b32 %0, %1, 0x7F807F80, %2, 0xEA;" : "=r"(ec) : "r"(L), "r"(cB));
    asm("fma.rn.bf16x2 %0, %1, %2, %3;" : "=r"(r) : "r"(L), "r"(mh), "r"(ec));
    return r;
}
constexpr uint32_t MUFU_MASK = 0x4949;

struct cf { float x, y; };
__device__ __forceinline__ cf cmul(cf a, cf b) { cf r; r.x = a.x * b.x - a.y * b.y; r.y = a.x * b.y + a.y * b.x; return r; }
__device__ __forceinline__ cf cexp_p(float a2, float b, float p) {
    float e = ex2f(a2 * p);
    float ph = b * p;
    ph -= (ph + 12582912.0f) - 12582912.0f;
    float ang = ph * 6.283185307f;
    cf r; r.x = e * __cosf(ang); r.y = e * __sinf(ang);
    return r;
}
__device__ __forceinline__ uint32_t h2_cmul(uint32_t w, uint32_t wsw, uint32_t e) {
    __half2 hw = *(__half2*)&w, hs = *(__half2*)&wsw, he = *(__half2*)&e;
    __half2 r = __hfma2(hs, __high2half2(he), __hmul2(hw, __low2half2(he)));
    return *(uint32_t*)&r;
}

template<bool B> struct BoolC { static constexpr bool value = B; };
struct Params {
    const __nv_bfloat16 *u, *lar, *aim, *cre, *cim, *logdt, *dskip;
    __nv_bfloat16* out;
};

constexpr int B_O = 0, B_KV = 8, B_X = 16, B_WO = 18, B_U = 19, B_ST = 20, B_H = 21, NBAR = 23;

__device__ __forceinline__ void helper_role(const Params& P, uint8_t* sp) {
    const int tid = threadIdx.x - 544;
    const int d0 = blockIdx.x * 4;
    uint8_t* sB = sp + SM_B;
    const uint2 dsk = __ldg((const uint2*)(P.dskip + d0));
    {
        const uint32_t* map = (const uint32_t*)g_tabmap.v;
        uint32_t mp[12];
        #pragma unroll
        for (int i = 0; i < 12; i++) { const int w = tid + 96 * i; mp[i] = (w < TABN / 2) ? __ldg(map + w) : 0u; }
        bar_sync(8, 640);
        #pragma unroll 1
        for (int cc = 0; cc < 4; cc++) {
            const float* kc = (const float*)(sB + S_KC + cc * 4096);
            uint32_t* tab = (uint32_t*)(sB + S_TAB + cc * TABN * 2);
            #pragma unroll
            for (int i = 0; i < 12; i++) { const int w = tid + 96 * i; if (w < TABN / 2) tab[w] = pack_bf16(kc[mp[i] & 0xFFFF], kc[mp[i] >> 16]); }
        }
    }
    bar_arrive(9, 608);
    PROF2(2);
    bar_sync(10, 608);
    {
        uint32_t dd[4] = {__byte_perm(dsk.x, 0, 0x1010), __byte_perm(dsk.x, 0, 0x3232), __byte_perm(dsk.y, 0, 0x1010), __byte_perm(dsk.y, 0, 0x3232)};
        #pragma unroll 2
        for (int pi = tid; pi < 1024; pi += 96) {
            const int l = 2 * pi;
            uint32_t r[4];
            #pragma unroll
            for (int cc = 0; cc < 4; cc++) {
                const uint32_t y2 = *(const uint32_t*)(sB + S_Y + cc * 4096 + l * 2);
                const uint32_t u2 = *(const uint32_t*)(sB + S_U + cc * ULEN * 2 + (PADU + l) * 2);
                __nv_bfloat162 pr = __hmul2(*(const __nv_bfloat162*)&u2, *(const __nv_bfloat162*)&dd[cc]);
                __nv_bfloat162 sm = __hadd2(*(const __nv_bfloat162*)&y2, pr);
                r[cc] = *(uint32_t*)&sm;
            }
            *(uint2*)(P.out + (size_t)l * 1024 + 512 + d0) = make_uint2(__byte_perm(r[0], r[1], 0x5410), __byte_perm(r[2], r[3], 0x5410));
            *(uint2*)(P.out + (size_t)(l + 1) * 1024 + 512 + d0) = make_uint2(__byte_perm(r[0], r[1], 0x7632), __byte_perm(r[2], r[3], 0x7632));
        }
    }
    bar_arrive(11, 128);
    PROF2(4);
}

__global__ void __cluster_dims__(2, 1, 1) __launch_bounds__(NTHR, 1)
fused_kernel(const __grid_constant__ CUtensorMap tm_x, const __grid_constant__ CUtensorMap tm_wq,
             const __grid_constant__ CUtensorMap tm_wo, const __grid_constant__ CUtensorMap tm_wk,
             const __grid_constant__ CUtensorMap tm_wv, const __grid_constant__ CUtensorMap tm_u, const Params P) {
    extern __shared__ uint8_t smem_raw[];
    const uint32_t sb = (smem_u32(smem_raw) + 1023u) & ~1023u;
    uint8_t* sp = smem_raw + (sb - smem_u32(smem_raw));

    const int tid = threadIdx.x, warp = tid >> 5, lane = tid & 31, wg = tid >> 7, wiw = warp & 3;
    const int g = lane >> 2, t = lane & 3;
    const int qb = blockIdx.x >> 3, hg = blockIdx.x & 7;
    const uint32_t rank = blockIdx.x & 1;
    const int rowhalf = wg & 1, nh = wg >> 1;
    const bool kv_cta = hg < 4;
    const int kv_sel = hg >> 1;
    const bool kv_wg = kv_cta && (wg == (hg & 1));

    const uint32_t bars = sb + SM_BAR;
    float* s_misc = (float*)(sp + SM_BAR + 256);
    const CUtensorMap* tm_kv = kv_sel ? &tm_wv : &tm_wk;

    PROF(0);
    unsigned short p_lar = 0, p_aim = 0, p_cre = 0, p_cim = 0, p_ldt = 0;
    if (wg < 4) {
        const int n = (blockIdx.x * 4 + wg) * 128 + (tid & 127);
        p_lar = __ldg((const unsigned short*)P.lar + n);
        p_aim = __ldg((const unsigned short*)P.aim + n);
        p_cre = __ldg((const unsigned short*)P.cre + n);
        p_cim = __ldg((const unsigned short*)P.cim + n);
        p_ldt = __ldg((const unsigned short*)P.logdt + blockIdx.x * 4 + wg);
    } else if (warp == 16) {
        const CUtensorMap* m = lane == 0 ? &tm_x : lane == 1 ? &tm_wq : lane == 2 ? tm_kv : lane == 3 ? &tm_u : &tm_wo;
        if (lane < 5) asm volatile("prefetch.tensormap [%0];" :: "l"((uint64_t)m) : "memory");
        if (lane < NBAR) {
            const uint32_t bar = bars + 8 * lane;
            mbar_init(bar, lane >= B_H ? 2 : 1);
            asm volatile("fence.mbarrier_init.release.cluster;" ::: "memory");
            fence_async_smem();
            const uint32_t bytes = lane < B_X ? 16384u : lane < B_WO ? (98304u + (kv_cta ? 8192u : 0u)) : lane == B_WO ? 65536u : 32768u;
            if (lane <= B_U) mbar_expect_tx(bar, bytes);
        }
        __syncwarp();
        if (lane < 2) tma_2d(sb + SM_WQ + lane * 32768, &tm_wq, hg * 64, lane * 256, bars + 8 * (B_X + lane));
        else if (lane < 6 && kv_cta) tma_2d(sb + SM_WKV + (lane - 2) * 4096, tm_kv, ((lane - 2) >> 1) * 8, (lane & 1) * 256, bars + 8 * (B_X + (lane & 1)));
    }
    asm volatile("barrier.cluster.arrive.release.aligned;" ::: "memory");
    const unsigned epoch = *(volatile unsigned*)&g_epoch + 1u;
    asm volatile("barrier.cluster.wait.acquire.aligned;" ::: "memory");
    PROF(5);

    if (warp == 16) {
        if (lane == 0) tma_3d_mc(sb + SM_A + rank * 65536, &tm_x, 0, qb * 128, rank * 4, bars + 8 * (B_X + rank));
        bar_sync(8, 640);
        if (lane == 0) pair_sync(bars + 8 * B_H, rank ^ 1);
        __syncwarp();
        if (lane < 4) tma_2d_mc(sb + SM_B + S_W3 + (rank * 4 + lane) * 4096, &tm_u, (blockIdx.x >> 1) * 8, (rank * 4 + lane) * 256, bars + 8 * B_U);
        *(uint2*)(sp + SM_V + 32768 + lane * 8) = make_uint2(0x3F803F80u, 0x3F803F80u);
        fence_async_smem();
        float km = wait_flag64(&g_flag_kv[2 * lane], epoch);
        float vm = wait_flag64(&g_flag_kv[2 * lane + 1], epoch);
        __syncwarp();
        if (lane < 8) {
            fence_async_all();
            const uint32_t bar = bars + 8 * (B_KV + lane);
            if (rank == 0) bulk_g2s_mc(sb + SM_K + lane * 8192, g_kimg + lane * 8192, 8192, bar);
            else {
                bulk_g2s_mc(sb + SM_V + lane * 4096, g_vimg + lane * 4096, 4096, bar);
                bulk_g2s_mc(sb + SM_V + 33024 + (7 - lane) * 4096, g_vimg + 33024 + (7 - lane) * 4096, 4096, bar);
            }
        }
        #pragma unroll
        for (int o = 16; o; o >>= 1) { km = fmaxf(km, __shfl_xor_sync(0xffffffffu, km, o)); vm = fmaxf(vm, __shfl_xor_sync(0xffffffffu, vm, o)); }
        if (lane == 0) { s_misc[16] = km; s_misc[17] = vm; mbar_arrive(bars + 8 * B_ST); }
        bar_sync(11, 128);
        if (lane < 2) { fence_async_smem(); tma_2d(sb + SM_B + lane * 32768, &tm_wo, hg * 64, lane * 256, bars + 8 * B_WO); }
        bar_sync(12, 544);
        if (lane == 0) {
            st_release(&g_flag_o[blockIdx.x], epoch);
            pair_sync(bars + 8 * (B_H + 1), rank ^ 1);
        }
        __syncwarp();
        if (lane < 4) {
            const int src = 2 * lane + rank;
            wait_flag(&g_flag_o[qb * 8 + src], epoch);
            fence_async_all();
            bulk_g2s_mc(sb + SM_A + src * 16384, g_oimg + qb * 131072 + src * 16384, 16384, bars + 8 * (B_O + src));
        }
        __syncwarp();
        if (lane == 0) {
            const unsigned prev = atomicAdd(&g_done, 1u);
            if (prev == NCTA - 1) {
                g_done = 0;
                __threadfence();
                *(volatile unsigned*)&g_epoch = epoch;
            }
        }
    } else if (wg == 4) {
        helper_role(P, sp);
    } else {
        uint8_t* sB = sp + SM_B;
        const uint32_t sBa = sb + SM_B;
        {
            const int c = wg;
            const float dt = bf_round(expf(bf_lo(p_ldt)));
            const float are = -bf_round(expf(bf_lo(p_lar))) * dt;
            const float aim = bf_lo(p_aim) * dt;
            float cr = 2.0f * (bf_lo(p_cre) * dt);
            float ci = 2.0f * (bf_lo(p_cim) * dt);
            const float a2 = are * 1.4426950408889634f, bb = aim * 0.15915494309189535f;
            float m = fmaxf(fabsf(cr), fabsf(ci));
            #pragma unroll
            for (int o = 16; o; o >>= 1) m = fmaxf(m, __shfl_xor_sync(0xffffffffu, m, o));
            int ebits = (__float_as_uint(m) >> 23) & 0xFF;
            ebits = min(max(ebits, 2), 250);
            const float scale = __uint_as_float((uint32_t)(ebits + 1) << 23);
            const float iscale = __uint_as_float((uint32_t)(253 - ebits) << 23);
            cf cc; cc.x = cr * iscale; cc.y = ci * iscale;

            const uint32_t stg = sBa + S_KC + warp * 1024;
            uint4* stp = (uint4*)(sB + S_KC + warp * 1024 + lane * 32);
            const uint32_t fa = stg + t * 32 + g * 4;

            uint32_t af[4][2][4];
            cf E256;
            {
                const cf E8 = cexp_p(a2, bb, 8.0f);
                uint32_t w[8];
                cf cur; cur.x = 1.0f; cur.y = 0.0f;
                w[0] = pack_f16(1.0f, 0.0f);
                cur = E8; w[1] = pack_f16(cur.x, cur.y);
                #pragma unroll
                for (int i = 2; i < 8; i++) { cur = cmul(cur, E8); w[i] = pack_f16(cur.x, cur.y); }
                stp[0] = make_uint4(w[0], w[1], w[2], w[3]);
                stp[1] = make_uint4(w[4], w[5], w[6], w[7]);
                const cf E64 = cexp_p(a2, bb, 64.0f);
                const cf E128 = cmul(E64, E64), E192 = cmul(E128, E64);
                E256 = cexp_p(a2, bb, 256.0f);
                const uint32_t e1 = pack_f16(E64.x, E64.y), e2 = pack_f16(E128.x, E128.y), e3 = pack_f16(E192.x, E192.y);
                __syncwarp();
                #pragma unroll
                for (int s = 0; s < 4; s++) {
                    #pragma unroll
                    for (int hh = 0; hh < 2; hh++) {
                        const uint32_t w0 = lds32(fa + s * 256 + hh * 128);
                        const uint32_t wsw = __byte_perm(w0, 0, 0x1032) ^ 0x00008000u;
                        const int src = 8 * s + t + 4 * hh;
                        const uint32_t f1 = __shfl_sync(0xffffffffu, e1, src), f2 = __shfl_sync(0xffffffffu, e2, src), f3 = __shfl_sync(0xffffffffu, e3, src);
                        af[s][0][2 * hh] = w0;
                        af[s][0][2 * hh + 1] = h2_cmul(w0, wsw, f1);
                        af[s][1][2 * hh] = h2_cmul(w0, wsw, f2);
                        af[s][1][2 * hh + 1] = h2_cmul(w0, wsw, f3);
                    }
                }
                __syncwarp();
            }
            float acc[2][3][4];
            #pragma unroll
            for (int i = 0; i < 24; i++) (&acc[0][0][0])[i] = 0.0f;
            const cf E1 = cexp_p(a2, bb, 1.0f);
            const cf E2 = cmul(E1, E1), E4 = cmul(E2, E2);
            cf X512;
            #pragma unroll
            for (int nt = 0; nt < 3; nt++) {
                uint32_t xv[8];
                if (nt == 0) {
                    cf cur = cc;
                    xv[0] = pack_f16(cur.x, -cur.y);
                    #pragma unroll
                    for (int i = 1; i < 8; i++) { cur = cmul(cur, E1); xv[i] = pack_f16(cur.x, -cur.y); }
                } else if (nt == 1) {
                    cf cur = cmul(cc, E256);
                    X512 = cmul(cur, E256);
                    xv[0] = pack_f16(cur.x, -cur.y);
                    #pragma unroll
                    for (int i = 1; i < 4; i++) { cur = cmul(cur, E2); xv[i] = pack_f16(cur.x, -cur.y); }
                    cur = cmul(X512, E4);
                    xv[4] = pack_f16(X512.x, -X512.y); xv[5] = pack_f16(cur.x, -cur.y);
                    X512 = cmul(X512, E256);
                    cur = cmul(X512, E4);
                    xv[6] = pack_f16(X512.x, -X512.y); xv[7] = pack_f16(cur.x, -cur.y);
                } else {
                    cf cur = X512;
                    #pragma unroll
                    for (int i = 0; i < 5; i++) { cur = cmul(cur, E256); xv[i] = pack_f16(cur.x, -cur.y); }
                    xv[5] = 0; xv[6] = 0; xv[7] = 0;
                }
                stp[0] = make_uint4(xv[0], xv[1], xv[2], xv[3]);
                stp[1] = make_uint4(xv[4], xv[5], xv[6], xv[7]);
                __syncwarp();
                #pragma unroll
                for (int s = 0; s < 4; s++) {
                    const uint32_t b0 = lds32(fa + s * 256), b1 = lds32(fa + s * 256 + 128);
                    mma_f16(acc[0][nt], af[s][0], b0, b1);
                    mma_f16(acc[1][nt], af[s][1], b0, b1);
                }
                __syncwarp();
            }
            float* kc = (float*)(sB + S_KC + c * 4096);
            bar_sync(4 + c, 128);
            #pragma unroll 1
            for (int step = 0; step < 4; step++) {
                if ((warp & 3) == step) {
                    #pragma unroll
                    for (int mt = 0; mt < 2; mt++)
                        #pragma unroll
                        for (int nt = 0; nt < 3; nt++)
                            #pragma unroll
                            for (int hh = 0; hh < 2; hh++) {
                                float2* p = (float2*)(kc + (mt * 16 + hh * 8 + g) * 24 + nt * 8 + 2 * t);
                                float2 v = make_float2(acc[mt][nt][2 * hh] * scale, acc[mt][nt][2 * hh + 1] * scale);
                                if (step) { float2 o = *p; v.x += o.x; v.y += o.y; }
                                *p = v;
                            }
                }
                if (step < 3) bar_sync(4 + c, 128);
            }
        }

        PROF(4);
        uint32_t q[2][4];
        {
            float acc[16], akv[8];
            #pragma unroll
            for (int i = 0; i < 16; i++) acc[i] = 0.0f;
            #pragma unroll
            for (int i = 0; i < 8; i++) akv[i] = 0.0f;
            fence_regs<16>(acc);
            fence_regs<8>(akv);
            const uint64_t dA = make_desc(sb + SM_A + rowhalf * 8192, 16, 1024, 1);
            const uint64_t dB = make_desc(sb + SM_WQ + nh * 64, 16, 1024, 1);
            const uint64_t dC = make_desc(sb + SM_WKV, 128, 8192, 0);
            auto proj_loop = [&](auto KV) {
                #pragma unroll 1
                for (int ch = 0; ch < 8; ch++) {
                    if ((ch & 3) == 0) mbar_wait(bars + 8 * (B_X + (ch >> 2)), 0);
                    if (ch == 0) PROF(2);
                    if (ch == 4) PROF(15);
                    wg_fence();
                    if (decltype(KV)::value) {
                        #pragma unroll
                        for (int ks = 0; ks < 4; ks++) wg_ss16(akv, dA + ch * 1024 + ks * 2, dC + (ch * 4 + ks) * 16);
                    }
                    #pragma unroll
                    for (int ks = 0; ks < 4; ks++) wg_ss32(acc, dA + ch * 1024 + ks * 2, dB + (ch * 4 + ks) * 128);
                    wg_commit();
                }
                wg_wait<0>();
            };
            if (kv_wg) proj_loop(BoolC<true>()); else proj_loop(BoolC<false>());
            fence_regs<16>(acc);
            fence_regs<8>(akv);
            if (kv_wg) {
                const int key = qb * 128 + rowhalf * 64 + wiw * 16 + g;
                uint32_t pk[4];
                #pragma unroll
                for (int i = 0; i < 4; i++) pk[i] = pack_bf16(akv[2 * i], akv[2 * i + 1]);
                float st;
                if (kv_sel == 0) {
                    uint8_t* b = g_kimg + (key >> 3) * 256 + (key & 7) * 16 + 4 * t;
                    *(uint32_t*)(b) = pk[0]; *(uint32_t*)(b + 256) = pk[1]; *(uint32_t*)(b + 128) = pk[2]; *(uint32_t*)(b + 384) = pk[3];
                    float n0 = bf_lo(pk[0]) * bf_lo(pk[0]) + bf_hi(pk[0]) * bf_hi(pk[0]) + bf_lo(pk[2]) * bf_lo(pk[2]) + bf_hi(pk[2]) * bf_hi(pk[2]);
                    float n1 = bf_lo(pk[1]) * bf_lo(pk[1]) + bf_hi(pk[1]) * bf_hi(pk[1]) + bf_lo(pk[3]) * bf_lo(pk[3]) + bf_hi(pk[3]) * bf_hi(pk[3]);
                    n0 += __shfl_xor_sync(0xffffffffu, n0, 1); n0 += __shfl_xor_sync(0xffffffffu, n0, 2);
                    n1 += __shfl_xor_sync(0xffffffffu, n1, 1); n1 += __shfl_xor_sync(0xffffffffu, n1, 2);
                    st = (n0 != n0 || n1 != n1) ? __int_as_float(0x7f800000) : fmaxf(n0, n1);
                } else {
                    const int s = key >> 4;
                    uint8_t* lo = g_vimg + s * 256 + g * 16 + 4 * t;
                    uint8_t* hi = g_vimg + 33024 + (127 - s) * 256 + g * 16 + 4 * t;
                    *(uint32_t*)(lo) = pk[0]; *(uint32_t*)(lo + 128) = pk[1]; *(uint32_t*)(hi) = pk[2]; *(uint32_t*)(hi + 128) = pk[3];
                    st = 0.0f;
                    #pragma unroll
                    for (int i = 0; i < 4; i++) {
                        float a = fabsf(bf_lo(pk[i])), b = fabsf(bf_hi(pk[i]));
                        st = (a != a || b != b) ? __int_as_float(0x7f800000) : fmaxf(st, fmaxf(a, b));
                    }
                }
                #pragma unroll
                for (int o = 16; o; o >>= 1) st = fmaxf(st, __shfl_xor_sync(0xffffffffu, st, o));
                if (lane == 0) s_misc[20 + wiw] = st;
                __threadfence();
                bar_sync(3, 128);
                if ((tid & 127) == 0) {
                    st = fmaxf(fmaxf(s_misc[20], s_misc[21]), fmaxf(s_misc[22], s_misc[23]));
                    st_release64(&g_flag_kv[(qb * 2 + rowhalf) * 2 + kv_sel], ((unsigned long long)epoch << 32) | __float_as_uint(st));
                }
            }
            const float QS = 0.25f * 1.4426950408889634f;
            float qm = 0.0f;
            #pragma unroll
            for (int i = 0; i < 2; i++) {
                #pragma unroll
                for (int j = 0; j < 4; j++) q[i][j] = pack_bf16(acc[8 * i + 2 * j] * QS, acc[8 * i + 2 * j + 1] * QS);
                float n0 = bf_lo(q[i][0]) * bf_lo(q[i][0]) + bf_hi(q[i][0]) * bf_hi(q[i][0]) + bf_lo(q[i][2]) * bf_lo(q[i][2]) + bf_hi(q[i][2]) * bf_hi(q[i][2]);
                float n1 = bf_lo(q[i][1]) * bf_lo(q[i][1]) + bf_hi(q[i][1]) * bf_hi(q[i][1]) + bf_lo(q[i][3]) * bf_lo(q[i][3]) + bf_hi(q[i][3]) * bf_hi(q[i][3]);
                n0 += __shfl_xor_sync(0xffffffffu, n0, 1); n0 += __shfl_xor_sync(0xffffffffu, n0, 2);
                n1 += __shfl_xor_sync(0xffffffffu, n1, 1); n1 += __shfl_xor_sync(0xffffffffu, n1, 2);
                qm = (n0 != n0 || n1 != n1) ? __int_as_float(0x7f800000) : fmaxf(qm, fmaxf(n0, n1));
            }
            #pragma unroll
            for (int o = 16; o; o >>= 1) qm = fmaxf(qm, __shfl_xor_sync(0xffffffffu, qm, o));
            if (lane == 0) s_misc[warp] = qm;
        }
        bar_sync(8, 640);
        PROF(3);
        if (tid < 4 * (PADU / 8)) *(uint4*)(sB + S_U + (tid / (PADU / 8)) * ULEN * 2 + (tid % (PADU / 8)) * 16) = make_uint4(0, 0, 0, 0);
        PROF(8);
        mbar_wait(bars + 8 * B_U, 0);
        PROF(14);
        #pragma unroll
        for (int i = 0; i < 2; i++) {
            const int l = 2 * (tid + 512 * i);
            const uint2 r0 = *(const uint2*)(sB + S_W3 + l * 16 + rank * 8), r1 = *(const uint2*)(sB + S_W3 + l * 16 + 16 + rank * 8);
            uint32_t* dst = (uint32_t*)(sB + S_U + (PADU + l) * 2);
            dst[0] = __byte_perm(r0.x, r1.x, 0x5410);
            dst[ULEN / 2] = __byte_perm(r0.x, r1.x, 0x7632);
            dst[ULEN] = __byte_perm(r0.y, r1.y, 0x5410);
            dst[3 * ULEN / 2] = __byte_perm(r0.y, r1.y, 0x7632);
        }
        bar_sync(1, 512);
        #pragma unroll 1
        for (int task = tid; task < 4 * 194; task += 512) {
            const int c = task / 194, i = task % 194;
            const uint4* src = (const uint4*)(sB + S_U + c * ULEN * 2 + (PADU + 8 * i - WPAD - 8) * 2);
            const uint4 v0 = src[0], v1 = src[1], v2 = src[2];
            float x[24];
            const uint32_t vv[12] = {v0.x, v0.y, v0.z, v0.w, v1.x, v1.y, v1.z, v1.w, v2.x, v2.y, v2.z, v2.w};
            #pragma unroll
            for (int k = 0; k < 12; k++) { x[2 * k] = bf_lo(vv[k]); x[2 * k + 1] = bf_hi(vv[k]); }
            float w3[12], w5[8];
            #pragma unroll
            for (int e = 0; e < 12; e++) w3[e] = (x[3 + e] + x[4 + e]) + x[5 + e];
            #pragma unroll
            for (int e = 0; e < 8; e++) w5[e] = w3[4 + e] + (x[6 + e] + x[10 + e]);
            *(uint4*)(sB + S_W3 + c * W2LEN * 2 + i * 16) = make_uint4(pack_bf16(w3[0], w3[1]), pack_bf16(w3[2], w3[3]), pack_bf16(w3[4], w3[5]), pack_bf16(w3[6], w3[7]));
            *(uint4*)(sB + S_W5 + c * W2LEN * 2 + i * 16) = make_uint4(pack_bf16(w5[0], w5[1]), pack_bf16(w5[2], w5[3]), pack_bf16(w5[4], w5[5]), pack_bf16(w5[6], w5[7]));
            if (i < 130) {
                float w7[8], w9[8];
                #pragma unroll
                for (int e = 0; e < 8; e++) { w7[e] = w5[e] + (x[5 + e] + x[11 + e]); w9[e] = w7[e] + (x[4 + e] + x[12 + e]); }
                *(uint4*)(sB + S_W7 + c * W3LEN * 2 + i * 16) = make_uint4(pack_bf16(w7[0], w7[1]), pack_bf16(w7[2], w7[3]), pack_bf16(w7[4], w7[5]), pack_bf16(w7[6], w7[7]));
                *(uint4*)(sB + S_W9 + c * W3LEN * 2 + i * 16) = make_uint4(pack_bf16(w9[0], w9[1]), pack_bf16(w9[2], w9[3]), pack_bf16(w9[4], w9[5]), pack_bf16(w9[6], w9[7]));
            }
        }
        PROF(1);
        bar_sync(9, 608);
        PROF(6);
        {
            const int c = warp >> 2, grp = (warp + c) & 3;
            float acc[4][4];
            #pragma unroll
            for (int i = 0; i < 16; i++) (&acc[0][0])[i] = 0.0f;
            const uint32_t tabc = sBa + S_TAB + c * TABN * 2;
            const int e2 = (g - 2 * t) * 2;
            const uint32_t tD = tabc + ((g & 1) ? (TD1 + CD + 1) : (TD0 + CD)) * 2 - e2;
            const uint32_t tE = tabc + ((g & 1) ? (TE1 + CE + 1) : (TE0 + CE)) * 2 - e2;
            const uint32_t t2 = tabc + (T2B + ((g & 1) ? (T2C + C2 + 1) : C2)) * 2 - e2;
            const uint32_t t3 = tabc + (T3B + ((g & 1) ? (T3C + C3 + 1) : C3)) * 2 - e2;
            const int mi = lane >> 3, r8 = lane & 7;
            const uint32_t ub = sBa + S_U + c * ULEN * 2 + (PADU + 16 * (8 * (mi >> 1) + r8) + 8 * (mi & 1)) * 2 + (4 * grp - 4) * 256;
            #pragma unroll 1
            for (int rho = 0; rho < 8; rho++) {
                uint32_t R[5][3];
                #pragma unroll
                for (int qq = 0; qq < 5; qq++) {
                    if (qq < 4 || rho < 2) {
                        const uint32_t a = tD - 32 * (rho + 8 * qq);
                        R[qq][0] = lds32(a + 16); R[qq][1] = lds32(a); R[qq][2] = lds32(a - 16);
                    } else { R[qq][0] = 0; R[qq][1] = 0; R[qq][2] = 0; }
                }
                #pragma unroll
                for (int jp = 0; jp < 4; jp++) {
                    if (grp == 0 && (jp == 0 || (jp == 1 && rho > 0))) continue;
                    if (jp == 0 && rho >= 2) {
                        uint32_t b[4];
                        ldsm4(b, ub + jp * 512 - rho * 32);
                        mma_bf16(acc[0], R[3][1], R[3][2], R[3][0], R[3][1], b[2], b[3]);
                        continue;
                    }
                    uint32_t b[4];
                    ldsm4(b, ub + jp * 512 - rho * 32);
                    #pragma unroll
                    for (int hh = 0; hh < 2; hh++) {
                        #pragma unroll
                        for (int qq = 0; qq < 5; qq++) {
                            const int jr = 2 * jp + hh + qq - 4;
                            if (jr >= 0 && jr < 4) {
                                if (qq < 4 || rho < 2) mma_bf16(acc[jr], R[qq][1], R[qq][2], R[qq][0], R[qq][1], b[2 * hh], b[2 * hh + 1]);
                            }
                        }
                    }
                }
            }
            if (grp >= 2) {
                uint32_t R[5];
                #pragma unroll
                for (int i = 0; i < 5; i++) R[i] = lds32(tE - 16 * (127 + i));
                #pragma unroll
                for (int kk = 0; kk < 2; kk++) {
                    #pragma unroll
                    for (int jp = 0; jp < 2; jp++) {
                        uint32_t b[4];
                        ldsm4(b, ub + (4 + 2 * jp) * 256 - (64 + kk) * 32);
                        mma_bf16(acc[2 * jp], R[2 * kk + 1], R[2 * kk + 2], R[2 * kk], R[2 * kk + 1], b[0], b[1]);
                        mma_bf16(acc[2 * jp + 1], R[2 * kk + 1], R[2 * kk + 2], R[2 * kk], R[2 * kk + 1], b[2], b[3]);
                    }
                }
            }
            const uint32_t soff = (WPAD + 16 * (8 * (mi >> 1) + r8) + 8 * (mi & 1)) * 2 + grp * 1024;
            if (grp >= 1) {
                #pragma unroll 1
                for (int s = 0; s < 4; s++) {
                    const uint32_t sig = sBa + ((s & 1) ? S_W3 : S_W5) + c * W2LEN * 2 + soff - ((s == 0) ? 32 : (s == 1) ? 0 : 16);
                    uint32_t R[7];
                    #pragma unroll
                    for (int i = 0; i < 7; i++) R[i] = lds32(t2 + s * (T2S * 2) - 16 * (3 + i));
                    #pragma unroll
                    for (int bb = 1; bb <= 4; bb++) {
                        if (2 * grp - bb < 0) continue;
                        uint32_t a[4];
                        ldsm4t(a, sig - bb * 512);
                        #pragma unroll
                        for (int jj = 0; jj < 4; jj++) {
                            const int h = jj + 2 * bb;
                            if (h >= 4 && h <= 9) mma_bf16(acc[jj], a[0], a[1], a[2], a[3], R[h - 3], R[h - 4]);
                        }
                    }
                }
            }
            if (grp >= 2) {
                #pragma unroll 1
                for (int s = 0; s < 2; s++) {
                    const uint32_t sig = sBa + (s ? S_W7 : S_W9) + c * W3LEN * 2 + soff - (s ? 16 : 32);
                    uint32_t R[9];
                    #pragma unroll
                    for (int i = 0; i < 9; i++) R[i] = lds32(t3 + s * (T3S * 2) - 16 * (7 + i));
                    #pragma unroll
                    for (int bb = 3; bb <= 6; bb++) {
                        if (2 * grp - bb < 0) continue;
                        uint32_t a[4];
                        ldsm4t(a, sig - bb * 512);
                        #pragma unroll
                        for (int jj = 0; jj < 4; jj++) {
                            const int h = jj + 2 * bb;
                            if (h >= 8 && h <= 15) mma_bf16(acc[jj], a[0], a[1], a[2], a[3], R[h - 7], R[h - 8]);
                        }
                    }
                }
            }
            __nv_bfloat16* ys = (__nv_bfloat16*)(sB + S_Y + c * 4096);
            #pragma unroll
            for (int jj = 0; jj < 4; jj++) {
                const int A = 8 * (4 * grp + jj) + 2 * t;
                ys[16 * A + g] = __float2bfloat16_rn(acc[jj][0]);
                ys[16 * A + 16 + g] = __float2bfloat16_rn(acc[jj][1]);
                ys[16 * A + g + 8] = __float2bfloat16_rn(acc[jj][2]);
                ys[16 * A + 16 + g + 8] = __float2bfloat16_rn(acc[jj][3]);
            }
        }
        bar_arrive(10, 608);
        PROF(7);
        {
            mbar_wait(bars + 8 * B_ST, 0);
            PROF(9); PROFC(8);
            float qm = 0.0f;
            #pragma unroll
            for (int i = 0; i < 16; i++) qm = fmaxf(qm, s_misc[i]);
            const float vm = s_misc[17];
            const bool fast = (qm * s_misc[16] <= 60.0f * 60.0f) && (vm <= 1.0e12f) && (vm >= 1.0e-12f || vm == 0.0f);
            const uint64_t dVstep = 16ull - (16ull << 32);
            uint8_t* ob = g_oimg + qb * 131072 + hg * 16384 + nh * 8192 + (rowhalf * 8 + wiw * 2) * 128 + g * 16 + 4 * t;
            uint32_t cA = 0xBF00BF00u, cB = 0x00030003u;
            asm volatile("" : "+r"(cA), "+r"(cB));
            #pragma unroll 1
            for (int tile = 0; tile < 2; tile++) {
                uint64_t dK = make_desc(sb + SM_K, 128, 256, 0);
                uint64_t dV = make_desc(sb + SM_V, 128, 32768, 0);
                float o[12], s[32];
                uint32_t p[16], qq[4];
                #pragma unroll
                for (int i = 0; i < 4; i++) qq[i] = tile ? q[1][i] : q[0][i];
                #pragma unroll
                for (int i = 0; i < 12; i++) o[i] = 0.0f;
                #pragma unroll
                for (int i = 0; i < 32; i++) s[i] = 0.0f;
                fence_regs<12>(o);
                fence_regs<32>(s);
                if (fast) {
                    #pragma unroll 1
                    for (int c = 0; c < SEQ / 256; c++) {
                        mbar_wait(bars + 8 * (B_KV + c), 0);
                        wg_fence();
                        wg_qk(s, qq, dK);
                        wg_commit();
                        #pragma unroll
                        for (int u = 0; u < 4; u++) {
                            wg_wait<0>();
                            fence_regs<32>(s);
                            #pragma unroll
                            for (int i = 0; i < 16; i++) {
                                if ((MUFU_MASK >> i) & 1) p[i] = exp_mufu(s[2 * i], s[2 * i + 1]);
                                else p[i] = exp_sw(s[2 * i], s[2 * i + 1], cA, cB);
                            }
                            wg_fence();
                            if (u + 1 < 4) wg_qk(s, qq, dK + (u + 1) * 128);
                            #pragma unroll
                            for (int kk = 0; kk < 4; kk++) wg_pv(o, p + 4 * kk, dV + (u * 4 + kk) * dVstep);
                            wg_commit();
                        }
                        dK += 512;
                        dV += 16 * dVstep;
                    }
                    wg_wait<0>();
                } else {
                    float mx0 = -INFINITY, mx1 = -INFINITY;
                    #pragma unroll 1
                    for (int c = 0; c < SEQ / 64; c++) {
                        mbar_wait(bars + 8 * (B_KV + (c >> 2)), 0);
                        wg_fence();
                        wg_qk(s, qq, dK);
                        wg_commit();
                        wg_wait<0>();
                        fence_regs<32>(s);
                        fence_regs<12>(o);
                        float m0 = mx0, m1 = mx1;
                        #pragma unroll
                        for (int j = 0; j < 8; j++) {
                            m0 = fmaxf(m0, fmaxf(s[4 * j], s[4 * j + 1]));
                            m1 = fmaxf(m1, fmaxf(s[4 * j + 2], s[4 * j + 3]));
                        }
                        m0 = fmaxf(m0, __shfl_xor_sync(0xffffffffu, m0, 1)); m0 = fmaxf(m0, __shfl_xor_sync(0xffffffffu, m0, 2));
                        m1 = fmaxf(m1, __shfl_xor_sync(0xffffffffu, m1, 1)); m1 = fmaxf(m1, __shfl_xor_sync(0xffffffffu, m1, 2));
                        const float c0 = ex2f(mx0 - m0), c1 = ex2f(mx1 - m1);
                        mx0 = m0; mx1 = m1;
                        #pragma unroll
                        for (int j = 0; j < 3; j++) { o[4 * j] *= c0; o[4 * j + 1] *= c0; o[4 * j + 2] *= c1; o[4 * j + 3] *= c1; }
                        #pragma unroll
                        for (int j = 0; j < 8; j++) {
                            p[2 * j] = exp_mufu(s[4 * j] - m0, s[4 * j + 1] - m0);
                            p[2 * j + 1] = exp_mufu(s[4 * j + 2] - m1, s[4 * j + 3] - m1);
                        }
                        wg_fence();
                        #pragma unroll
                        for (int kk = 0; kk < 4; kk++) wg_pv(o, p + 4 * kk, dV + kk * dVstep);
                        wg_commit();
                        wg_wait<0>();
                        dK += 128;
                        dV += 4 * dVstep;
                    }
                }
                fence_regs<12>(o);
                const float i0 = 1.0f / o[4], i1 = 1.0f / o[6];
                uint8_t* b = ob + tile * 4096;
                *(uint32_t*)(b) = pack_bf16(o[0] * i0, o[1] * i0);
                *(uint32_t*)(b + 128) = pack_bf16(o[2] * i1, o[3] * i1);
                *(uint32_t*)(b + 2048) = pack_bf16(o[8] * i0, o[9] * i0);
                *(uint32_t*)(b + 2048 + 128) = pack_bf16(o[10] * i1, o[11] * i1);
            }
            __threadfence();
        }
        PROF(10); PROFC(9);
        bar_arrive(12, 544);

        {
            float acc[16];
            #pragma unroll
            for (int i = 0; i < 16; i++) acc[i] = 0.0f;
            fence_regs<16>(acc);
            const uint64_t dA = make_desc(sb + SM_A + rowhalf * 1024, 2048, 128, 0);
            const uint64_t dB = make_desc(sb + SM_B + nh * 64, 16, 1024, 1);
            mbar_wait(bars + 8 * B_WO, 0);
            #pragma unroll 1
            for (int i = 0; i < 8; i++) {
                const int src = (hg + i) & 7;
                mbar_wait(bars + 8 * (B_O + src), 0);
                wg_fence();
                #pragma unroll
                for (int kk = 0; kk < 4; kk++) wg_ss32(acc, dA + src * 1024 + kk * 256, dB + (src * 4 + kk) * 128);
                wg_commit();
            }
            wg_wait<0>();
            fence_regs<16>(acc);
            PROF(12);
            const int row = qb * 128 + rowhalf * 64 + wiw * 16 + g;
            uint32_t* o32 = (uint32_t*)(P.out + (size_t)row * 1024 + hg * 64 + nh * 32 + 2 * t);
            #pragma unroll
            for (int j = 0; j < 4; j++) {
                o32[4 * j] = pack_bf16(acc[4 * j], acc[4 * j + 1]);
                o32[4 * j + 8 * 512] = pack_bf16(acc[4 * j + 2], acc[4 * j + 3]);
            }
        }
        PROF(13);
    }
}

typedef CUresult (*EncodeFn)(CUtensorMap*, CUtensorMapDataType, cuuint32_t, void*, const cuuint64_t*, const cuuint64_t*,
                             const cuuint32_t*, const cuuint32_t*, CUtensorMapInterleave, CUtensorMapSwizzle,
                             CUtensorMapL2promotion, CUtensorMapFloatOOBfill);

void make_map(EncodeFn fn, CUtensorMap* m, const void* ptr, uint64_t inner, uint64_t outer, uint32_t box_in, uint32_t box_out, CUtensorMapSwizzle swz) {
    cuuint64_t dims[2] = {inner, outer};
    cuuint64_t strides[1] = {inner * 2};
    cuuint32_t box[2] = {box_in, box_out};
    cuuint32_t es[2] = {1, 1};
    fn(m, CU_TENSOR_MAP_DATA_TYPE_BFLOAT16, 2, const_cast<void*>(ptr), dims, strides, box, es, CU_TENSOR_MAP_INTERLEAVE_NONE, swz,
       CU_TENSOR_MAP_L2_PROMOTION_L2_128B, CU_TENSOR_MAP_FLOAT_OOB_FILL_NONE);
}

}

extern "C" void kernel_launch(void* const* d_in, const int* in_sizes, int n_in, void* d_out, int out_size) {
    (void)in_sizes; (void)n_in; (void)out_size;
    static EncodeFn fn = nullptr;
    if (!fn) {
        void* p = nullptr;
        cudaDriverEntryPointQueryResult qr;
        cudaGetDriverEntryPoint("cuTensorMapEncodeTiled", &p, cudaEnableDefault, &qr);
        fn = (EncodeFn)p;
        cudaFuncSetAttribute(fused_kernel, cudaFuncAttributeMaxDynamicSharedMemorySize, SM_ALLOC);
    }
    CUtensorMap tx, twq, two, twk, twv, tu;
    {
        cuuint64_t dims[3] = {64, 2048, 8};
        cuuint64_t strides[2] = {1024, 128};
        cuuint32_t box[3] = {64, 128, 4};
        cuuint32_t es[3] = {1, 1, 1};
        fn(&tx, CU_TENSOR_MAP_DATA_TYPE_BFLOAT16, 3, d_in[0], dims, strides, box, es, CU_TENSOR_MAP_INTERLEAVE_NONE, CU_TENSOR_MAP_SWIZZLE_128B,
           CU_TENSOR_MAP_L2_PROMOTION_L2_128B, CU_TENSOR_MAP_FLOAT_OOB_FILL_NONE);
    }
    make_map(fn, &tu, d_in[5], 512, 2048, 8, 256, CU_TENSOR_MAP_SWIZZLE_NONE);
    make_map(fn, &twq, d_in[1], 512, 512, 64, 256, CU_TENSOR_MAP_SWIZZLE_128B);
    make_map(fn, &twk, d_in[2], 16, 512, 8, 256, CU_TENSOR_MAP_SWIZZLE_NONE);
    make_map(fn, &twv, d_in[3], 16, 512, 8, 256, CU_TENSOR_MAP_SWIZZLE_NONE);
    make_map(fn, &two, d_in[4], 512, 512, 64, 256, CU_TENSOR_MAP_SWIZZLE_128B);
    Params P;
    P.u = (const __nv_bfloat16*)d_in[5];
    P.lar = (const __nv_bfloat16*)d_in[6];
    P.aim = (const __nv_bfloat16*)d_in[7];
    P.cre = (const __nv_bfloat16*)d_in[8];
    P.cim = (const __nv_bfloat16*)d_in[9];
    P.logdt = (const __nv_bfloat16*)d_in[10];
    P.dskip = (const __nv_bfloat16*)d_in[11];
    P.out = (__nv_bfloat16*)d_out;
    fused_kernel<<<NCTA, NTHR, SM_ALLOC>>>(tx, twq, two, twk, twv, tu, P);
}
```

```cpp
#include <cuda_runtime.h>
#include <cuda_bf16.h>
#include <cuda_fp16.h>
#include <cuda.h>
#include <stdint.h>

namespace {

constexpr int SEQ = 2048;
constexpr int NCTA = 128, NTHR = 640;

constexpr int SM_A = 0;
constexpr int SM_WQ = 131072;
constexpr int SM_WKV = SM_WQ + 65536;
constexpr int SM_K = 0, SM_V = 65536;
constexpr int SM_B = 132096;

constexpr int PADU = 288, ULEN = PADU + 2048;
constexpr int WPAD = 16, W2LEN = WPAD + 1536, W3LEN = WPAD + 1024;
constexpr int TABN = 2240;
constexpr int S_U = 0;
constexpr int S_W3 = S_U + 4 * ULEN * 2;
constexpr int S_W5 = S_W3 + 4 * W2LEN * 2;
constexpr int S_W7 = S_W5 + 4 * W2LEN * 2;
constexpr int S_W9 = S_W7 + 4 * W3LEN * 2;
constexpr int S_TAB = S_W9 + 4 * W3LEN * 2;
constexpr int S_KC = 214016 - SM_B;
constexpr int S_Y = S_KC;
constexpr int SM_BAR = SM_B + S_KC + 16384;
constexpr int SM_TOTAL = SM_BAR + 1024;
constexpr int SM_ALLOC = SM_TOTAL + 1024;
static_assert(SM_V + 65536 + 256 <= SM_B && SM_ALLOC <= 232448 && S_TAB + 4 * TABN * 2 <= S_KC && SM_WKV + 16384 <= SM_B + S_KC, "smem map");

constexpr int TD0 = 0, TD1 = 560, CD = 544;
constexpr int TE0 = 1120, TE1 = 1168, CE = 1056;
constexpr int T2B = 1216, T2S = 160, T2C = 80, C2 = 80;
constexpr int T3B = 1856, T3S = 192, T3C = 96, C3 = 144;

constexpr int rne8(int t) {
    if (t < 256) return t;
    int sh = 0;
    while ((t >> sh) >= 256) sh++;
    int q = t >> sh, rem = t & ((1 << sh) - 1), half = 1 << (sh - 1);
    if (rem > half || (rem == half && (q & 1))) q++;
    return q << sh;
}
constexpr int kcidx(int p) {
    if (p < 256) return (p >> 3) * 24 + (p & 7);
    if (p < 512) return ((p - 256) >> 3) * 24 + 8 + (((p - 256) & 7) >> 1);
    if (p < 1024) { int q = p - 512, hi = q >> 8, rem = q & 255; return (rem >> 3) * 24 + 12 + 2 * hi + ((rem & 7) >> 2); }
    if (p < 2048) { int q = p - 1024; return ((q & 255) >> 3) * 24 + 16 + (q >> 8); }
    return 20;
}
constexpr int KC_ZERO = 23;
constexpr int tab_dense(int t) { return (t >= 0 && t <= 514) ? kcidx(rne8(t)) : KC_ZERO; }
constexpr int tab_extra(int t) { return (t >= 1027 && t <= 1028) ? kcidx(1024) : KC_ZERO; }
constexpr int tab_2(int s, int lag) { return (lag >= 32 && lag <= 63) ? kcidx(s == 0 ? 16 * (lag + 1) : 16 * lag + 4 * s) : KC_ZERO; }
constexpr int tab_3(int s, int lag) { return (lag >= 64 && lag <= 127) ? kcidx(s == 0 ? 16 * (lag + 1) : 16 * lag + 8) : KC_ZERO; }
struct TabMap {
    uint16_t v[TABN];
    constexpr TabMap() : v{} {
        for (int i = 0; i < 560; i++) { v[TD0 + i] = tab_dense(CD - i); v[TD1 + i] = tab_dense(CD + 1 - i); }
        for (int i = 0; i < 48; i++) { v[TE0 + i] = tab_extra(CE - i); v[TE1 + i] = tab_extra(CE + 1 - i); }
        for (int s = 0; s < 4; s++)
            for (int i = 0; i < T2C; i++) { v[T2B + s * T2S + i] = tab_2(s, C2 - i); v[T2B + s * T2S + T2C + i] = tab_2(s, C2 + 1 - i); }
        for (int s = 0; s < 2; s++)
            for (int i = 0; i < T3C; i++) { v[T3B + s * T3S + i] = tab_3(s, C3 - i); v[T3B + s * T3S + T3C + i] = tab_3(s, C3 + 1 - i); }
    }
};
__device__ const __align__(16) TabMap g_tabmap = TabMap();

__device__ __align__(1024) uint8_t g_kimg[65536];
__device__ __align__(1024) uint8_t g_vimg[65536 + 256];
__device__ __align__(1024) uint8_t g_oimg[16 * 131072];
__device__ unsigned long long g_flag_kv[64];
__device__ unsigned g_flag_o[128];
__device__ unsigned g_epoch;
__device__ unsigned g_done;

#define PROF(i) do {} while (0)
#define PROF2(i) do {} while (0)
#define PROFC(i) do {} while (0)
#define PROF3(i) do {} while (0)

__device__ __forceinline__ uint32_t smem_u32(const void* p) { return (uint32_t)__cvta_generic_to_shared(p); }
__device__ __forceinline__ void mbar_init(uint32_t bar, uint32_t cnt) { asm volatile("mbarrier.init.shared::cta.b64 [%0], %1;" :: "r"(bar), "r"(cnt) : "memory"); }
__device__ __forceinline__ void mbar_expect_tx(uint32_t bar, uint32_t bytes) {
    asm volatile("mbarrier.arrive.expect_tx.shared::cta.b64 _, [%0], %1;" :: "r"(bar), "r"(bytes) : "memory"); }
__device__ __forceinline__ void mbar_wait(uint32_t bar, uint32_t parity) {
    uint32_t ok = 0;
    for (int it = 0; it < (1 << 22) && !ok; it++) {
        asm volatile("{ .reg .pred p; mbarrier.try_wait.parity.shared::cta.b64 p, [%1], %2; selp.u32 %0, 1, 0, p; }"
                     : "=r"(ok) : "r"(bar), "r"(parity) : "memory");
    }
}
__device__ __forceinline__ void tma_2d(uint32_t dst, const CUtensorMap* map, int c0, int c1, uint32_t bar) {
    asm volatile("cp.async.bulk.tensor.2d.shared::cluster.global.mbarrier::complete_tx::bytes [%0], [%1, {%3, %4}], [%2];"
                 :: "r"(dst), "l"((uint64_t)map), "r"(bar), "r"(c0), "r"(c1) : "memory");
}
__device__ __forceinline__ void tma_2d_mc(uint32_t dst, const CUtensorMap* map, int c0, int c1, uint32_t bar) {
    asm volatile("cp.async.bulk.tensor.2d.shared::cluster.global.mbarrier::complete_tx::bytes.multicast::cluster [%0], [%1, {%3, %4}], [%2], %5;"
                 :: "r"(dst), "l"((uint64_t)map), "r"(bar), "r"(c0), "r"(c1), "h"((uint16_t)3) : "memory");
}
__device__ __forceinline__ void bulk_g2s_mc(uint32_t dst, const void* src, uint32_t bytes, uint32_t bar) {
    asm volatile("cp.async.bulk.shared::cluster.global.mbarrier::complete_tx::bytes.multicast::cluster [%0], [%1], %2, [%3], %4;"
                 :: "r"(dst), "l"((uint64_t)src), "r"(bytes), "r"(bar), "h"((uint16_t)3) : "memory");
}
__device__ __forceinline__ void pair_sync(uint32_t bar, uint32_t peer) {
    uint32_t ra;
    asm volatile("mapa.shared::cluster.u32 %0, %1, %2;" : "=r"(ra) : "r"(bar), "r"(peer));
    asm volatile("mbarrier.arrive.shared::cluster.b64 _, [%0];" :: "r"(ra) : "memory");
    asm volatile("mbarrier.arrive.shared::cta.b64 _, [%0];" :: "r"(bar) : "memory");
    uint32_t ok = 0;
    for (int it = 0; it < (1 << 22) && !ok; it++) {
        asm volatile("{ .reg .pred p; mbarrier.try_wait.parity.shared::cta.b64 p, [%1], 0; selp.u32 %0, 1, 0, p; }"
                     : "=r"(ok) : "r"(bar) : "memory");
    }
}
__device__ __forceinline__ void fence_async_all() { asm volatile("fence.proxy.async.global;" ::: "memory"); }
__device__ __forceinline__ void fence_async_smem() { asm volatile("fence.proxy.async.shared::cta;" ::: "memory"); }
__device__ __forceinline__ unsigned ld_acquire(const unsigned* p) {
    unsigned v; asm volatile("ld.acquire.gpu.global.u32 %0, [%1];" : "=r"(v) : "l"(p) : "memory"); return v; }
__device__ __forceinline__ void st_release(unsigned* p, unsigned v) { asm volatile("st.release.gpu.global.u32 [%0], %1;" :: "l"(p), "r"(v) : "memory"); }
__device__ __forceinline__ void wait_flag(const unsigned* p, unsigned epoch) {
    for (int it = 0; it < (1 << 22); it++) { if (ld_acquire(p) == epoch) break; }
}
__device__ __forceinline__ unsigned long long ld_acquire64(const unsigned long long* p) {
    unsigned long long v; asm volatile("ld.acquire.gpu.global.u64 %0, [%1];" : "=l"(v) : "l"(p) : "memory"); return v; }
__device__ __forceinline__ void st_release64(unsigned long long* p, unsigned long long v) { asm volatile("st.release.gpu.global.u64 [%0], %1;" :: "l"(p), "l"(v) : "memory"); }
__device__ __forceinline__ float wait_flag64(const unsigned long long* p, unsigned epoch) {
    unsigned long long v = 0;
    for (int it = 0; it < (1 << 22); it++) { v = ld_acquire64(p); if ((unsigned)(v >> 32) == epoch) break; }
    return __uint_as_float((unsigned)v);
}
__device__ __forceinline__ void tma_3d_mc(uint32_t dst, const CUtensorMap* map, int c0, int c1, int c2, uint32_t bar) {
    asm volatile("cp.async.bulk.tensor.3d.shared::cluster.global.mbarrier::complete_tx::bytes.multicast::cluster [%0], [%1, {%3, %4, %5}], [%2], %6;"
                 :: "r"(dst), "l"((uint64_t)map), "r"(bar), "r"(c0), "r"(c1), "r"(c2), "h"((uint16_t)3) : "memory");
}
__device__ __forceinline__ void bar_sync(int id, int n) { asm volatile("bar.sync %0, %1;" :: "r"(id), "r"(n) : "memory"); }
__device__ __forceinline__ void bar_arrive(int id, int n) { asm volatile("bar.arrive %0, %1;" :: "r"(id), "r"(n) : "memory"); }
__device__ __forceinline__ void mbar_arrive(uint32_t bar) { asm volatile("mbarrier.arrive.shared::cta.b64 _, [%0];" :: "r"(bar) : "memory"); }

__device__ __forceinline__ uint64_t make_desc(uint32_t saddr, uint32_t lbo, uint32_t sbo, uint32_t swz) {
    uint64_t d = 0;
    d |= (uint64_t)((saddr & 0x3FFFF) >> 4);
    d |= (uint64_t)((lbo >> 4) & 0x3FFF) << 16;
    d |= (uint64_t)((sbo >> 4) & 0x3FFF) << 32;
    d |= (uint64_t)swz << 62;
    return d;
}
__device__ __forceinline__ void wg_fence() { asm volatile("wgmma.fence.sync.aligned;" ::: "memory"); }
__device__ __forceinline__ void wg_commit() { asm volatile("wgmma.commit_group.sync.aligned;" ::: "memory"); }
template<int N> __device__ __forceinline__ void wg_wait() { asm volatile("wgmma.wait_group.sync.aligned %0;" :: "n"(N) : "memory"); }
#define A4(d, o) "+f"(d[o + 0]), "+f"(d[o + 1]), "+f"(d[o + 2]), "+f"(d[o + 3])
#define A16(d, o) A4(d, o), A4(d, o + 4), A4(d, o + 8), A4(d, o + 12)

__device__ __forceinline__ void wg_pv(float* d, const uint32_t* a, uint64_t desc) {
    asm volatile("wgmma.mma_async.sync.aligned.m64n24k16.f32.bf16.bf16 {%0,%1,%2,%3,%4,%5,%6,%7,%8,%9,%10,%11}, {%12,%13,%14,%15}, %16, 1, 1, 1, 1;"
                 : A4(d, 0), A4(d, 4), A4(d, 8) : "r"(a[0]), "r"(a[1]), "r"(a[2]), "r"(a[3]), "l"(desc));
}
__device__ __forceinline__ void wg_qk(float* d, const uint32_t* a, uint64_t desc) {
    asm volatile("wgmma.mma_async.sync.aligned.m64n64k16.f32.bf16.bf16 {%0,%1,%2,%3,%4,%5,%6,%7,%8,%9,%10,%11,%12,%13,%14,%15,%16,%17,%18,%19,%20,%21,%22,%23,%24,%25,%26,%27,%28,%29,%30,%31}, {%32,%33,%34,%35}, %36, 0, 1, 1, 0;"
                 : A16(d, 0), A16(d, 16) : "r"(a[0]), "r"(a[1]), "r"(a[2]), "r"(a[3]), "l"(desc));
}
__device__ __forceinline__ void wg_ss32(float* d, uint64_t da, uint64_t db) {
    asm volatile("wgmma.mma_async.sync.aligned.m64n32k16.f32.bf16.bf16 {%0,%1,%2,%3,%4,%5,%6,%7,%8,%9,%10,%11,%12,%13,%14,%15}, %16, %17, 1, 1, 1, 0, 1;"
                 : A16(d, 0) : "l"(da), "l"(db));
}
__device__ __forceinline__ void wg_ss16(float* d, uint64_t da, uint64_t db) {
    asm volatile("wgmma.mma_async.sync.aligned.m64n16k16.f32.bf16.bf16 {%0,%1,%2,%3,%4,%5,%6,%7}, %8, %9, 1, 1, 1, 0, 1;"
                 : A4(d, 0), A4(d, 4) : "l"(da), "l"(db));
}
template<int N> __device__ __forceinline__ void fence_regs(float* r) {
    #pragma unroll
    for (int i = 0; i < N; i++) asm volatile("" : "+f"(r[i]) :: "memory");
}
__device__ __forceinline__ void mma_bf16(float* d, uint32_t a0, uint32_t a1, uint32_t a2, uint32_t a3, uint32_t b0, uint32_t b1) {
    asm volatile("mma.sync.aligned.m16n8k16.row.col.f32.bf16.bf16.f32 {%0,%1,%2,%3}, {%4,%5,%6,%7}, {%8,%9}, {%0,%1,%2,%3};"
                 : "+f"(d[0]), "+f"(d[1]), "+f"(d[2]), "+f"(d[3]) : "r"(a0), "r"(a1), "r"(a2), "r"(a3), "r"(b0), "r"(b1));
}
__device__ __forceinline__ void mma_f16(float* d, const uint32_t* a, uint32_t b0, uint32_t b1) {
    asm volatile("mma.sync.aligned.m16n8k16.row.col.f32.f16.f16.f32 {%0,%1,%2,%3}, {%4,%5,%6,%7}, {%8,%9}, {%0,%1,%2,%3};"
                 : "+f"(d[0]), "+f"(d[1]), "+f"(d[2]), "+f"(d[3]) : "r"(a[0]), "r"(a[1]), "r"(a[2]), "r"(a[3]), "r"(b0), "r"(b1));
}
__device__ __forceinline__ void ldsm4(uint32_t* r, uint32_t addr) {
    asm volatile("ldmatrix.sync.aligned.m8n8.x4.shared.b16 {%0,%1,%2,%3}, [%4];" : "=r"(r[0]), "=r"(r[1]), "=r"(r[2]), "=r"(r[3]) : "r"(addr) : "memory");
}
__device__ __forceinline__ void ldsm4t(uint32_t* r, uint32_t addr) {
    asm volatile("ldmatrix.sync.aligned.m8n8.x4.trans.shared.b16 {%0,%1,%2,%3}, [%4];" : "=r"(r[0]), "=r"(r[1]), "=r"(r[2]), "=r"(r[3]) : "r"(addr) : "memory");
}
__device__ __forceinline__ uint32_t lds32(uint32_t addr) { uint32_t v; asm volatile("ld.shared.u32 %0, [%1];" : "=r"(v) : "r"(addr) : "memory"); return v; }
__device__ __forceinline__ float ex2f(float x) { float r; asm("ex2.approx.ftz.f32 %0, %1;" : "=f"(r) : "f"(x)); return r; }
__device__ __forceinline__ uint32_t pack_bf16(float lo, float hi) { uint32_t r; asm("cvt.rn.bf16x2.f32 %0, %1, %2;" : "=r"(r) : "f"(hi), "f"(lo)); return r; }
__device__ __forceinline__ uint32_t pack_f16(float lo, float hi) { uint32_t r; asm("cvt.rn.f16x2.f32 %0, %1, %2;" : "=r"(r) : "f"(hi), "f"(lo)); return r; }
__device__ __forceinline__ float bf_lo(uint32_t v) { return __uint_as_float(v << 16); }
__device__ __forceinline__ float bf_hi(uint32_t v) { return __uint_as_float(v & 0xFFFF0000u); }
__device__ __forceinline__ float bf_round(float x) { return __bfloat162float(__float2bfloat16_rn(x)); }

__device__ __forceinline__ uint32_t exp_mufu(float x0, float x1) { return pack_bf16(ex2f(x0), ex2f(x1)); }
#define SW_MAGIC (256.0f + 127.0f - 0.598938f)
__device__ __forceinline__ uint32_t exp_sw(float x0, float x1, uint32_t cA, uint32_t cB) {
    float t0 = x0 + SW_MAGIC, t1 = x1 + SW_MAGIC;
    uint32_t L, mh, ec, r;
    asm("prmt.b32 %0, %1, %2, 0x6521;" : "=r"(L) : "r"(__float_as_uint(t0)), "r"(__float_as_uint(t1)));
    asm("lop3.b32 %0, %1, 0x007F007F, %2, 0xEA;" : "=r"(mh) : "r"(L), "r"(cA));
    asm("lop3.b32 %0, %1, 0x7F807F80, %2, 0xEA;" : "=r"(ec) : "r"(L), "r"(cB));
    asm("fma.rn.bf16x2 %0, %1, %2, %3;" : "=r"(r) : "r"(L), "r"(mh), "r"(ec));
    return r;
}
constexpr uint32_t MUFU_MASK = 0x4949;

struct cf { float x, y; };
__device__ __forceinline__ cf cmul(cf a, cf b) { cf r; r.x = a.x * b.x - a.y * b.y; r.y = a.x * b.y + a.y * b.x; return r; }
__device__ __forceinline__ cf cexp_p(float a2, float b, float p) {
    float e = ex2f(a2 * p);
    float ph = b * p;
    ph -= (ph + 12582912.0f) - 12582912.0f;
    float ang = ph * 6.283185307f;
    cf r; r.x = e * __cosf(ang); r.y = e * __sinf(ang);
    return r;
}
__device__ __forceinline__ uint32_t h2_cmul(uint32_t w, uint32_t wsw, uint32_t e) {
    __half2 hw = *(__half2*)&w, hs = *(__half2*)&wsw, he = *(__half2*)&e;
    __half2 r = __hfma2(hs, __high2half2(he), __hmul2(hw, __low2half2(he)));
    return *(uint32_t*)&r;
}

template<bool B> struct BoolC { static constexpr bool value = B; };
struct Params {
    const __nv_bfloat16 *u, *lar, *aim, *cre, *cim, *logdt, *dskip;
    __nv_bfloat16* out;
};

constexpr int B_O = 0, B_KV = 8, B_X = 16, B_WO = 18, B_U = 19, B_ST = 20, B_H = 21, NBAR = 23;

__device__ __forceinline__ void helper_role(const Params& P, uint8_t* sp) {
    const int tid = threadIdx.x - 544;
    const int d0 = blockIdx.x * 4;
    uint8_t* sB = sp + SM_B;
    const uint2 dsk = __ldg((const uint2*)(P.dskip + d0));
    {
        const uint32_t* map = (const uint32_t*)g_tabmap.v;
        uint32_t mp[12];
        #pragma unroll
        for (int i = 0; i < 12; i++) { const int w = tid + 96 * i; mp[i] = (w < TABN / 2) ? __ldg(map + w) : 0u; }
        bar_sync(8, 640);
        #pragma unroll 1
        for (int cc = 0; cc < 4; cc++) {
            const float* kc = (const float*)(sB + S_KC + cc * 4096);
            uint32_t* tab = (uint32_t*)(sB + S_TAB + cc * TABN * 2);
            #pragma unroll
            for (int i = 0; i < 12; i++) { const int w = tid + 96 * i; if (w < TABN / 2) tab[w] = pack_bf16(kc[mp[i] & 0xFFFF], kc[mp[i] >> 16]); }
        }
    }
    bar_arrive(9, 608);
    PROF2(2);
    bar_sync(10, 608);
    {
        uint32_t dd[4] = {__byte_perm(dsk.x, 0, 0x1010), __byte_perm(dsk.x, 0, 0x3232), __byte_perm(dsk.y, 0, 0x1010), __byte_perm(dsk.y, 0, 0x3232)};
        #pragma unroll 2
        for (int pi = tid; pi < 1024; pi += 96) {
            const int l = 2 * pi;
            uint32_t r[4];
            #pragma unroll
            for (int cc = 0; cc < 4; cc++) {
                const uint32_t y2 = *(const uint32_t*)(sB + S_Y + cc * 4096 + l * 2);
                const uint32_t u2 = *(const uint32_t*)(sB + S_U + cc * ULEN * 2 + (PADU + l) * 2);
                __nv_bfloat162 pr = __hmul2(*(const __nv_bfloat162*)&u2, *(const __nv_bfloat162*)&dd[cc]);
                __nv_bfloat162 sm = __hadd2(*(const __nv_bfloat162*)&y2, pr);
                r[cc] = *(uint32_t*)&sm;
            }
            *(uint2*)(P.out + (size_t)l * 1024 + 512 + d0) = make_uint2(__byte_perm(r[0], r[1], 0x5410), __byte_perm(r[2], r[3], 0x5410));
            *(uint2*)(P.out + (size_t)(l + 1) * 1024 + 512 + d0) = make_uint2(__byte_perm(r[0], r[1], 0x7632), __byte_perm(r[2], r[3], 0x7632));
        }
    }
    bar_arrive(11, 128);
    PROF2(4);
}

__global__ void __cluster_dims__(2, 1, 1) __launch_bounds__(NTHR, 1)
fused_kernel(const __grid_constant__ CUtensorMap tm_x, const __grid_constant__ CUtensorMap tm_wq,
             const __grid_constant__ CUtensorMap tm_wo, const __grid_constant__ CUtensorMap tm_wk,
             const __grid_constant__ CUtensorMap tm_wv, const __grid_constant__ CUtensorMap tm_u, const Params P) {
    extern __shared__ uint8_t smem_raw[];
    const uint32_t sb = (smem_u32(smem_raw) + 1023u) & ~1023u;
    uint8_t* sp = smem_raw + (sb - smem_u32(smem_raw));

    const int tid = threadIdx.x, warp = tid >> 5, lane = tid & 31, wg = tid >> 7, wiw = warp & 3;
    const int g = lane >> 2, t = lane & 3;
    const int qb = blockIdx.x >> 3, hg = blockIdx.x & 7;
    const uint32_t rank = blockIdx.x & 1;
    const int rowhalf = wg & 1, nh = wg >> 1;
    const bool kv_cta = hg < 4;
    const int kv_sel = hg >> 1;
    const bool kv_wg = kv_cta && (wg == (hg & 1));

    const uint32_t bars = sb + SM_BAR;
    float* s_misc = (float*)(sp + SM_BAR + 256);
    const CUtensorMap* tm_kv = kv_sel ? &tm_wv : &tm_wk;

    PROF(0);
    unsigned short p_lar = 0, p_aim = 0, p_cre = 0, p_cim = 0, p_ldt = 0;
    if (wg < 4) {
        const int n = (blockIdx.x * 4 + wg) * 128 + (tid & 127);
        p_lar = __ldg((const unsigned short*)P.lar + n);
        p_aim = __ldg((const unsigned short*)P.aim + n);
        p_cre = __ldg((const unsigned short*)P.cre + n);
        p_cim = __ldg((const unsigned short*)P.cim + n);
        p_ldt = __ldg((const unsigned short*)P.logdt + blockIdx.x * 4 + wg);
    } else if (warp == 16) {
        PROF3(5);
        const CUtensorMap* m = lane == 0 ? &tm_x : lane == 1 ? &tm_wq : lane == 2 ? tm_kv : lane == 3 ? &tm_u : &tm_wo;
        if (lane < 5) asm volatile("prefetch.tensormap [%0];" :: "l"((uint64_t)m) : "memory");
        if (lane < NBAR) {
            const uint32_t bar = bars + 8 * lane;
            mbar_init(bar, lane >= B_H ? 2 : 1);
            asm volatile("fence.mbarrier_init.release.cluster;" ::: "memory");
            fence_async_smem();
            const uint32_t bytes = lane < B_X ? 16384u : lane < B_WO ? (98304u + (kv_cta ? 8192u : 0u)) : lane == B_WO ? 65536u : 32768u;
            if (lane <= B_U) mbar_expect_tx(bar, bytes);
        }
        __syncwarp();
        PROF3(6);
        if (lane < 2) tma_2d(sb + SM_WQ + lane * 32768, &tm_wq, hg * 64, lane * 256, bars + 8 * (B_X + lane));
        else if (lane < 6 && kv_cta) tma_2d(sb + SM_WKV + (lane - 2) * 4096, tm_kv, ((lane - 2) >> 1) * 8, (lane & 1) * 256, bars + 8 * (B_X + (lane & 1)));
    }
    PROF3(7);
    PROF(11);
    asm volatile("barrier.cluster.arrive.relaxed.aligned;" ::: "memory");
    const unsigned epoch = *(volatile unsigned*)&g_epoch + 1u;
    asm volatile("barrier.cluster.wait.aligned;" ::: "memory");
    PROF(5);

    if (warp == 16) {
        if (lane == 0) tma_3d_mc(sb + SM_A + rank * 65536, &tm_x, 0, qb * 128, rank * 4, bars + 8 * (B_X + rank));
        PROF3(10);
        bar_sync(8, 640);
        if (lane == 0) pair_sync(bars + 8 * B_H, rank ^ 1);
        __syncwarp();
        if (lane < 4) tma_2d_mc(sb + SM_B + S_W3 + (rank * 4 + lane) * 4096, &tm_u, (blockIdx.x >> 1) * 8, (rank * 4 + lane) * 256, bars + 8 * B_U);
        PROF3(11);
        *(uint2*)(sp + SM_V + 32768 + lane * 8) = make_uint2(0x3F803F80u, 0x3F803F80u);
        fence_async_smem();
        float km = wait_flag64(&g_flag_kv[2 * lane], epoch);
        float vm = wait_flag64(&g_flag_kv[2 * lane + 1], epoch);
        __syncwarp();
        PROF3(12);
        if (lane < 8) {
            fence_async_all();
            const uint32_t bar = bars + 8 * (B_KV + lane);
            if (rank == 0) bulk_g2s_mc(sb + SM_K + lane * 8192, g_kimg + lane * 8192, 8192, bar);
            else {
                bulk_g2s_mc(sb + SM_V + lane * 4096, g_vimg + lane * 4096, 4096, bar);
                bulk_g2s_mc(sb + SM_V + 33024 + (7 - lane) * 4096, g_vimg + 33024 + (7 - lane) * 4096, 4096, bar);
            }
        }
        #pragma unroll
        for (int o = 16; o; o >>= 1) { km = fmaxf(km, __shfl_xor_sync(0xffffffffu, km, o)); vm = fmaxf(vm, __shfl_xor_sync(0xffffffffu, vm, o)); }
        if (lane == 0) { s_misc[16] = km; s_misc[17] = vm; mbar_arrive(bars + 8 * B_ST); }
        PROF3(13);
        bar_sync(11, 128);
        if (lane < 2) { fence_async_smem(); tma_2d(sb + SM_B + lane * 32768, &tm_wo, hg * 64, lane * 256, bars + 8 * B_WO); }
        bar_sync(12, 544);
        if (lane == 0) {
            st_release(&g_flag_o[blockIdx.x], epoch);
            pair_sync(bars + 8 * (B_H + 1), rank ^ 1);
        }
        __syncwarp();
        PROF3(14);
        if (lane < 4) {
            const int src = 2 * lane + rank;
            wait_flag(&g_flag_o[qb * 8 + src], epoch);
            fence_async_all();
            bulk_g2s_mc(sb + SM_A + src * 16384, g_oimg + qb * 131072 + src * 16384, 16384, bars + 8 * (B_O + src));
        }
        __syncwarp();
        PROF3(15);
        if (lane == 0) {
            const unsigned prev = atomicAdd(&g_done, 1u);
            if (prev == NCTA - 1) {
                g_done = 0;
                __threadfence();
                *(volatile unsigned*)&g_epoch = epoch;
            }
        }
    } else if (wg == 4) {
        helper_role(P, sp);
    } else {
        uint8_t* sB = sp + SM_B;
        const uint32_t sBa = sb + SM_B;
        {
            const int c = wg;
            const float dt = bf_round(expf(bf_lo(p_ldt)));
            const float are = -bf_round(expf(bf_lo(p_lar))) * dt;
            const float aim = bf_lo(p_aim) * dt;
            float cr = 2.0f * (bf_lo(p_cre) * dt);
            float ci = 2.0f * (bf_lo(p_cim) * dt);
            const float a2 = are * 1.4426950408889634f, bb = aim * 0.15915494309189535f;
            float m = fmaxf(fabsf(cr), fabsf(ci));
            #pragma unroll
            for (int o = 16; o; o >>= 1) m = fmaxf(m, __shfl_xor_sync(0xffffffffu, m, o));
            int ebits = (__float_as_uint(m) >> 23) & 0xFF;
            ebits = min(max(ebits, 2), 250);
            const float scale = __uint_as_float((uint32_t)(ebits + 1) << 23);
            const float iscale = __uint_as_float((uint32_t)(253 - ebits) << 23);
            cf cc; cc.x = cr * iscale; cc.y = ci * iscale;

            const uint32_t stg = sBa + S_KC + warp * 1024;
            uint4* stp = (uint4*)(sB + S_KC + warp * 1024 + lane * 32);
            const uint32_t fa = stg + t * 32 + g * 4;

            uint32_t af[4][2][4];
            cf E256;
            {
                const cf E8 = cexp_p(a2, bb, 8.0f);
                uint32_t w[8];
                cf cur; cur.x = 1.0f; cur.y = 0.0f;
                w[0] = pack_f16(1.0f, 0.0f);
                cur = E8; w[1] = pack_f16(cur.x, cur.y);
                #pragma unroll
                for (int i = 2; i < 8; i++) { cur = cmul(cur, E8); w[i] = pack_f16(cur.x, cur.y); }
                stp[0] = make_uint4(w[0], w[1], w[2], w[3]);
                stp[1] = make_uint4(w[4], w[5], w[6], w[7]);
                const cf E64 = cexp_p(a2, bb, 64.0f);
                const cf E128 = cmul(E64, E64), E192 = cmul(E128, E64);
                E256 = cexp_p(a2, bb, 256.0f);
                const uint32_t e1 = pack_f16(E64.x, E64.y), e2 = pack_f16(E128.x, E128.y), e3 = pack_f16(E192.x, E192.y);
                __syncwarp();
                #pragma unroll
                for (int s = 0; s < 4; s++) {
                    #pragma unroll
                    for (int hh = 0; hh < 2; hh++) {
                        const uint32_t w0 = lds32(fa + s * 256 + hh * 128);
                        const uint32_t wsw = __byte_perm(w0, 0, 0x1032) ^ 0x00008000u;
                        const int src = 8 * s + t + 4 * hh;
                        const uint32_t f1 = __shfl_sync(0xffffffffu, e1, src), f2 = __shfl_sync(0xffffffffu, e2, src), f3 = __shfl_sync(0xffffffffu, e3, src);
                        af[s][0][2 * hh] = w0;
                        af[s][0][2 * hh + 1] = h2_cmul(w0, wsw, f1);
                        af[s][1][2 * hh] = h2_cmul(w0, wsw, f2);
                        af[s][1][2 * hh + 1] = h2_cmul(w0, wsw, f3);
                    }
                }
                __syncwarp();
            }
            float acc[2][3][4];
            #pragma unroll
            for (int i = 0; i < 24; i++) (&acc[0][0][0])[i] = 0.0f;
            const cf E1 = cexp_p(a2, bb, 1.0f);
            const cf E2 = cmul(E1, E1), E4 = cmul(E2, E2);
            cf X512;
            #pragma unroll
            for (int nt = 0; nt < 3; nt++) {
                uint32_t xv[8];
                if (nt == 0) {
                    cf cur = cc;
                    xv[0] = pack_f16(cur.x, -cur.y);
                    #pragma unroll
                    for (int i = 1; i < 8; i++) { cur = cmul(cur, E1); xv[i] = pack_f16(cur.x, -cur.y); }
                } else if (nt == 1) {
                    cf cur = cmul(cc, E256);
                    X512 = cmul(cur, E256);
                    xv[0] = pack_f16(cur.x, -cur.y);
                    #pragma unroll
                    for (int i = 1; i < 4; i++) { cur = cmul(cur, E2); xv[i] = pack_f16(cur.x, -cur.y); }
                    cur = cmul(X512, E4);
                    xv[4] = pack_f16(X512.x, -X512.y); xv[5] = pack_f16(cur.x, -cur.y);
                    X512 = cmul(X512, E256);
                    cur = cmul(X512, E4);
                    xv[6] = pack_f16(X512.x, -X512.y); xv[7] = pack_f16(cur.x, -cur.y);
                } else {
                    cf cur = X512;
                    #pragma unroll
                    for (int i = 0; i < 5; i++) { cur = cmul(cur, E256); xv[i] = pack_f16(cur.x, -cur.y); }
                    xv[5] = 0; xv[6] = 0; xv[7] = 0;
                }
                stp[0] = make_uint4(xv[0], xv[1], xv[2], xv[3]);
                stp[1] = make_uint4(xv[4], xv[5], xv[6], xv[7]);
                __syncwarp();
                #pragma unroll
                for (int s = 0; s < 4; s++) {
                    const uint32_t b0 = lds32(fa + s * 256), b1 = lds32(fa + s * 256 + 128);
                    mma_f16(acc[0][nt], af[s][0], b0, b1);
                    mma_f16(acc[1][nt], af[s][1], b0, b1);
                }
                __syncwarp();
            }
            float* kc = (float*)(sB + S_KC + c * 4096);
            bar_sync(4 + c, 128);
            #pragma unroll 1
            for (int step = 0; step < 4; step++) {
                if ((warp & 3) == step) {
                    #pragma unroll
                    for (int mt = 0; mt < 2; mt++)
                        #pragma unroll
                        for (int nt = 0; nt < 3; nt++)
                            #pragma unroll
                            for (int hh = 0; hh < 2; hh++) {
                                float2* p = (float2*)(kc + (mt * 16 + hh * 8 + g) * 24 + nt * 8 + 2 * t);
                                float2 v = make_float2(acc[mt][nt][2 * hh] * scale, acc[mt][nt][2 * hh + 1] * scale);
                                if (step) { float2 o = *p; v.x += o.x; v.y += o.y; }
                                *p = v;
                            }
                }
                if (step < 3) bar_sync(4 + c, 128);
            }
        }

        PROF(4);
        uint32_t q[2][4];
        {
            float acc[16], akv[8];
            #pragma unroll
            for (int i = 0; i < 16; i++) acc[i] = 0.0f;
            #pragma unroll
            for (int i = 0; i < 8; i++) akv[i] = 0.0f;
            fence_regs<16>(acc);
            fence_regs<8>(akv);
            const uint64_t dA = make_desc(sb + SM_A + rowhalf * 8192, 16, 1024, 1);
            const uint64_t dB = make_desc(sb + SM_WQ + nh * 64, 16, 1024, 1);
            const uint64_t dC = make_desc(sb + SM_WKV, 128, 8192, 0);
            auto proj_loop = [&](auto KV) {
                #pragma unroll 1
                for (int ch = 0; ch < 8; ch++) {
                    if ((ch & 3) == 0) mbar_wait(bars + 8 * (B_X + (ch >> 2)), 0);
                    if (ch == 0) PROF(2);
                    if (ch == 4) PROF(15);
                    wg_fence();
                    if (decltype(KV)::value) {
                        #pragma unroll
                        for (int ks = 0; ks < 4; ks++) wg_ss16(akv, dA + ch * 1024 + ks * 2, dC + (ch * 4 + ks) * 16);
                    }
                    #pragma unroll
                    for (int ks = 0; ks < 4; ks++) wg_ss32(acc, dA + ch * 1024 + ks * 2, dB + (ch * 4 + ks) * 128);
                    wg_commit();
                }
                wg_wait<0>();
            };
            if (kv_wg) proj_loop(BoolC<true>()); else proj_loop(BoolC<false>());
            fence_regs<16>(acc);
            fence_regs<8>(akv);
            if (kv_wg) {
                const int key = qb * 128 + rowhalf * 64 + wiw * 16 + g;
                uint32_t pk[4];
                #pragma unroll
                for (int i = 0; i < 4; i++) pk[i] = pack_bf16(akv[2 * i], akv[2 * i + 1]);
                float st;
                if (kv_sel == 0) {
                    uint8_t* b = g_kimg + (key >> 3) * 256 + (key & 7) * 16 + 4 * t;
                    *(uint32_t*)(b) = pk[0]; *(uint32_t*)(b + 256) = pk[1]; *(uint32_t*)(b + 128) = pk[2]; *(uint32_t*)(b + 384) = pk[3];
                    float n0 = bf_lo(pk[0]) * bf_lo(pk[0]) + bf_hi(pk[0]) * bf_hi(pk[0]) + bf_lo(pk[2]) * bf_lo(pk[2]) + bf_hi(pk[2]) * bf_hi(pk[2]);
                    float n1 = bf_lo(pk[1]) * bf_lo(pk[1]) + bf_hi(pk[1]) * bf_hi(pk[1]) + bf_lo(pk[3]) * bf_lo(pk[3]) + bf_hi(pk[3]) * bf_hi(pk[3]);
                    n0 += __shfl_xor_sync(0xffffffffu, n0, 1); n0 += __shfl_xor_sync(0xffffffffu, n0, 2);
                    n1 += __shfl_xor_sync(0xffffffffu, n1, 1); n1 += __shfl_xor_sync(0xffffffffu, n1, 2);
                    st = (n0 != n0 || n1 != n1) ? __int_as_float(0x7f800000) : fmaxf(n0, n1);
                } else {
                    const int s = key >> 4;
                    uint8_t* lo = g_vimg + s * 256 + g * 16 + 4 * t;
                    uint8_t* hi = g_vimg + 33024 + (127 - s) * 256 + g * 16 + 4 * t;
                    *(uint32_t*)(lo) = pk[0]; *(uint32_t*)(lo + 128) = pk[1]; *(uint32_t*)(hi) = pk[2]; *(uint32_t*)(hi + 128) = pk[3];
                    st = 0.0f;
                    #pragma unroll
                    for (int i = 0; i < 4; i++) {
                        float a = fabsf(bf_lo(pk[i])), b = fabsf(bf_hi(pk[i]));
                        st = (a != a || b != b) ? __int_as_float(0x7f800000) : fmaxf(st, fmaxf(a, b));
                    }
                }
                #pragma unroll
                for (int o = 16; o; o >>= 1) st = fmaxf(st, __shfl_xor_sync(0xffffffffu, st, o));
                if (lane == 0) s_misc[20 + wiw] = st;
                bar_sync(3, 128);
                if ((tid & 127) == 0) {
                    st = fmaxf(fmaxf(s_misc[20], s_misc[21]), fmaxf(s_misc[22], s_misc[23]));
                    st_release64(&g_flag_kv[(qb * 2 + rowhalf) * 2 + kv_sel], ((unsigned long long)epoch << 32) | __float_as_uint(st));
                }
            }
            const float QS = 0.25f * 1.4426950408889634f;
            float qm = 0.0f;
            #pragma unroll
            for (int i = 0; i < 2; i++) {
                #pragma unroll
                for (int j = 0; j < 4; j++) q[i][j] = pack_bf16(acc[8 * i + 2 * j] * QS, acc[8 * i + 2 * j + 1] * QS);
                float n0 = bf_lo(q[i][0]) * bf_lo(q[i][0]) + bf_hi(q[i][0]) * bf_hi(q[i][0]) + bf_lo(q[i][2]) * bf_lo(q[i][2]) + bf_hi(q[i][2]) * bf_hi(q[i][2]);
                float n1 = bf_lo(q[i][1]) * bf_lo(q[i][1]) + bf_hi(q[i][1]) * bf_hi(q[i][1]) + bf_lo(q[i][3]) * bf_lo(q[i][3]) + bf_hi(q[i][3]) * bf_hi(q[i][3]);
                n0 += __shfl_xor_sync(0xffffffffu, n0, 1); n0 += __shfl_xor_sync(0xffffffffu, n0, 2);
                n1 += __shfl_xor_sync(0xffffffffu, n1, 1); n1 += __shfl_xor_sync(0xffffffffu, n1, 2);
                qm = (n0 != n0 || n1 != n1) ? __int_as_float(0x7f800000) : fmaxf(qm, fmaxf(n0, n1));
            }
            #pragma unroll
            for (int o = 16; o; o >>= 1) qm = fmaxf(qm, __shfl_xor_sync(0xffffffffu, qm, o));
            if (lane == 0) s_misc[warp] = qm;
        }
        bar_sync(8, 640);
        PROF(3);
        if (tid < 4 * (PADU / 8)) *(uint4*)(sB + S_U + (tid / (PADU / 8)) * ULEN * 2 + (tid % (PADU / 8)) * 16) = make_uint4(0, 0, 0, 0);
        PROF(8);
        mbar_wait(bars + 8 * B_U, 0);
        PROF(14);
        #pragma unroll
        for (int i = 0; i < 2; i++) {
            const int l = 2 * (tid + 512 * i);
            const uint2 r0 = *(const uint2*)(sB + S_W3 + l * 16 + rank * 8), r1 = *(const uint2*)(sB + S_W3 + l * 16 + 16 + rank * 8);
            uint32_t* dst = (uint32_t*)(sB + S_U + (PADU + l) * 2);
            dst[0] = __byte_perm(r0.x, r1.x, 0x5410);
            dst[ULEN / 2] = __byte_perm(r0.x, r1.x, 0x7632);
            dst[ULEN] = __byte_perm(r0.y, r1.y, 0x5410);
            dst[3 * ULEN / 2] = __byte_perm(r0.y, r1.y, 0x7632);
        }
        bar_sync(1, 512);
        #pragma unroll 1
        for (int task = tid; task < 4 * 194; task += 512) {
            const int c = task / 194, i = task % 194;
            const uint4* src = (const uint4*)(sB + S_U + c * ULEN * 2 + (PADU + 8 * i - WPAD - 8) * 2);
            const uint4 v0 = src[0], v1 = src[1], v2 = src[2];
            float x[24];
            const uint32_t vv[12] = {v0.x, v0.y, v0.z, v0.w, v1.x, v1.y, v1.z, v1.w, v2.x, v2.y, v2.z, v2.w};
            #pragma unroll
            for (int k = 0; k < 12; k++) { x[2 * k] = bf_lo(vv[k]); x[2 * k + 1] = bf_hi(vv[k]); }
            float w3[12], w5[8];
            #pragma unroll
            for (int e = 0; e < 12; e++) w3[e] = (x[3 + e] + x[4 + e]) + x[5 + e];
            #pragma unroll
            for (int e = 0; e < 8; e++) w5[e] = w3[4 + e] + (x[6 + e] + x[10 + e]);
            *(uint4*)(sB + S_W3 + c * W2LEN * 2 + i * 16) = make_uint4(pack_bf16(w3[0], w3[1]), pack_bf16(w3[2], w3[3]), pack_bf16(w3[4], w3[5]), pack_bf16(w3[6], w3[7]));
            *(uint4*)(sB + S_W5 + c * W2LEN * 2 + i * 16) = make_uint4(pack_bf16(w5[0], w5[1]), pack_bf16(w5[2], w5[3]), pack_bf16(w5[4], w5[5]), pack_bf16(w5[6], w5[7]));
            if (i < 130) {
                float w7[8], w9[8];
                #pragma unroll
                for (int e = 0; e < 8; e++) { w7[e] = w5[e] + (x[5 + e] + x[11 + e]); w9[e] = w7[e] + (x[4 + e] + x[12 + e]); }
                *(uint4*)(sB + S_W7 + c * W3LEN * 2 + i * 16) = make_uint4(pack_bf16(w7[0], w7[1]), pack_bf16(w7[2], w7[3]), pack_bf16(w7[4], w7[5]), pack_bf16(w7[6], w7[7]));
                *(uint4*)(sB + S_W9 + c * W3LEN * 2 + i * 16) = make_uint4(pack_bf16(w9[0], w9[1]), pack_bf16(w9[2], w9[3]), pack_bf16(w9[4], w9[5]), pack_bf16(w9[6], w9[7]));
            }
        }
        PROF(1);
        bar_sync(9, 608);
        PROF(6);
        {
            const int c = warp >> 2, grp = (warp + c) & 3;
            float acc[4][4];
            #pragma unroll
            for (int i = 0; i < 16; i++) (&acc[0][0])[i] = 0.0f;
            const uint32_t tabc = sBa + S_TAB + c * TABN * 2;
            const int e2 = (g - 2 * t) * 2;
            const uint32_t tD = tabc + ((g & 1) ? (TD1 + CD + 1) : (TD0 + CD)) * 2 - e2;
            const uint32_t tE = tabc + ((g & 1) ? (TE1 + CE + 1) : (TE0 + CE)) * 2 - e2;
            const uint32_t t2 = tabc + (T2B + ((g & 1) ? (T2C + C2 + 1) : C2)) * 2 - e2;
            const uint32_t t3 = tabc + (T3B + ((g & 1) ? (T3C + C3 + 1) : C3)) * 2 - e2;
            const int mi = lane >> 3, r8 = lane & 7;
            const uint32_t ub = sBa + S_U + c * ULEN * 2 + (PADU + 16 * (8 * (mi >> 1) + r8) + 8 * (mi & 1)) * 2 + (4 * grp - 4) * 256;
            #pragma unroll 1
            for (int rho = 0; rho < 8; rho++) {
                uint32_t R[5][3];
                #pragma unroll
                for (int qq = 0; qq < 5; qq++) {
                    if (qq < 4 || rho < 2) {
                        const uint32_t a = tD - 32 * (rho + 8 * qq);
                        R[qq][0] = lds32(a + 16); R[qq][1] = lds32(a); R[qq][2] = lds32(a - 16);
                    } else { R[qq][0] = 0; R[qq][1] = 0; R[qq][2] = 0; }
                }
                #pragma unroll
                for (int jp = 0; jp < 4; jp++) {
                    if (grp == 0 && (jp == 0 || (jp == 1 && rho > 0))) continue;
                    if (jp == 0 && rho >= 2) {
                        uint32_t b[4];
                        ldsm4(b, ub + jp * 512 - rho * 32);
                        mma_bf16(acc[0], R[3][1], R[3][2], R[3][0], R[3][1], b[2], b[3]);
                        continue;
                    }
                    uint32_t b[4];
                    ldsm4(b, ub + jp * 512 - rho * 32);
                    #pragma unroll
                    for (int hh = 0; hh < 2; hh++) {
                        #pragma unroll
                        for (int qq = 0; qq < 5; qq++) {
                            const int jr = 2 * jp + hh + qq - 4;
                            if (jr >= 0 && jr < 4) {
                                if (qq < 4 || rho < 2) mma_bf16(acc[jr], R[qq][1], R[qq][2], R[qq][0], R[qq][1], b[2 * hh], b[2 * hh + 1]);
                            }
                        }
                    }
                }
            }
            if (grp >= 2) {
                uint32_t R[5];
                #pragma unroll
                for (int i = 0; i < 5; i++) R[i] = lds32(tE - 16 * (127 + i));
                #pragma unroll
                for (int kk = 0; kk < 2; kk++) {
                    #pragma unroll
                    for (int jp = 0; jp < 2; jp++) {
                        uint32_t b[4];
                        ldsm4(b, ub + (4 + 2 * jp) * 256 - (64 + kk) * 32);
                        mma_bf16(acc[2 * jp], R[2 * kk + 1], R[2 * kk + 2], R[2 * kk], R[2 * kk + 1], b[0], b[1]);
                        mma_bf16(acc[2 * jp + 1], R[2 * kk + 1], R[2 * kk + 2], R[2 * kk], R[2 * kk + 1], b[2], b[3]);
                    }
                }
            }
            const uint32_t soff = (WPAD + 16 * (8 * (mi >> 1) + r8) + 8 * (mi & 1)) * 2 + grp * 1024;
            if (grp >= 1) {
                #pragma unroll 1
                for (int s = 0; s < 4; s++) {
                    const uint32_t sig = sBa + ((s & 1) ? S_W3 : S_W5) + c * W2LEN * 2 + soff - ((s == 0) ? 32 : (s == 1) ? 0 : 16);
                    uint32_t R[7];
                    #pragma unroll
                    for (int i = 0; i < 7; i++) R[i] = lds32(t2 + s * (T2S * 2) - 16 * (3 + i));
                    #pragma unroll
                    for (int bb = 1; bb <= 4; bb++) {
                        if (2 * grp - bb < 0) continue;
                        uint32_t a[4];
                        ldsm4t(a, sig - bb * 512);
                        #pragma unroll
                        for (int jj = 0; jj < 4; jj++) {
                            const int h = jj + 2 * bb;
                            if (h >= 4 && h <= 9) mma_bf16(acc[jj], a[0], a[1], a[2], a[3], R[h - 3], R[h - 4]);
                        }
                    }
                }
            }
            if (grp >= 2) {
                #pragma unroll 1
                for (int s = 0; s < 2; s++) {
                    const uint32_t sig = sBa + (s ? S_W7 : S_W9) + c * W3LEN * 2 + soff - (s ? 16 : 32);
                    uint32_t R[9];
                    #pragma unroll
                    for (int i = 0; i < 9; i++) R[i] = lds32(t3 + s * (T3S * 2) - 16 * (7 + i));
                    #pragma unroll
                    for (int bb = 3; bb <= 6; bb++) {
                        if (2 * grp - bb < 0) continue;
                        uint32_t a[4];
                        ldsm4t(a, sig - bb * 512);
                        #pragma unroll
                        for (int jj = 0; jj < 4; jj++) {
                            const int h = jj + 2 * bb;
                            if (h >= 8 && h <= 15) mma_bf16(acc[jj], a[0], a[1], a[2], a[3], R[h - 7], R[h - 8]);
                        }
                    }
                }
            }
            __nv_bfloat16* ys = (__nv_bfloat16*)(sB + S_Y + c * 4096);
            #pragma unroll
            for (int jj = 0; jj < 4; jj++) {
                const int A = 8 * (4 * grp + jj) + 2 * t;
                ys[16 * A + g] = __float2bfloat16_rn(acc[jj][0]);
                ys[16 * A + 16 + g] = __float2bfloat16_rn(acc[jj][1]);
                ys[16 * A + g + 8] = __float2bfloat16_rn(acc[jj][2]);
                ys[16 * A + 16 + g + 8] = __float2bfloat16_rn(acc[jj][3]);
            }
        }
        bar_arrive(10, 608);
        PROF(7);
        {
            mbar_wait(bars + 8 * B_ST, 0);
            PROF(9); PROFC(8);
            float qm = 0.0f;
            #pragma unroll
            for (int i = 0; i < 16; i++) qm = fmaxf(qm, s_misc[i]);
            const float vm = s_misc[17];
            const bool fast = (qm * s_misc[16] <= 60.0f * 60.0f) && (vm <= 1.0e12f) && (vm >= 1.0e-12f || vm == 0.0f);
            const uint64_t dVstep = 16ull - (16ull << 32);
            uint8_t* ob = g_oimg + qb * 131072 + hg * 16384 + nh * 8192 + (rowhalf * 8 + wiw * 2) * 128 + g * 16 + 4 * t;
            uint32_t cA = 0xBF00BF00u, cB = 0x00030003u;
            asm volatile("" : "+r"(cA), "+r"(cB));
            #pragma unroll 1
            for (int tile = 0; tile < 2; tile++) {
                uint64_t dK = make_desc(sb + SM_K, 128, 256, 0);
                uint64_t dV = make_desc(sb + SM_V, 128, 32768, 0);
                float o[12], s[32];
                uint32_t p[16], qq[4];
                #pragma unroll
                for (int i = 0; i < 4; i++) qq[i] = tile ? q[1][i] : q[0][i];
                #pragma unroll
                for (int i = 0; i < 12; i++) o[i] = 0.0f;
                #pragma unroll
                for (int i = 0; i < 32; i++) s[i] = 0.0f;
                fence_regs<12>(o);
                fence_regs<32>(s);
                if (fast) {
                    #pragma unroll 1
                    for (int c = 0; c < SEQ / 256; c++) {
                        mbar_wait(bars + 8 * (B_KV + c), 0);
                        wg_fence();
                        wg_qk(s, qq, dK);
                        wg_commit();
                        #pragma unroll
                        for (int u = 0; u < 4; u++) {
                            wg_wait<0>();
                            fence_regs<32>(s);
                            #pragma unroll
                            for (int i = 0; i < 16; i++) {
                                if ((MUFU_MASK >> i) & 1) p[i] = exp_mufu(s[2 * i], s[2 * i + 1]);
                                else p[i] = exp_sw(s[2 * i], s[2 * i + 1], cA, cB);
                            }
                            wg_fence();
                            if (u + 1 < 4) wg_qk(s, qq, dK + (u + 1) * 128);
                            #pragma unroll
                            for (int kk = 0; kk < 4; kk++) wg_pv(o, p + 4 * kk, dV + (u * 4 + kk) * dVstep);
                            wg_commit();
                        }
                        dK += 512;
                        dV += 16 * dVstep;
                    }
                    wg_wait<0>();
                } else {
                    float mx0 = -INFINITY, mx1 = -INFINITY;
                    #pragma unroll 1
                    for (int c = 0; c < SEQ / 64; c++) {
                        mbar_wait(bars + 8 * (B_KV + (c >> 2)), 0);
                        wg_fence();
                        wg_qk(s, qq, dK);
                        wg_commit();
                        wg_wait<0>();
                        fence_regs<32>(s);
                        fence_regs<12>(o);
                        float m0 = mx0, m1 = mx1;
                        #pragma unroll
                        for (int j = 0; j < 8; j++) {
                            m0 = fmaxf(m0, fmaxf(s[4 * j], s[4 * j + 1]));
                            m1 = fmaxf(m1, fmaxf(s[4 * j + 2], s[4 * j + 3]));
                        }
                        m0 = fmaxf(m0, __shfl_xor_sync(0xffffffffu, m0, 1)); m0 = fmaxf(m0, __shfl_xor_sync(0xffffffffu, m0, 2));
                        m1 = fmaxf(m1, __shfl_xor_sync(0xffffffffu, m1, 1)); m1 = fmaxf(m1, __shfl_xor_sync(0xffffffffu, m1, 2));
                        const float c0 = ex2f(mx0 - m0), c1 = ex2f(mx1 - m1);
                        mx0 = m0; mx1 = m1;
                        #pragma unroll
                        for (int j = 0; j < 3; j++) { o[4 * j] *= c0; o[4 * j + 1] *= c0; o[4 * j + 2] *= c1; o[4 * j + 3] *= c1; }
                        #pragma unroll
                        for (int j = 0; j < 8; j++) {
                            p[2 * j] = exp_mufu(s[4 * j] - m0, s[4 * j + 1] - m0);
                            p[2 * j + 1] = exp_mufu(s[4 * j + 2] - m1, s[4 * j + 3] - m1);
                        }
                        wg_fence();
                        #pragma unroll
                        for (int kk = 0; kk < 4; kk++) wg_pv(o, p + 4 * kk, dV + kk * dVstep);
                        wg_commit();
                        wg_wait<0>();
                        dK += 128;
                        dV += 4 * dVstep;
                    }
                }
                fence_regs<12>(o);
                const float i0 = 1.0f / o[4], i1 = 1.0f / o[6];
                uint8_t* b = ob + tile * 4096;
                *(uint32_t*)(b) = pack_bf16(o[0] * i0, o[1] * i0);
                *(uint32_t*)(b + 128) = pack_bf16(o[2] * i1, o[3] * i1);
                *(uint32_t*)(b + 2048) = pack_bf16(o[8] * i0, o[9] * i0);
                *(uint32_t*)(b + 2048 + 128) = pack_bf16(o[10] * i1, o[11] * i1);
            }
        }
        PROF(10); PROFC(9);
        bar_arrive(12, 544);

        {
            float acc[16];
            #pragma unroll
            for (int i = 0; i < 16; i++) acc[i] = 0.0f;
            fence_regs<16>(acc);
            const uint64_t dA = make_desc(sb + SM_A + rowhalf * 1024, 2048, 128, 0);
            const uint64_t dB = make_desc(sb + SM_B + nh * 64, 16, 1024, 1);
            mbar_wait(bars + 8 * B_WO, 0);
            #pragma unroll 1
            for (int i = 0; i < 8; i++) {
                const int src = (hg + i) & 7;
                mbar_wait(bars + 8 * (B_O + src), 0);
                wg_fence();
                #pragma unroll
                for (int kk = 0; kk < 4; kk++) wg_ss32(acc, dA + src * 1024 + kk * 256, dB + (src * 4 + kk) * 128);
                wg_commit();
            }
            wg_wait<0>();
            fence_regs<16>(acc);
            PROF(12);
            const int row = qb * 128 + rowhalf * 64 + wiw * 16 + g;
            uint32_t* o32 = (uint32_t*)(P.out + (size_t)row * 1024 + hg * 64 + nh * 32 + 2 * t);
            #pragma unroll
            for (int j = 0; j < 4; j++) {
                o32[4 * j] = pack_bf16(acc[4 * j], acc[4 * j + 1]);
                o32[4 * j + 8 * 512] = pack_bf16(acc[4 * j + 2], acc[4 * j + 3]);
            }
        }
        PROF(13);
    }
}

typedef CUresult (*EncodeFn)(CUtensorMap*, CUtensorMapDataType, cuuint32_t, void*, const cuuint64_t*, const cuuint64_t*,
                             const cuuint32_t*, const cuuint32_t*, CUtensorMapInterleave, CUtensorMapSwizzle,
                             CUtensorMapL2promotion, CUtensorMapFloatOOBfill);

void make_map(EncodeFn fn, CUtensorMap* m, const void* ptr, uint64_t inner, uint64_t outer, uint32_t box_in, uint32_t box_out, CUtensorMapSwizzle swz) {
    cuuint64_t dims[2] = {inner, outer};
    cuuint64_t strides[1] = {inner * 2};
    cuuint32_t box[2] = {box_in, box_out};
    cuuint32_t es[2] = {1, 1};
    fn(m, CU_TENSOR_MAP_DATA_TYPE_BFLOAT16, 2, const_cast<void*>(ptr), dims, strides, box, es, CU_TENSOR_MAP_INTERLEAVE_NONE, swz,
       CU_TENSOR_MAP_L2_PROMOTION_L2_128B, CU_TENSOR_MAP_FLOAT_OOB_FILL_NONE);
}

}

extern "C" void kernel_launch(void* const* d_in, const int* in_sizes, int n_in, void* d_out, int out_size) {
    (void)in_sizes; (void)n_in; (void)out_size;
    static EncodeFn fn = nullptr;
    if (!fn) {
        void* p = nullptr;
        cudaDriverEntryPointQueryResult qr;
        cudaGetDriverEntryPoint("cuTensorMapEncodeTiled", &p, cudaEnableDefault, &qr);
        fn = (EncodeFn)p;
        cudaFuncSetAttribute(fused_kernel, cudaFuncAttributeMaxDynamicSharedMemorySize, SM_ALLOC);
    }
    CUtensorMap tx, twq, two, twk, twv, tu;
    {
        cuuint64_t dims[3] = {64, 2048, 8};
        cuuint64_t strides[2] = {1024, 128};
        cuuint32_t box[3] = {64, 128, 4};
        cuuint32_t es[3] = {1, 1, 1};
        fn(&tx, CU_TENSOR_MAP_DATA_TYPE_BFLOAT16, 3, d_in[0], dims, strides, box, es, CU_TENSOR_MAP_INTERLEAVE_NONE, CU_TENSOR_MAP_SWIZZLE_128B,
           CU_TENSOR_MAP_L2_PROMOTION_L2_128B, CU_TENSOR_MAP_FLOAT_OOB_FILL_NONE);
    }
    make_map(fn, &tu, d_in[5], 512, 2048, 8, 256, CU_TENSOR_MAP_SWIZZLE_NONE);
    make_map(fn, &twq, d_in[1], 512, 512, 64, 256, CU_TENSOR_MAP_SWIZZLE_128B);
    make_map(fn, &twk, d_in[2], 16, 512, 8, 256, CU_TENSOR_MAP_SWIZZLE_NONE);
    make_map(fn, &twv, d_in[3], 16, 512, 8, 256, CU_TENSOR_MAP_SWIZZLE_NONE);
    make_map(fn, &two, d_in[4], 512, 512, 64, 256, CU_TENSOR_MAP_SWIZZLE_128B);
    Params P;
    P.u = (const __nv_bfloat16*)d_in[5];
    P.lar = (const __nv_bfloat16*)d_in[6];
    P.aim = (const __nv_bfloat16*)d_in[7];
    P.cre = (const __nv_bfloat16*)d_in[8];
    P.cim = (const __nv_bfloat16*)d_in[9];
    P.logdt = (const __nv_bfloat16*)d_in[10];
    P.dskip = (const __nv_bfloat16*)d_in[11];
    P.out = (__nv_bfloat16*)d_out;
    fused_kernel<<<NCTA, NTHR, SM_ALLOC>>>(tx, twq, two, twk, twv, tu, P);
}
```

```cpp
#include <cuda_runtime.h>
#include <cuda_bf16.h>
#include <cuda_fp16.h>
#include <cuda.h>
#include <stdint.h>

namespace {

constexpr int SEQ = 2048;
constexpr int NCTA = 128, NTHR = 640;

constexpr int SM_A = 0;
constexpr int SM_WQ = 65536;
constexpr int SM_K = 0, SM_V = 65536;
constexpr int SM_B = 132096;
constexpr int SM_WKV = SM_B + 65536;

constexpr int PADU = 288, ULEN = PADU + 2048;
constexpr int WPAD = 16, W2LEN = WPAD + 1536, W3LEN = WPAD + 1024;
constexpr int TABN = 2240;
constexpr int S_U = 0;
constexpr int S_W3 = S_U + 4 * ULEN * 2;
constexpr int S_W5 = S_W3 + 4 * W2LEN * 2;
constexpr int S_W7 = S_W5 + 4 * W2LEN * 2;
constexpr int S_W9 = S_W7 + 4 * W3LEN * 2;
constexpr int S_TAB = S_W9 + 4 * W3LEN * 2;
constexpr int S_KC = 214016 - SM_B;
constexpr int S_Y = S_KC;
constexpr int SM_BAR = SM_B + S_KC + 16384;
constexpr int SM_TOTAL = SM_BAR + 1024;
constexpr int SM_ALLOC = SM_TOTAL + 1024;
static_assert(SM_V + 65536 + 256 <= SM_B && SM_ALLOC <= 232448 && S_TAB + 4 * TABN * 2 <= S_KC && SM_WKV + 16384 <= SM_B + S_KC, "smem map");

constexpr int TD0 = 0, TD1 = 560, CD = 544;
constexpr int TE0 = 1120, TE1 = 1168, CE = 1056;
constexpr int T2B = 1216, T2S = 160, T2C = 80, C2 = 80;
constexpr int T3B = 1856, T3S = 192, T3C = 96, C3 = 144;

constexpr int rne8(int t) {
    if (t < 256) return t;
    int sh = 0;
    while ((t >> sh) >= 256) sh++;
    int q = t >> sh, rem = t & ((1 << sh) - 1), half = 1 << (sh - 1);
    if (rem > half || (rem == half && (q & 1))) q++;
    return q << sh;
}
constexpr int kcidx(int p) {
    if (p < 256) return (p >> 3) * 24 + (p & 7);
    if (p < 512) return ((p - 256) >> 3) * 24 + 8 + (((p - 256) & 7) >> 1);
    if (p < 1024) { int q = p - 512, hi = q >> 8, rem = q & 255; return (rem >> 3) * 24 + 12 + 2 * hi + ((rem & 7) >> 2); }
    if (p < 2048) { int q = p - 1024; return ((q & 255) >> 3) * 24 + 16 + (q >> 8); }
    return 20;
}
constexpr int KC_ZERO = 23;
constexpr int tab_dense(int t) { return (t >= 0 && t <= 514) ? kcidx(rne8(t)) : KC_ZERO; }
constexpr int tab_extra(int t) { return (t >= 1027 && t <= 1028) ? kcidx(1024) : KC_ZERO; }
constexpr int tab_2(int s, int lag) { return (lag >= 32 && lag <= 63) ? kcidx(s == 0 ? 16 * (lag + 1) : 16 * lag + 4 * s) : KC_ZERO; }
constexpr int tab_3(int s, int lag) { return (lag >= 64 && lag <= 127) ? kcidx(s == 0 ? 16 * (lag + 1) : 16 * lag + 8) : KC_ZERO; }
struct TabMap {
    uint16_t v[TABN];
    constexpr TabMap() : v{} {
        for (int i = 0; i < 560; i++) { v[TD0 + i] = tab_dense(CD - i); v[TD1 + i] = tab_dense(CD + 1 - i); }
        for (int i = 0; i < 48; i++) { v[TE0 + i] = tab_extra(CE - i); v[TE1 + i] = tab_extra(CE + 1 - i); }
        for (int s = 0; s < 4; s++)
            for (int i = 0; i < T2C; i++) { v[T2B + s * T2S + i] = tab_2(s, C2 - i); v[T2B + s * T2S + T2C + i] = tab_2(s, C2 + 1 - i); }
        for (int s = 0; s < 2; s++)
            for (int i = 0; i < T3C; i++) { v[T3B + s * T3S + i] = tab_3(s, C3 - i); v[T3B + s * T3S + T3C + i] = tab_3(s, C3 + 1 - i); }
    }
};
__device__ const __align__(16) TabMap g_tabmap = TabMap();

__device__ __align__(1024) uint8_t g_kimg[65536];
__device__ __align__(1024) uint8_t g_vimg[65536 + 256];
__device__ __align__(1024) uint8_t g_oimg[16 * 131072];
__device__ unsigned long long g_flag_kv[64];
__device__ unsigned g_flag_o[128];
__device__ unsigned g_epoch;
__device__ unsigned g_done;

#define PROF(i) do {} while (0)
#define PROF2(i) do {} while (0)
#define PROFC(i) do {} while (0)
#define PROF3(i) do {} while (0)

__device__ __forceinline__ uint32_t smem_u32(const void* p) { return (uint32_t)__cvta_generic_to_shared(p); }
__device__ __forceinline__ void mbar_init(uint32_t bar, uint32_t cnt) { asm volatile("mbarrier.init.shared::cta.b64 [%0], %1;" :: "r"(bar), "r"(cnt) : "memory"); }
__device__ __forceinline__ void mbar_expect_tx(uint32_t bar, uint32_t bytes) {
    asm volatile("mbarrier.arrive.expect_tx.shared::cta.b64 _, [%0], %1;" :: "r"(bar), "r"(bytes) : "memory"); }
__device__ __forceinline__ void mbar_wait(uint32_t bar, uint32_t parity) {
    uint32_t ok = 0;
    for (int it = 0; it < (1 << 22) && !ok; it++) {
        asm volatile("{ .reg .pred p; mbarrier.try_wait.parity.shared::cta.b64 p, [%1], %2; selp.u32 %0, 1, 0, p; }"
                     : "=r"(ok) : "r"(bar), "r"(parity) : "memory");
    }
}
__device__ __forceinline__ void tma_2d(uint32_t dst, const CUtensorMap* map, int c0, int c1, uint32_t bar) {
    asm volatile("cp.async.bulk.tensor.2d.shared::cluster.global.mbarrier::complete_tx::bytes [%0], [%1, {%3, %4}], [%2];"
                 :: "r"(dst), "l"((uint64_t)map), "r"(bar), "r"(c0), "r"(c1) : "memory");
}
__device__ __forceinline__ void tma_2d_mc(uint32_t dst, const CUtensorMap* map, int c0, int c1, uint32_t bar) {
    asm volatile("cp.async.bulk.tensor.2d.shared::cluster.global.mbarrier::complete_tx::bytes.multicast::cluster [%0], [%1, {%3, %4}], [%2], %5;"
                 :: "r"(dst), "l"((uint64_t)map), "r"(bar), "r"(c0), "r"(c1), "h"((uint16_t)3) : "memory");
}
__device__ __forceinline__ void bulk_g2s_mc(uint32_t dst, const void* src, uint32_t bytes, uint32_t bar) {
    asm volatile("cp.async.bulk.shared::cluster.global.mbarrier::complete_tx::bytes.multicast::cluster [%0], [%1], %2, [%3], %4;"
                 :: "r"(dst), "l"((uint64_t)src), "r"(bytes), "r"(bar), "h"((uint16_t)3) : "memory");
}
__device__ __forceinline__ void pair_sync(uint32_t bar, uint32_t peer) {
    uint32_t ra;
    asm volatile("mapa.shared::cluster.u32 %0, %1, %2;" : "=r"(ra) : "r"(bar), "r"(peer));
    asm volatile("mbarrier.arrive.shared::cluster.b64 _, [%0];" :: "r"(ra) : "memory");
    asm volatile("mbarrier.arrive.shared::cta.b64 _, [%0];" :: "r"(bar) : "memory");
    uint32_t ok = 0;
    for (int it = 0; it < (1 << 22) && !ok; it++) {
        asm volatile("{ .reg .pred p; mbarrier.try_wait.parity.shared::cta.b64 p, [%1], 0; selp.u32 %0, 1, 0, p; }"
                     : "=r"(ok) : "r"(bar) : "memory");
    }
}
__device__ __forceinline__ void fence_async_all() { asm volatile("fence.proxy.async.global;" ::: "memory"); }
__device__ __forceinline__ void fence_async_smem() { asm volatile("fence.proxy.async.shared::cta;" ::: "memory"); }
__device__ __forceinline__ unsigned ld_acquire(const unsigned* p) {
    unsigned v; asm volatile("ld.acquire.gpu.global.u32 %0, [%1];" : "=r"(v) : "l"(p) : "memory"); return v; }
__device__ __forceinline__ void st_release(unsigned* p, unsigned v) { asm volatile("st.release.gpu.global.u32 [%0], %1;" :: "l"(p), "r"(v) : "memory"); }
__device__ __forceinline__ void wait_flag(const unsigned* p, unsigned epoch) {
    for (int it = 0; it < (1 << 22); it++) { if (ld_acquire(p) == epoch) break; }
}
__device__ __forceinline__ unsigned long long ld_acquire64(const unsigned long long* p) {
    unsigned long long v; asm volatile("ld.acquire.gpu.global.u64 %0, [%1];" : "=l"(v) : "l"(p) : "memory"); return v; }
__device__ __forceinline__ void st_release64(unsigned long long* p, unsigned long long v) { asm volatile("st.release.gpu.global.u64 [%0], %1;" :: "l"(p), "l"(v) : "memory"); }
__device__ __forceinline__ float wait_flag64(const unsigned long long* p, unsigned epoch) {
    unsigned long long v = 0;
    for (int it = 0; it < (1 << 22); it++) { v = ld_acquire64(p); if ((unsigned)(v >> 32) == epoch) break; }
    return __uint_as_float((unsigned)v);
}
__device__ __forceinline__ void tma_3d_mc(uint32_t dst, const CUtensorMap* map, int c0, int c1, int c2, uint32_t bar) {
    asm volatile("cp.async.bulk.tensor.3d.shared::cluster.global.mbarrier::complete_tx::bytes.multicast::cluster [%0], [%1, {%3, %4, %5}], [%2], %6;"
                 :: "r"(dst), "l"((uint64_t)map), "r"(bar), "r"(c0), "r"(c1), "r"(c2), "h"((uint16_t)3) : "memory");
}
__device__ __forceinline__ void bar_sync(int id, int n) { asm volatile("bar.sync %0, %1;" :: "r"(id), "r"(n) : "memory"); }
__device__ __forceinline__ void bar_arrive(int id, int n) { asm volatile("bar.arrive %0, %1;" :: "r"(id), "r"(n) : "memory"); }
__device__ __forceinline__ void mbar_arrive(uint32_t bar) { asm volatile("mbarrier.arrive.shared::cta.b64 _, [%0];" :: "r"(bar) : "memory"); }

__device__ __forceinline__ uint64_t make_desc(uint32_t saddr, uint32_t lbo, uint32_t sbo, uint32_t swz) {
    uint64_t d = 0;
    d |= (uint64_t)((saddr & 0x3FFFF) >> 4);
    d |= (uint64_t)((lbo >> 4) & 0x3FFF) << 16;
    d |= (uint64_t)((sbo >> 4) & 0x3FFF) << 32;
    d |= (uint64_t)swz << 62;
    return d;
}
__device__ __forceinline__ void wg_fence() { asm volatile("wgmma.fence.sync.aligned;" ::: "memory"); }
__device__ __forceinline__ void wg_commit() { asm volatile("wgmma.commit_group.sync.aligned;" ::: "memory"); }
template<int N> __device__ __forceinline__ void wg_wait() { asm volatile("wgmma.wait_group.sync.aligned %0;" :: "n"(N) : "memory"); }
#define A4(d, o) "+f"(d[o + 0]), "+f"(d[o + 1]), "+f"(d[o + 2]), "+f"(d[o + 3])
#define A16(d, o) A4(d, o), A4(d, o + 4), A4(d, o + 8), A4(d, o + 12)

__device__ __forceinline__ void wg_pv(float* d, const uint32_t* a, uint64_t desc) {
    asm volatile("wgmma.mma_async.sync.aligned.m64n24k16.f32.bf16.bf16 {%0,%1,%2,%3,%4,%5,%6,%7,%8,%9,%10,%11}, {%12,%13,%14,%15}, %16, 1, 1, 1, 1;"
                 : A4(d, 0), A4(d, 4), A4(d, 8) : "r"(a[0]), "r"(a[1]), "r"(a[2]), "r"(a[3]), "l"(desc));
}
__device__ __forceinline__ void wg_qk(float* d, const uint32_t* a, uint64_t desc) {
    asm volatile("wgmma.mma_async.sync.aligned.m64n64k16.f32.bf16.bf16 {%0,%1,%2,%3,%4,%5,%6,%7,%8,%9,%10,%11,%12,%13,%14,%15,%16,%17,%18,%19,%20,%21,%22,%23,%24,%25,%26,%27,%28,%29,%30,%31}, {%32,%33,%34,%35}, %36, 0, 1, 1, 0;"
                 : A16(d, 0), A16(d, 16) : "r"(a[0]), "r"(a[1]), "r"(a[2]), "r"(a[3]), "l"(desc));
}
__device__ __forceinline__ void wg_ss32(float* d, uint64_t da, uint64_t db) {
    asm volatile("wgmma.mma_async.sync.aligned.m64n32k16.f32.bf16.bf16 {%0,%1,%2,%3,%4,%5,%6,%7,%8,%9,%10,%11,%12,%13,%14,%15}, %16, %17, 1, 1, 1, 0, 1;"
                 : A16(d, 0) : "l"(da), "l"(db));
}
__device__ __forceinline__ void wg_ss16(float* d, uint64_t da, uint64_t db) {
    asm volatile("wgmma.mma_async.sync.aligned.m64n16k16.f32.bf16.bf16 {%0,%1,%2,%3,%4,%5,%6,%7}, %8, %9, 1, 1, 1, 0, 1;"
                 : A4(d, 0), A4(d, 4) : "l"(da), "l"(db));
}
template<int N> __device__ __forceinline__ void fence_regs(float* r) {
    #pragma unroll
    for (int i = 0; i < N; i++) asm volatile("" : "+f"(r[i]) :: "memory");
}
__device__ __forceinline__ void mma_bf16(float* d, uint32_t a0, uint32_t a1, uint32_t a2, uint32_t a3, uint32_t b0, uint32_t b1) {
    asm volatile("mma.sync.aligned.m16n8k16.row.col.f32.bf16.bf16.f32 {%0,%1,%2,%3}, {%4,%5,%6,%7}, {%8,%9}, {%0,%1,%2,%3};"
                 : "+f"(d[0]), "+f"(d[1]), "+f"(d[2]), "+f"(d[3]) : "r"(a0), "r"(a1), "r"(a2), "r"(a3), "r"(b0), "r"(b1));
}
__device__ __forceinline__ void mma_f16(float* d, const uint32_t* a, uint32_t b0, uint32_t b1) {
    asm volatile("mma.sync.aligned.m16n8k16.row.col.f32.f16.f16.f32 {%0,%1,%2,%3}, {%4,%5,%6,%7}, {%8,%9}, {%0,%1,%2,%3};"
                 : "+f"(d[0]), "+f"(d[1]), "+f"(d[2]), "+f"(d[3]) : "r"(a[0]), "r"(a[1]), "r"(a[2]), "r"(a[3]), "r"(b0), "r"(b1));
}
__device__ __forceinline__ void ldsm4(uint32_t* r, uint32_t addr) {
    asm volatile("ldmatrix.sync.aligned.m8n8.x4.shared.b16 {%0,%1,%2,%3}, [%4];" : "=r"(r[0]), "=r"(r[1]), "=r"(r[2]), "=r"(r[3]) : "r"(addr) : "memory");
}
__device__ __forceinline__ void ldsm4t(uint32_t* r, uint32_t addr) {
    asm volatile("ldmatrix.sync.aligned.m8n8.x4.trans.shared.b16 {%0,%1,%2,%3}, [%4];" : "=r"(r[0]), "=r"(r[1]), "=r"(r[2]), "=r"(r[3]) : "r"(addr) : "memory");
}
__device__ __forceinline__ uint32_t lds32(uint32_t addr) { uint32_t v; asm volatile("ld.shared.u32 %0, [%1];" : "=r"(v) : "r"(addr) : "memory"); return v; }
__device__ __forceinline__ float ex2f(float x) { float r; asm("ex2.approx.ftz.f32 %0, %1;" : "=f"(r) : "f"(x)); return r; }
__device__ __forceinline__ uint32_t pack_bf16(float lo, float hi) { uint32_t r; asm("cvt.rn.bf16x2.f32 %0, %1, %2;" : "=r"(r) : "f"(hi), "f"(lo)); return r; }
__device__ __forceinline__ uint32_t pack_f16(float lo, float hi) { uint32_t r; asm("cvt.rn.f16x2.f32 %0, %1, %2;" : "=r"(r) : "f"(hi), "f"(lo)); return r; }
__device__ __forceinline__ float bf_lo(uint32_t v) { return __uint_as_float(v << 16); }
__device__ __forceinline__ float bf_hi(uint32_t v) { return __uint_as_float(v & 0xFFFF0000u); }
__device__ __forceinline__ float bf_round(float x) { return __bfloat162float(__float2bfloat16_rn(x)); }

__device__ __forceinline__ uint32_t exp_mufu(float x0, float x1) { return pack_bf16(ex2f(x0), ex2f(x1)); }
#define SW_MAGIC (256.0f + 127.0f - 0.598938f)
__device__ __forceinline__ uint32_t exp_sw(float x0, float x1, uint32_t cA, uint32_t cB) {
    float t0 = x0 + SW_MAGIC, t1 = x1 + SW_MAGIC;
    uint32_t L, mh, ec, r;
    asm("prmt.b32 %0, %1, %2, 0x6521;" : "=r"(L) : "r"(__float_as_uint(t0)), "r"(__float_as_uint(t1)));
    asm("lop3.b32 %0, %1, 0x007F007F, %2, 0xEA;" : "=r"(mh) : "r"(L), "r"(cA));
    asm("lop3.b32 %0, %1, 0x7F807F80, %2, 0xEA;" : "=r"(ec) : "r"(L), "r"(cB));
    asm("fma.rn.bf16x2 %0, %1, %2, %3;" : "=r"(r) : "r"(L), "r"(mh), "r"(ec));
    return r;
}
constexpr uint32_t MUFU_MASK = 0x4949;

struct cf { float x, y; };
__device__ __forceinline__ cf cmul(cf a, cf b) { cf r; r.x = a.x * b.x - a.y * b.y; r.y = a.x * b.y + a.y * b.x; return r; }
__device__ __forceinline__ cf cexp_p(float a2, float b, float p) {
    float e = ex2f(a2 * p);
    float ph = b * p;
    ph -= (ph + 12582912.0f) - 12582912.0f;
    float ang = ph * 6.283185307f;
    cf r; r.x = e * __cosf(ang); r.y = e * __sinf(ang);
    return r;
}
__device__ __forceinline__ uint32_t h2_cmul(uint32_t w, uint32_t wsw, uint32_t e) {
    __half2 hw = *(__half2*)&w, hs = *(__half2*)&wsw, he = *(__half2*)&e;
    __half2 r = __hfma2(hs, __high2half2(he), __hmul2(hw, __low2half2(he)));
    return *(uint32_t*)&r;
}

template<bool B> struct BoolC { static constexpr bool value = B; };
struct Params {
    const __nv_bfloat16 *u, *lar, *aim, *cre, *cim, *logdt, *dskip;
    __nv_bfloat16* out;
};

constexpr int B_O = 0, B_KV = 8, B_WO = 16, B_U = 17, B_ST = 18, B_H = 19, B_X = 22;

__device__ __forceinline__ void helper_role(const Params& P, uint8_t* sp, unsigned epoch) {
    const int tid = threadIdx.x - 544;
    const int d0 = blockIdx.x * 4;
    uint8_t* sB = sp + SM_B;
    const uint2 dsk = __ldg((const uint2*)(P.dskip + d0));
    {
        const uint32_t* map = (const uint32_t*)g_tabmap.v;
        uint32_t mp[12];
        #pragma unroll
        for (int i = 0; i < 12; i++) { const int w = tid + 96 * i; mp[i] = (w < TABN / 2) ? __ldg(map + w) : 0u; }
        const int hg = blockIdx.x & 7;
        if (hg < 4 && tid < 32) {
            bar_sync(3, 160);
            if (tid == 0) {
                const float* s_misc = (const float*)(sp + SM_BAR + 256);
                const float st = fmaxf(fmaxf(s_misc[20], s_misc[21]), fmaxf(s_misc[22], s_misc[23]));
                st_release64(&g_flag_kv[((blockIdx.x >> 3) * 2 + (hg & 1)) * 2 + (hg >> 1)], ((unsigned long long)epoch << 32) | __float_as_uint(st));
            }
            __syncwarp();
        }
        bar_sync(8, 608);
        #pragma unroll 1
        for (int cc = 0; cc < 4; cc++) {
            const float* kc = (const float*)(sB + S_KC + cc * 4096);
            uint32_t* tab = (uint32_t*)(sB + S_TAB + cc * TABN * 2);
            #pragma unroll
            for (int i = 0; i < 12; i++) { const int w = tid + 96 * i; if (w < TABN / 2) tab[w] = pack_bf16(kc[mp[i] & 0xFFFF], kc[mp[i] >> 16]); }
        }
    }
    bar_arrive(9, 608);
    PROF2(2);
    bar_sync(10, 608);
    {
        uint32_t dd[4] = {__byte_perm(dsk.x, 0, 0x1010), __byte_perm(dsk.x, 0, 0x3232), __byte_perm(dsk.y, 0, 0x1010), __byte_perm(dsk.y, 0, 0x3232)};
        #pragma unroll 2
        for (int pi = tid; pi < 1024; pi += 96) {
            const int l = 2 * pi;
            uint32_t r[4];
            #pragma unroll
            for (int cc = 0; cc < 4; cc++) {
                const uint32_t y2 = *(const uint32_t*)(sB + S_Y + cc * 4096 + l * 2);
                const uint32_t u2 = *(const uint32_t*)(sB + S_U + cc * ULEN * 2 + (PADU + l) * 2);
                __nv_bfloat162 pr = __hmul2(*(const __nv_bfloat162*)&u2, *(const __nv_bfloat162*)&dd[cc]);
                __nv_bfloat162 sm = __hadd2(*(const __nv_bfloat162*)&y2, pr);
                r[cc] = *(uint32_t*)&sm;
            }
            *(uint2*)(P.out + (size_t)l * 1024 + 512 + d0) = make_uint2(__byte_perm(r[0], r[1], 0x5410), __byte_perm(r[2], r[3], 0x5410));
            *(uint2*)(P.out + (size_t)(l + 1) * 1024 + 512 + d0) = make_uint2(__byte_perm(r[0], r[1], 0x7632), __byte_perm(r[2], r[3], 0x7632));
        }
    }
    bar_arrive(11, 128);
    PROF2(4);
}

__global__ void __cluster_dims__(2, 1, 1) __launch_bounds__(NTHR, 1)
fused_kernel(const __grid_constant__ CUtensorMap tm_x, const __grid_constant__ CUtensorMap tm_wq,
             const __grid_constant__ CUtensorMap tm_wo, const __grid_constant__ CUtensorMap tm_wk,
             const __grid_constant__ CUtensorMap tm_wv, const __grid_constant__ CUtensorMap tm_u, const Params P) {
    extern __shared__ uint8_t smem_raw[];
    const uint32_t sb = (smem_u32(smem_raw) + 1023u) & ~1023u;
    uint8_t* sp = smem_raw + (sb - smem_u32(smem_raw));

    const int tid = threadIdx.x, warp = tid >> 5, lane = tid & 31, wg = tid >> 7, wiw = warp & 3;
    const int g = lane >> 2, t = lane & 3;
    const int qb = blockIdx.x >> 3, hg = blockIdx.x & 7;
    const uint32_t rank = blockIdx.x & 1;
    const int rowhalf = wg & 1, nh = wg >> 1;
    const bool kv_cta = hg < 4;
    const int kv_sel = hg >> 1;
    const bool kv_wg = kv_cta && (wg == (hg & 1));

    const uint32_t bars = sb + SM_BAR;
    float* s_misc = (float*)(sp + SM_BAR + 256);
    const CUtensorMap* tm_kv = kv_sel ? &tm_wv : &tm_wk;

    PROF(0);
    unsigned short p_lar = 0, p_aim = 0, p_cre = 0, p_cim = 0, p_ldt = 0;
    if (wg < 4) {
        const int n = (blockIdx.x * 4 + wg) * 128 + (tid & 127);
        p_lar = __ldg((const unsigned short*)P.lar + n);
        p_aim = __ldg((const unsigned short*)P.aim + n);
        p_cre = __ldg((const unsigned short*)P.cre + n);
        p_cim = __ldg((const unsigned short*)P.cim + n);
        p_ldt = __ldg((const unsigned short*)P.logdt + blockIdx.x * 4 + wg);
    } else if (warp == 16) {
        PROF3(5);
        if (lane == 0) {
            asm volatile("prefetch.tensormap [%0];" :: "l"((uint64_t)&tm_wq) : "memory");
            asm volatile("prefetch.tensormap [%0];" :: "l"((uint64_t)&tm_x) : "memory");
            mbar_init(bars + 8 * B_X, 1);
            mbar_init(bars + 8 * B_X + 8, 1);
            asm volatile("fence.mbarrier_init.release.cluster;" ::: "memory");
            fence_async_smem();
            #pragma unroll
            for (int h = 0; h < 2; h++) {
                mbar_expect_tx(bars + 8 * (B_X + h), 98304u + (kv_cta ? 8192u : 0u));
                tma_2d(sb + SM_WQ + h * 32768, &tm_wq, hg * 64, h * 256, bars + 8 * (B_X + h));
            }
        }
        PROF3(6);
    } else if (lane == 0) {
        for (int i = warp - 17; i < B_X; i += 3) {
            mbar_init(bars + 8 * i, i >= B_H ? 2 : 1);
            if (i <= B_U) mbar_expect_tx(bars + 8 * i, i < B_WO ? 16384u : i == B_WO ? 65536u : 32768u);
        }
        asm volatile("fence.mbarrier_init.release.cluster;" ::: "memory");
        fence_async_smem();
    }
    PROF3(7);
    PROF(11);
    asm volatile("barrier.cluster.arrive.relaxed.aligned;" ::: "memory");
    const unsigned epoch = *(volatile unsigned*)&g_epoch + 1u;
    asm volatile("barrier.cluster.wait.aligned;" ::: "memory");
    PROF(5);

    if (warp == 16) {
        if (lane == 0) {
            tma_3d_mc(sb + (rank ? SM_A : SM_B), &tm_x, 0, qb * 128, rank * 4, bars + 8 * (B_X + rank));
            if (kv_cta) {
                #pragma unroll
                for (int i = 0; i < 4; i++) tma_2d(sb + SM_WKV + i * 4096, tm_kv, (i >> 1) * 8, (i & 1) * 256, bars + 8 * (B_X + (i & 1)));
            }
            asm volatile("prefetch.tensormap [%0];" :: "l"((uint64_t)&tm_u) : "memory");
            asm volatile("prefetch.tensormap [%0];" :: "l"((uint64_t)&tm_wo) : "memory");
        }
        PROF3(10);
        bar_sync(13, 544);
        if (lane == 0) {
            pair_sync(bars + 8 * (B_H + 2), rank ^ 1);
            #pragma unroll
            for (int i = 0; i < 4; i++) tma_2d_mc(sb + SM_B + S_W3 + (rank * 4 + i) * 4096, &tm_u, (blockIdx.x >> 1) * 8, (rank * 4 + i) * 256, bars + 8 * B_U);
        }
        bar_sync(14, 544);
        if (lane == 0) pair_sync(bars + 8 * B_H, rank ^ 1);
        __syncwarp();
        PROF3(11);
        *(uint2*)(sp + SM_V + 32768 + lane * 8) = make_uint2(0x3F803F80u, 0x3F803F80u);
        fence_async_smem();
        float km = wait_flag64(&g_flag_kv[2 * lane], epoch);
        float vm = wait_flag64(&g_flag_kv[2 * lane + 1], epoch);
        __syncwarp();
        PROF3(12);
        if (lane < 8) {
            fence_async_all();
            const uint32_t bar = bars + 8 * (B_KV + lane);
            if (rank == 0) bulk_g2s_mc(sb + SM_K + lane * 8192, g_kimg + lane * 8192, 8192, bar);
            else {
                bulk_g2s_mc(sb + SM_V + lane * 4096, g_vimg + lane * 4096, 4096, bar);
                bulk_g2s_mc(sb + SM_V + 33024 + (7 - lane) * 4096, g_vimg + 33024 + (7 - lane) * 4096, 4096, bar);
            }
        }
        #pragma unroll
        for (int o = 16; o; o >>= 1) { km = fmaxf(km, __shfl_xor_sync(0xffffffffu, km, o)); vm = fmaxf(vm, __shfl_xor_sync(0xffffffffu, vm, o)); }
        if (lane == 0) { s_misc[16] = km; s_misc[17] = vm; mbar_arrive(bars + 8 * B_ST); }
        PROF3(13);
        bar_sync(11, 128);
        if (lane < 2) { fence_async_smem(); tma_2d(sb + SM_B + lane * 32768, &tm_wo, hg * 64, lane * 256, bars + 8 * B_WO); }
        bar_sync(12, 544);
        if (lane == 0) {
            st_release(&g_flag_o[blockIdx.x], epoch);
            pair_sync(bars + 8 * (B_H + 1), rank ^ 1);
        }
        __syncwarp();
        PROF3(14);
        if (lane < 4) {
            const int src = 2 * lane + rank;
            wait_flag(&g_flag_o[qb * 8 + src], epoch);
            fence_async_all();
            bulk_g2s_mc(sb + SM_A + src * 16384, g_oimg + qb * 131072 + src * 16384, 16384, bars + 8 * (B_O + src));
        }
        __syncwarp();
        PROF3(15);
        if (lane == 0) {
            const unsigned prev = atomicAdd(&g_done, 1u);
            if (prev == NCTA - 1) {
                g_done = 0;
                __threadfence();
                *(volatile unsigned*)&g_epoch = epoch;
            }
        }
    } else if (wg == 4) {
        helper_role(P, sp, epoch);
    } else {
        uint8_t* sB = sp + SM_B;
        const uint32_t sBa = sb + SM_B;
        {
            const int c = wg;
            const float dt = bf_round(expf(bf_lo(p_ldt)));
            const float are = -bf_round(expf(bf_lo(p_lar))) * dt;
            const float aim = bf_lo(p_aim) * dt;
            float cr = 2.0f * (bf_lo(p_cre) * dt);
            float ci = 2.0f * (bf_lo(p_cim) * dt);
            const float a2 = are * 1.4426950408889634f, bb = aim * 0.15915494309189535f;
            float m = fmaxf(fabsf(cr), fabsf(ci));
            #pragma unroll
            for (int o = 16; o; o >>= 1) m = fmaxf(m, __shfl_xor_sync(0xffffffffu, m, o));
            int ebits = (__float_as_uint(m) >> 23) & 0xFF;
            ebits = min(max(ebits, 2), 250);
            const float scale = __uint_as_float((uint32_t)(ebits + 1) << 23);
            const float iscale = __uint_as_float((uint32_t)(253 - ebits) << 23);
            cf cc; cc.x = cr * iscale; cc.y = ci * iscale;

            const uint32_t stg = sBa + S_KC + warp * 1024;
            uint4* stp = (uint4*)(sB + S_KC + warp * 1024 + lane * 32);
            const uint32_t fa = stg + t * 32 + g * 4;

            uint32_t af[4][2][4];
            cf E256;
            {
                const cf E8 = cexp_p(a2, bb, 8.0f);
                uint32_t w[8];
                cf cur; cur.x = 1.0f; cur.y = 0.0f;
                w[0] = pack_f16(1.0f, 0.0f);
                cur = E8; w[1] = pack_f16(cur.x, cur.y);
                #pragma unroll
                for (int i = 2; i < 8; i++) { cur = cmul(cur, E8); w[i] = pack_f16(cur.x, cur.y); }
                stp[0] = make_uint4(w[0], w[1], w[2], w[3]);
                stp[1] = make_uint4(w[4], w[5], w[6], w[7]);
                const cf E64 = cexp_p(a2, bb, 64.0f);
                const cf E128 = cmul(E64, E64), E192 = cmul(E128, E64);
                E256 = cexp_p(a2, bb, 256.0f);
                const uint32_t e1 = pack_f16(E64.x, E64.y), e2 = pack_f16(E128.x, E128.y), e3 = pack_f16(E192.x, E192.y);
                __syncwarp();
                #pragma unroll
                for (int s = 0; s < 4; s++) {
                    #pragma unroll
                    for (int hh = 0; hh < 2; hh++) {
                        const uint32_t w0 = lds32(fa + s * 256 + hh * 128);
                        const uint32_t wsw = __byte_perm(w0, 0, 0x1032) ^ 0x00008000u;
                        const int src = 8 * s + t + 4 * hh;
                        const uint32_t f1 = __shfl_sync(0xffffffffu, e1, src), f2 = __shfl_sync(0xffffffffu, e2, src), f3 = __shfl_sync(0xffffffffu, e3, src);
                        af[s][0][2 * hh] = w0;
                        af[s][0][2 * hh + 1] = h2_cmul(w0, wsw, f1);
                        af[s][1][2 * hh] = h2_cmul(w0, wsw, f2);
                        af[s][1][2 * hh + 1] = h2_cmul(w0, wsw, f3);
                    }
                }
                __syncwarp();
            }
            float acc[2][3][4];
            #pragma unroll
            for (int i = 0; i < 24; i++) (&acc[0][0][0])[i] = 0.0f;
            const cf E1 = cexp_p(a2, bb, 1.0f);
            const cf E2 = cmul(E1, E1), E4 = cmul(E2, E2);
            cf X512;
            #pragma unroll
            for (int nt = 0; nt < 3; nt++) {
                uint32_t xv[8];
                if (nt == 0) {
                    cf cur = cc;
                    xv[0] = pack_f16(cur.x, -cur.y);
                    #pragma unroll
                    for (int i = 1; i < 8; i++) { cur = cmul(cur, E1); xv[i] = pack_f16(cur.x, -cur.y); }
                } else if (nt == 1) {
                    cf cur = cmul(cc, E256);
                    X512 = cmul(cur, E256);
                    xv[0] = pack_f16(cur.x, -cur.y);
                    #pragma unroll
                    for (int i = 1; i < 4; i++) { cur = cmul(cur, E2); xv[i] = pack_f16(cur.x, -cur.y); }
                    cur = cmul(X512, E4);
                    xv[4] = pack_f16(X512.x, -X512.y); xv[5] = pack_f16(cur.x, -cur.y);
                    X512 = cmul(X512, E256);
                    cur = cmul(X512, E4);
                    xv[6] = pack_f16(X512.x, -X512.y); xv[7] = pack_f16(cur.x, -cur.y);
                } else {
                    cf cur = X512;
                    #pragma unroll
                    for (int i = 0; i < 5; i++) { cur = cmul(cur, E256); xv[i] = pack_f16(cur.x, -cur.y); }
                    xv[5] = 0; xv[6] = 0; xv[7] = 0;
                }
                stp[0] = make_uint4(xv[0], xv[1], xv[2], xv[3]);
                stp[1] = make_uint4(xv[4], xv[5], xv[6], xv[7]);
                __syncwarp();
                #pragma unroll
                for (int s = 0; s < 4; s++) {
                    const uint32_t b0 = lds32(fa + s * 256), b1 = lds32(fa + s * 256 + 128);
                    mma_f16(acc[0][nt], af[s][0], b0, b1);
                    mma_f16(acc[1][nt], af[s][1], b0, b1);
                }
                __syncwarp();
            }
            float* kc = (float*)(sB + S_KC + c * 4096);
            bar_sync(4 + c, 128);
            #pragma unroll 1
            for (int step = 0; step < 4; step++) {
                if ((warp & 3) == step) {
                    #pragma unroll
                    for (int mt = 0; mt < 2; mt++)
                        #pragma unroll
                        for (int nt = 0; nt < 3; nt++)
                            #pragma unroll
                            for (int hh = 0; hh < 2; hh++) {
                                float2* p = (float2*)(kc + (mt * 16 + hh * 8 + g) * 24 + nt * 8 + 2 * t);
                                float2 v = make_float2(acc[mt][nt][2 * hh] * scale, acc[mt][nt][2 * hh + 1] * scale);
                                if (step) { float2 o = *p; v.x += o.x; v.y += o.y; }
                                *p = v;
                            }
                }
                if (step < 3) bar_sync(4 + c, 128);
            }
        }

        PROF(4);
        uint32_t q[2][4];
        {
            float acc[16], akv[8];
            #pragma unroll
            for (int i = 0; i < 16; i++) acc[i] = 0.0f;
            #pragma unroll
            for (int i = 0; i < 8; i++) akv[i] = 0.0f;
            fence_regs<16>(acc);
            fence_regs<8>(akv);
            const uint64_t dA0 = make_desc(sb + SM_B + rowhalf * 8192, 16, 1024, 1);
            const uint64_t dA1 = make_desc(sb + SM_A + rowhalf * 8192, 16, 1024, 1) - 4096;
            const uint64_t dB = make_desc(sb + SM_WQ + nh * 64, 16, 1024, 1);
            const uint64_t dC = make_desc(sb + SM_WKV, 128, 8192, 0);
            auto proj_loop = [&](auto KV) {
                #pragma unroll 1
                for (int ch = 0; ch < 8; ch++) {
                    if (ch == 4) { wg_wait<0>(); bar_arrive(13, 544); }
                    if ((ch & 3) == 0) mbar_wait(bars + 8 * (B_X + (ch >> 2)), 0);
                    const uint64_t dA = ch < 4 ? dA0 : dA1;
                    if (ch == 0) PROF(2);
                    if (ch == 4) PROF(15);
                    wg_fence();
                    if (decltype(KV)::value) {
                        #pragma unroll
                        for (int ks = 0; ks < 4; ks++) wg_ss16(akv, dA + ch * 1024 + ks * 2, dC + (ch * 4 + ks) * 16);
                    }
                    #pragma unroll
                    for (int ks = 0; ks < 4; ks++) wg_ss32(acc, dA + ch * 1024 + ks * 2, dB + (ch * 4 + ks) * 128);
                    wg_commit();
                }
                wg_wait<0>();
            };
            if (kv_wg) proj_loop(BoolC<true>()); else proj_loop(BoolC<false>());
            fence_regs<16>(acc);
            fence_regs<8>(akv);
            if (kv_wg) {
                const int key = qb * 128 + rowhalf * 64 + wiw * 16 + g;
                uint32_t pk[4];
                #pragma unroll
                for (int i = 0; i < 4; i++) pk[i] = pack_bf16(akv[2 * i], akv[2 * i + 1]);
                float st;
                if (kv_sel == 0) {
                    uint8_t* b = g_kimg + (key >> 3) * 256 + (key & 7) * 16 + 4 * t;
                    *(uint32_t*)(b) = pk[0]; *(uint32_t*)(b + 256) = pk[1]; *(uint32_t*)(b + 128) = pk[2]; *(uint32_t*)(b + 384) = pk[3];
                    float n0 = bf_lo(pk[0]) * bf_lo(pk[0]) + bf_hi(pk[0]) * bf_hi(pk[0]) + bf_lo(pk[2]) * bf_lo(pk[2]) + bf_hi(pk[2]) * bf_hi(pk[2]);
                    float n1 = bf_lo(pk[1]) * bf_lo(pk[1]) + bf_hi(pk[1]) * bf_hi(pk[1]) + bf_lo(pk[3]) * bf_lo(pk[3]) + bf_hi(pk[3]) * bf_hi(pk[3]);
                    n0 += __shfl_xor_sync(0xffffffffu, n0, 1); n0 += __shfl_xor_sync(0xffffffffu, n0, 2);
                    n1 += __shfl_xor_sync(0xffffffffu, n1, 1); n1 += __shfl_xor_sync(0xffffffffu, n1, 2);
                    st = (n0 != n0 || n1 != n1) ? __int_as_float(0x7f800000) : fmaxf(n0, n1);
                } else {
                    const int s = key >> 4;
                    uint8_t* lo = g_vimg + s * 256 + g * 16 + 4 * t;
                    uint8_t* hi = g_vimg + 33024 + (127 - s) * 256 + g * 16 + 4 * t;
                    *(uint32_t*)(lo) = pk[0]; *(uint32_t*)(lo + 128) = pk[1]; *(uint32_t*)(hi) = pk[2]; *(uint32_t*)(hi + 128) = pk[3];
                    st = 0.0f;
                    #pragma unroll
                    for (int i = 0; i < 4; i++) {
                        float a = fabsf(bf_lo(pk[i])), b = fabsf(bf_hi(pk[i]));
                        st = (a != a || b != b) ? __int_as_float(0x7f800000) : fmaxf(st, fmaxf(a, b));
                    }
                }
                #pragma unroll
                for (int o = 16; o; o >>= 1) st = fmaxf(st, __shfl_xor_sync(0xffffffffu, st, o));
                if (lane == 0) s_misc[20 + wiw] = st;
                bar_arrive(3, 160);
            }
            const float QS = 0.25f * 1.4426950408889634f;
            float qm = 0.0f;
            #pragma unroll
            for (int i = 0; i < 2; i++) {
                #pragma unroll
                for (int j = 0; j < 4; j++) q[i][j] = pack_bf16(acc[8 * i + 2 * j] * QS, acc[8 * i + 2 * j + 1] * QS);
                float n0 = bf_lo(q[i][0]) * bf_lo(q[i][0]) + bf_hi(q[i][0]) * bf_hi(q[i][0]) + bf_lo(q[i][2]) * bf_lo(q[i][2]) + bf_hi(q[i][2]) * bf_hi(q[i][2]);
                float n1 = bf_lo(q[i][1]) * bf_lo(q[i][1]) + bf_hi(q[i][1]) * bf_hi(q[i][1]) + bf_lo(q[i][3]) * bf_lo(q[i][3]) + bf_hi(q[i][3]) * bf_hi(q[i][3]);
                n0 += __shfl_xor_sync(0xffffffffu, n0, 1); n0 += __shfl_xor_sync(0xffffffffu, n0, 2);
                n1 += __shfl_xor_sync(0xffffffffu, n1, 1); n1 += __shfl_xor_sync(0xffffffffu, n1, 2);
                qm = (n0 != n0 || n1 != n1) ? __int_as_float(0x7f800000) : fmaxf(qm, fmaxf(n0, n1));
            }
            #pragma unroll
            for (int o = 16; o; o >>= 1) qm = fmaxf(qm, __shfl_xor_sync(0xffffffffu, qm, o));
            if (lane == 0) s_misc[warp] = qm;
        }
        bar_arrive(14, 544);
        bar_arrive(8, 608);
        bar_sync(1, 512);
        PROF(3);
        if (tid < 4 * (PADU / 8)) *(uint4*)(sB + S_U + (tid / (PADU / 8)) * ULEN * 2 + (tid % (PADU / 8)) * 16) = make_uint4(0, 0, 0, 0);
        PROF(8);
        mbar_wait(bars + 8 * B_U, 0);
        PROF(14);
        #pragma unroll
        for (int i = 0; i < 2; i++) {
            const int l = 2 * (tid + 512 * i);
            const uint2 r0 = *(const uint2*)(sB + S_W3 + l * 16 + rank * 8), r1 = *(const uint2*)(sB + S_W3 + l * 16 + 16 + rank * 8);
            uint32_t* dst = (uint32_t*)(sB + S_U + (PADU + l) * 2);
            dst[0] = __byte_perm(r0.x, r1.x, 0x5410);
            dst[ULEN / 2] = __byte_perm(r0.x, r1.x, 0x7632);
            dst[ULEN] = __byte_perm(r0.y, r1.y, 0x5410);
            dst[3 * ULEN / 2] = __byte_perm(r0.y, r1.y, 0x7632);
        }
        bar_sync(1, 512);
        #pragma unroll 1
        for (int task = tid; task < 4 * 194; task += 512) {
            const int c = task / 194, i = task % 194;
            const uint4* src = (const uint4*)(sB + S_U + c * ULEN * 2 + (PADU + 8 * i - WPAD - 8) * 2);
            const uint4 v0 = src[0], v1 = src[1], v2 = src[2];
            float x[24];
            const uint32_t vv[12] = {v0.x, v0.y, v0.z, v0.w, v1.x, v1.y, v1.z, v1.w, v2.x, v2.y, v2.z, v2.w};
            #pragma unroll
            for (int k = 0; k < 12; k++) { x[2 * k] = bf_lo(vv[k]); x[2 * k + 1] = bf_hi(vv[k]); }
            float w3[12], w5[8];
            #pragma unroll
            for (int e = 0; e < 12; e++) w3[e] = (x[3 + e] + x[4 + e]) + x[5 + e];
            #pragma unroll
            for (int e = 0; e < 8; e++) w5[e] = w3[4 + e] + (x[6 + e] + x[10 + e]);
            *(uint4*)(sB + S_W3 + c * W2LEN * 2 + i * 16) = make_uint4(pack_bf16(w3[0], w3[1]), pack_bf16(w3[2], w3[3]), pack_bf16(w3[4], w3[5]), pack_bf16(w3[6], w3[7]));
            *(uint4*)(sB + S_W5 + c * W2LEN * 2 + i * 16) = make_uint4(pack_bf16(w5[0], w5[1]), pack_bf16(w5[2], w5[3]), pack_bf16(w5[4], w5[5]), pack_bf16(w5[6], w5[7]));
            if (i < 130) {
                float w7[8], w9[8];
                #pragma unroll
                for (int e = 0; e < 8; e++) { w7[e] = w5[e] + (x[5 + e] + x[11 + e]); w9[e] = w7[e] + (x[4 + e] + x[12 + e]); }
                *(uint4*)(sB + S_W7 + c * W3LEN * 2 + i * 16) = make_uint4(pack_bf16(w7[0], w7[1]), pack_bf16(w7[2], w7[3]), pack_bf16(w7[4], w7[5]), pack_bf16(w7[6], w7[7]));
                *(uint4*)(sB + S_W9 + c * W3LEN * 2 + i * 16) = make_uint4(pack_bf16(w9[0], w9[1]), pack_bf16(w9[2], w9[3]), pack_bf16(w9[4], w9[5]), pack_bf16(w9[6], w9[7]));
            }
        }
        PROF(1);
        bar_sync(9, 608);
        PROF(6);
        {
            const int c = warp >> 2, grp = (warp + c) & 3;
            float acc[4][4];
            #pragma unroll
            for (int i = 0; i < 16; i++) (&acc[0][0])[i] = 0.0f;
            const uint32_t tabc = sBa + S_TAB + c * TABN * 2;
            const int e2 = (g - 2 * t) * 2;
            const uint32_t tD = tabc + ((g & 1) ? (TD1 + CD + 1) : (TD0 + CD)) * 2 - e2;
            const uint32_t tE = tabc + ((g & 1) ? (TE1 + CE + 1) : (TE0 + CE)) * 2 - e2;
            const uint32_t t2 = tabc + (T2B + ((g & 1) ? (T2C + C2 + 1) : C2)) * 2 - e2;
            const uint32_t t3 = tabc + (T3B + ((g & 1) ? (T3C + C3 + 1) : C3)) * 2 - e2;
            const int mi = lane >> 3, r8 = lane & 7;
            const uint32_t ub = sBa + S_U + c * ULEN * 2 + (PADU + 16 * (8 * (mi >> 1) + r8) + 8 * (mi & 1)) * 2 + (4 * grp - 4) * 256;
            #pragma unroll 1
            for (int rho = 0; rho < 8; rho++) {
                uint32_t R[5][3];
                #pragma unroll
                for (int qq = 0; qq < 5; qq++) {
                    if (qq < 4 || rho < 2) {
                        const uint32_t a = tD - 32 * (rho + 8 * qq);
                        R[qq][0] = lds32(a + 16); R[qq][1] = lds32(a); R[qq][2] = lds32(a - 16);
                    } else { R[qq][0] = 0; R[qq][1] = 0; R[qq][2] = 0; }
                }
                #pragma unroll
                for (int jp = 0; jp < 4; jp++) {
                    if (grp == 0 && (jp == 0 || (jp == 1 && rho > 0))) continue;
                    if (jp == 0 && rho >= 2) {
                        uint32_t b[4];
                        ldsm4(b, ub + jp * 512 - rho * 32);
                        mma_bf16(acc[0], R[3][1], R[3][2], R[3][0], R[3][1], b[2], b[3]);
                        continue;
                    }
                    uint32_t b[4];
                    ldsm4(b, ub + jp * 512 - rho * 32);
                    #pragma unroll
                    for (int hh = 0; hh < 2; hh++) {
                        #pragma unroll
                        for (int qq = 0; qq < 5; qq++) {
                            const int jr = 2 * jp + hh + qq - 4;
                            if (jr >= 0 && jr < 4) {
                                if (qq < 4 || rho < 2) mma_bf16(acc[jr], R[qq][1], R[qq][2], R[qq][0], R[qq][1], b[2 * hh], b[2 * hh + 1]);
                            }
                        }
                    }
                }
            }
            if (grp >= 2) {
                uint32_t R[5];
                #pragma unroll
                for (int i = 0; i < 5; i++) R[i] = lds32(tE - 16 * (127 + i));
                #pragma unroll
                for (int kk = 0; kk < 2; kk++) {
                    #pragma unroll
                    for (int jp = 0; jp < 2; jp++) {
                        uint32_t b[4];
                        ldsm4(b, ub + (4 + 2 * jp) * 256 - (64 + kk) * 32);
                        mma_bf16(acc[2 * jp], R[2 * kk + 1], R[2 * kk + 2], R[2 * kk], R[2 * kk + 1], b[0], b[1]);
                        mma_bf16(acc[2 * jp + 1], R[2 * kk + 1], R[2 * kk + 2], R[2 * kk], R[2 * kk + 1], b[2], b[3]);
                    }
                }
            }
            const uint32_t soff = (WPAD + 16 * (8 * (mi >> 1) + r8) + 8 * (mi & 1)) * 2 + grp * 1024;
            if (grp >= 1) {
                #pragma unroll 1
                for (int s = 0; s < 4; s++) {
                    const uint32_t sig = sBa + ((s & 1) ? S_W3 : S_W5) + c * W2LEN * 2 + soff - ((s == 0) ? 32 : (s == 1) ? 0 : 16);
                    uint32_t R[7];
                    #pragma unroll
                    for (int i = 0; i < 7; i++) R[i] = lds32(t2 + s * (T2S * 2) - 16 * (3 + i));
                    #pragma unroll
                    for (int bb = 1; bb <= 4; bb++) {
                        if (2 * grp - bb < 0) continue;
                        uint32_t a[4];
                        ldsm4t(a, sig - bb * 512);
                        #pragma unroll
                        for (int jj = 0; jj < 4; jj++) {
                            const int h = jj + 2 * bb;
                            if (h >= 4 && h <= 9) mma_bf16(acc[jj], a[0], a[1], a[2], a[3], R[h - 3], R[h - 4]);
                        }
                    }
                }
            }
            if (grp >= 2) {
                #pragma unroll 1
                for (int s = 0; s < 2; s++) {
                    const uint32_t sig = sBa + (s ? S_W7 : S_W9) + c * W3LEN * 2 + soff - (s ? 16 : 32);
                    uint32_t R[9];
                    #pragma unroll
                    for (int i = 0; i < 9; i++) R[i] = lds32(t3 + s * (T3S * 2) - 16 * (7 + i));
                    #pragma unroll
                    for (int bb = 3; bb <= 6; bb++) {
                        if (2 * grp - bb < 0) continue;
                        uint32_t a[4];
                        ldsm4t(a, sig - bb * 512);
                        #pragma unroll
                        for (int jj = 0; jj < 4; jj++) {
                            const int h = jj + 2 * bb;
                            if (h >= 8 && h <= 15) mma_bf16(acc[jj], a[0], a[1], a[2], a[3], R[h - 7], R[h - 8]);
                        }
                    }
                }
            }
            __nv_bfloat16* ys = (__nv_bfloat16*)(sB + S_Y + c * 4096);
            #pragma unroll
            for (int jj = 0; jj < 4; jj++) {
                const int A = 8 * (4 * grp + jj) + 2 * t;
                ys[16 * A + g] = __float2bfloat16_rn(acc[jj][0]);
                ys[16 * A + 16 + g] = __float2bfloat16_rn(acc[jj][1]);
                ys[16 * A + g + 8] = __float2bfloat16_rn(acc[jj][2]);
                ys[16 * A + 16 + g + 8] = __float2bfloat16_rn(acc[jj][3]);
            }
        }
        bar_arrive(10, 608);
        PROF(7);
        {
            mbar_wait(bars + 8 * B_ST, 0);
            PROF(9); PROFC(8);
            float qm = 0.0f;
            #pragma unroll
            for (int i = 0; i < 16; i++) qm = fmaxf(qm, s_misc[i]);
            const float vm = s_misc[17];
            const bool fast = (qm * s_misc[16] <= 60.0f * 60.0f) && (vm <= 1.0e12f) && (vm >= 1.0e-12f || vm == 0.0f);
            const uint64_t dVstep = 16ull - (16ull << 32);
            uint8_t* ob = g_oimg + qb * 131072 + hg * 16384 + nh * 8192 + (rowhalf * 8 + wiw * 2) * 128 + g * 16 + 4 * t;
            uint32_t cA = 0xBF00BF00u, cB = 0x00030003u;
            asm volatile("" : "+r"(cA), "+r"(cB));
            #pragma unroll 1
            for (int tile = 0; tile < 2; tile++) {
                uint64_t dK = make_desc(sb + SM_K, 128, 256, 0);
                uint64_t dV = make_desc(sb + SM_V, 128, 32768, 0);
                float o[12], s[32];
                uint32_t p[16], qq[4];
                #pragma unroll
                for (int i = 0; i < 4; i++) qq[i] = tile ? q[1][i] : q[0][i];
                #pragma unroll
                for (int i = 0; i < 12; i++) o[i] = 0.0f;
                #pragma unroll
                for (int i = 0; i < 32; i++) s[i] = 0.0f;
                fence_regs<12>(o);
                fence_regs<32>(s);
                if (fast) {
                    #pragma unroll 1
                    for (int c = 0; c < SEQ / 256; c++) {
                        mbar_wait(bars + 8 * (B_KV + c), 0);
                        wg_fence();
                        wg_qk(s, qq, dK);
                        wg_commit();
                        #pragma unroll
                        for (int u = 0; u < 4; u++) {
                            wg_wait<0>();
                            fence_regs<32>(s);
                            #pragma unroll
                            for (int i = 0; i < 16; i++) {
                                if ((MUFU_MASK >> i) & 1) p[i] = exp_mufu(s[2 * i], s[2 * i + 1]);
                                else p[i] = exp_sw(s[2 * i], s[2 * i + 1], cA, cB);
                            }
                            wg_fence();
                            if (u + 1 < 4) wg_qk(s, qq, dK + (u + 1) * 128);
                            #pragma unroll
                            for (int kk = 0; kk < 4; kk++) wg_pv(o, p + 4 * kk, dV + (u * 4 + kk) * dVstep);
                            wg_commit();
                        }
                        dK += 512;
                        dV += 16 * dVstep;
                    }
                    wg_wait<0>();
                } else {
                    float mx0 = -INFINITY, mx1 = -INFINITY;
                    #pragma unroll 1
                    for (int c = 0; c < SEQ / 64; c++) {
                        mbar_wait(bars + 8 * (B_KV + (c >> 2)), 0);
                        wg_fence();
                        wg_qk(s, qq, dK);
                        wg_commit();
                        wg_wait<0>();
                        fence_regs<32>(s);
                        fence_regs<12>(o);
                        float m0 = mx0, m1 = mx1;
                        #pragma unroll
                        for (int j = 0; j < 8; j++) {
                            m0 = fmaxf(m0, fmaxf(s[4 * j], s[4 * j + 1]));
                            m1 = fmaxf(m1, fmaxf(s[4 * j + 2], s[4 * j + 3]));
                        }
                        m0 = fmaxf(m0, __shfl_xor_sync(0xffffffffu, m0, 1)); m0 = fmaxf(m0, __shfl_xor_sync(0xffffffffu, m0, 2));
                        m1 = fmaxf(m1, __shfl_xor_sync(0xffffffffu, m1, 1)); m1 = fmaxf(m1, __shfl_xor_sync(0xffffffffu, m1, 2));
                        const float c0 = ex2f(mx0 - m0), c1 = ex2f(mx1 - m1);
                        mx0 = m0; mx1 = m1;
                        #pragma unroll
                        for (int j = 0; j < 3; j++) { o[4 * j] *= c0; o[4 * j + 1] *= c0; o[4 * j + 2] *= c1; o[4 * j + 3] *= c1; }
                        #pragma unroll
                        for (int j = 0; j < 8; j++) {
                            p[2 * j] = exp_mufu(s[4 * j] - m0, s[4 * j + 1] - m0);
                            p[2 * j + 1] = exp_mufu(s[4 * j + 2] - m1, s[4 * j + 3] - m1);
                        }
                        wg_fence();
                        #pragma unroll
                        for (int kk = 0; kk < 4; kk++) wg_pv(o, p + 4 * kk, dV + kk * dVstep);
                        wg_commit();
                        wg_wait<0>();
                        dK += 128;
                        dV += 4 * dVstep;
                    }
                }
                fence_regs<12>(o);
                const float i0 = 1.0f / o[4], i1 = 1.0f / o[6];
                uint8_t* b = ob + tile * 4096;
                *(uint32_t*)(b) = pack_bf16(o[0] * i0, o[1] * i0);
                *(uint32_t*)(b + 128) = pack_bf16(o[2] * i1, o[3] * i1);
                *(uint32_t*)(b + 2048) = pack_bf16(o[8] * i0, o[9] * i0);
                *(uint32_t*)(b + 2048 + 128) = pack_bf16(o[10] * i1, o[11] * i1);
            }
        }
        PROF(10); PROFC(9);
        bar_arrive(12, 544);

        {
            float acc[16];
            #pragma unroll
            for (int i = 0; i < 16; i++) acc[i] = 0.0f;
            fence_regs<16>(acc);
            const uint64_t dA = make_desc(sb + SM_A + rowhalf * 1024, 2048, 128, 0);
            const uint64_t dB = make_desc(sb + SM_B + nh * 64, 16, 1024, 1);
            mbar_wait(bars + 8 * B_WO, 0);
            #pragma unroll 1
            for (int i = 0; i < 8; i++) {
                const int src = (hg + i) & 7;
                mbar_wait(bars + 8 * (B_O + src), 0);
                wg_fence();
                #pragma unroll
                for (int kk = 0; kk < 4; kk++) wg_ss32(acc, dA + src * 1024 + kk * 256, dB + (src * 4 + kk) * 128);
                wg_commit();
            }
            wg_wait<0>();
            fence_regs<16>(acc);
            PROF(12);
            const int row = qb * 128 + rowhalf * 64 + wiw * 16 + g;
            uint32_t* o32 = (uint32_t*)(P.out + (size_t)row * 1024 + hg * 64 + nh * 32 + 2 * t);
            #pragma unroll
            for (int j = 0; j < 4; j++) {
                o32[4 * j] = pack_bf16(acc[4 * j], acc[4 * j + 1]);
                o32[4 * j + 8 * 512] = pack_bf16(acc[4 * j + 2], acc[4 * j + 3]);
            }
        }
        PROF(13);
    }
}

typedef CUresult (*EncodeFn)(CUtensorMap*, CUtensorMapDataType, cuuint32_t, void*, const cuuint64_t*, const cuuint64_t*,
                             const cuuint32_t*, const cuuint32_t*, CUtensorMapInterleave, CUtensorMapSwizzle,
                             CUtensorMapL2promotion, CUtensorMapFloatOOBfill);

void make_map(EncodeFn fn, CUtensorMap* m, const void* ptr, uint64_t inner, uint64_t outer, uint32_t box_in, uint32_t box_out, CUtensorMapSwizzle swz) {
    cuuint64_t dims[2] = {inner, outer};
    cuuint64_t strides[1] = {inner * 2};
    cuuint32_t box[2] = {box_in, box_out};
    cuuint32_t es[2] = {1, 1};
    fn(m, CU_TENSOR_MAP_DATA_TYPE_BFLOAT16, 2, const_cast<void*>(ptr), dims, strides, box, es, CU_TENSOR_MAP_INTERLEAVE_NONE, swz,
       CU_TENSOR_MAP_L2_PROMOTION_L2_128B, CU_TENSOR_MAP_FLOAT_OOB_FILL_NONE);
}

}

extern "C" void kernel_launch(void* const* d_in, const int* in_sizes, int n_in, void* d_out, int out_size) {
    (void)in_sizes; (void)n_in; (void)out_size;
    static EncodeFn fn = nullptr;
    if (!fn) {
        void* p = nullptr;
        cudaDriverEntryPointQueryResult qr;
        cudaGetDriverEntryPoint("cuTensorMapEncodeTiled", &p, cudaEnableDefault, &qr);
        fn = (EncodeFn)p;
        cudaFuncSetAttribute(fused_kernel, cudaFuncAttributeMaxDynamicSharedMemorySize, SM_ALLOC);
    }
    CUtensorMap tx, twq, two, twk, twv, tu;
    {
        cuuint64_t dims[3] = {64, 2048, 8};
        cuuint64_t strides[2] = {1024, 128};
        cuuint32_t box[3] = {64, 128, 4};
        cuuint32_t es[3] = {1, 1, 1};
        fn(&tx, CU_TENSOR_MAP_DATA_TYPE_BFLOAT16, 3, d_in[0], dims, strides, box, es, CU_TENSOR_MAP_INTERLEAVE_NONE, CU_TENSOR_MAP_SWIZZLE_128B,
           CU_TENSOR_MAP_L2_PROMOTION_L2_128B, CU_TENSOR_MAP_FLOAT_OOB_FILL_NONE);
    }
    make_map(fn, &tu, d_in[5], 512, 2048, 8, 256, CU_TENSOR_MAP_SWIZZLE_NONE);
    make_map(fn, &twq, d_in[1], 512, 512, 64, 256, CU_TENSOR_MAP_SWIZZLE_128B);
    make_map(fn, &twk, d_in[2], 16, 512, 8, 256, CU_TENSOR_MAP_SWIZZLE_NONE);
    make_map(fn, &twv, d_in[3], 16, 512, 8, 256, CU_TENSOR_MAP_SWIZZLE_NONE);
    make_map(fn, &two, d_in[4], 512, 512, 64, 256, CU_TENSOR_MAP_SWIZZLE_128B);
    Params P;
    P.u = (const __nv_bfloat16*)d_in[5];
    P.lar = (const __nv_bfloat16*)d_in[6];
    P.aim = (const __nv_bfloat16*)d_in[7];
    P.cre = (const __nv_bfloat16*)d_in[8];
    P.cim = (const __nv_bfloat16*)d_in[9];
    P.logdt = (const __nv_bfloat16*)d_in[10];
    P.dskip = (const __nv_bfloat16*)d_in[11];
    P.out = (__nv_bfloat16*)d_out;
    fused_kernel<<<NCTA, NTHR, SM_ALLOC>>>(tx, twq, two, twk, twv, tu, P);
}
```

```cpp
#include <cuda_runtime.h>
#include <cuda_bf16.h>
#include <cuda_fp16.h>
#include <cuda.h>
#include <stdint.h>

namespace {

constexpr int SEQ = 2048;
constexpr int NCTA = 128, NTHR = 640;

constexpr int SM_A = 0;
constexpr int SM_WQ = 65536;
constexpr int SM_K = 0, SM_V = 65536;
constexpr int SM_B = 132096;
constexpr int SM_WKV = SM_B + 65536;

constexpr int PADU = 288, ULEN = PADU + 2048;
constexpr int WPAD = 16, W2LEN = WPAD + 1536, W3LEN = WPAD + 1024;
constexpr int TABN = 2240;
constexpr int S_U = 0;
constexpr int S_W3 = S_U + 4 * ULEN * 2;
constexpr int S_W5 = S_W3 + 4 * W2LEN * 2;
constexpr int S_W7 = S_W5 + 4 * W2LEN * 2;
constexpr int S_W9 = S_W7 + 4 * W3LEN * 2;
constexpr int S_TAB = S_W9 + 4 * W3LEN * 2;
constexpr int S_KC = 214016 - SM_B;
constexpr int S_Y = S_KC;
constexpr int SM_BAR = SM_B + S_KC + 16384;
constexpr int SM_TOTAL = SM_BAR + 1024;
constexpr int SM_ALLOC = SM_TOTAL + 1024;
static_assert(SM_V + 65536 + 256 <= SM_B && SM_ALLOC <= 232448 && S_TAB + 4 * TABN * 2 <= S_KC && SM_WKV + 16384 <= SM_B + S_KC, "smem map");

constexpr int TD0 = 0, TD1 = 560, CD = 544;
constexpr int TE0 = 1120, TE1 = 1168, CE = 1056;
constexpr int T2B = 1216, T2S = 160, T2C = 80, C2 = 80;
constexpr int T3B = 1856, T3S = 192, T3C = 96, C3 = 144;

constexpr int rne8(int t) {
    if (t < 256) return t;
    int sh = 0;
    while ((t >> sh) >= 256) sh++;
    int q = t >> sh, rem = t & ((1 << sh) - 1), half = 1 << (sh - 1);
    if (rem > half || (rem == half && (q & 1))) q++;
    return q << sh;
}
constexpr int kcidx(int p) {
    if (p < 256) return (p >> 3) * 24 + (p & 7);
    if (p < 512) return ((p - 256) >> 3) * 24 + 8 + (((p - 256) & 7) >> 1);
    if (p < 1024) { int q = p - 512, hi = q >> 8, rem = q & 255; return (rem >> 3) * 24 + 12 + 2 * hi + ((rem & 7) >> 2); }
    if (p < 2048) { int q = p - 1024; return ((q & 255) >> 3) * 24 + 16 + (q >> 8); }
    return 20;
}
constexpr int KC_ZERO = 23;
constexpr int tab_dense(int t) { return (t >= 0 && t <= 514) ? kcidx(rne8(t)) : KC_ZERO; }
constexpr int tab_extra(int t) { return (t >= 1027 && t <= 1028) ? kcidx(1024) : KC_ZERO; }
constexpr int tab_2(int s, int lag) { return (lag >= 32 && lag <= 63) ? kcidx(s == 0 ? 16 * (lag + 1) : 16 * lag + 4 * s) : KC_ZERO; }
constexpr int tab_3(int s, int lag) { return (lag >= 64 && lag <= 127) ? kcidx(s == 0 ? 16 * (lag + 1) : 16 * lag + 8) : KC_ZERO; }
struct TabMap {
    uint16_t v[TABN];
    constexpr TabMap() : v{} {
        for (int i = 0; i < 560; i++) { v[TD0 + i] = tab_dense(CD - i); v[TD1 + i] = tab_dense(CD + 1 - i); }
        for (int i = 0; i < 48; i++) { v[TE0 + i] = tab_extra(CE - i); v[TE1 + i] = tab_extra(CE + 1 - i); }
        for (int s = 0; s < 4; s++)
            for (int i = 0; i < T2C; i++) { v[T2B + s * T2S + i] = tab_2(s, C2 - i); v[T2B + s * T2S + T2C + i] = tab_2(s, C2 + 1 - i); }
        for (int s = 0; s < 2; s++)
            for (int i = 0; i < T3C; i++) { v[T3B + s * T3S + i] = tab_3(s, C3 - i); v[T3B + s * T3S + T3C + i] = tab_3(s, C3 + 1 - i); }
    }
};
__device__ const __align__(16) TabMap g_tabmap = TabMap();

__device__ __align__(1024) uint8_t g_kimg[65536];
__device__ __align__(1024) uint8_t g_vimg[65536 + 256];
__device__ __align__(1024) uint8_t g_oimg[16 * 131072];
__device__ unsigned long long g_flag_kv[64];
__device__ unsigned g_flag_o[128];
__device__ unsigned g_epoch;
__device__ unsigned g_done;

#define PROF(i) do {} while (0)
#define PROF2(i) do {} while (0)
#define PROFC(i) do {} while (0)
#define PROF3(i) do {} while (0)

__device__ __forceinline__ uint32_t smem_u32(const void* p) { return (uint32_t)__cvta_generic_to_shared(p); }
__device__ __forceinline__ void mbar_init(uint32_t bar, uint32_t cnt) { asm volatile("mbarrier.init.shared::cta.b64 [%0], %1;" :: "r"(bar), "r"(cnt) : "memory"); }
__device__ __forceinline__ void mbar_expect_tx(uint32_t bar, uint32_t bytes) {
    asm volatile("mbarrier.arrive.expect_tx.shared::cta.b64 _, [%0], %1;" :: "r"(bar), "r"(bytes) : "memory"); }
__device__ __forceinline__ void mbar_wait(uint32_t bar, uint32_t parity) {
    uint32_t ok = 0;
    for (int it = 0; it < (1 << 22) && !ok; it++) {
        asm volatile("{ .reg .pred p; mbarrier.try_wait.parity.shared::cta.b64 p, [%1], %2; selp.u32 %0, 1, 0, p; }"
                     : "=r"(ok) : "r"(bar), "r"(parity) : "memory");
    }
}
__device__ __forceinline__ void tma_2d(uint32_t dst, const CUtensorMap* map, int c0, int c1, uint32_t bar) {
    asm volatile("cp.async.bulk.tensor.2d.shared::cluster.global.mbarrier::complete_tx::bytes [%0], [%1, {%3, %4}], [%2];"
                 :: "r"(dst), "l"((uint64_t)map), "r"(bar), "r"(c0), "r"(c1) : "memory");
}
__device__ __forceinline__ void tma_2d_mc(uint32_t dst, const CUtensorMap* map, int c0, int c1, uint32_t bar) {
    asm volatile("cp.async.bulk.tensor.2d.shared::cluster.global.mbarrier::complete_tx::bytes.multicast::cluster [%0], [%1, {%3, %4}], [%2], %5;"
                 :: "r"(dst), "l"((uint64_t)map), "r"(bar), "r"(c0), "r"(c1), "h"((uint16_t)3) : "memory");
}
__device__ __forceinline__ void bulk_g2s_mc(uint32_t dst, const void* src, uint32_t bytes, uint32_t bar) {
    asm volatile("cp.async.bulk.shared::cluster.global.mbarrier::complete_tx::bytes.multicast::cluster [%0], [%1], %2, [%3], %4;"
                 :: "r"(dst), "l"((uint64_t)src), "r"(bytes), "r"(bar), "h"((uint16_t)3) : "memory");
}
__device__ __forceinline__ void pair_sync(uint32_t bar, uint32_t peer) {
    uint32_t ra;
    asm volatile("mapa.shared::cluster.u32 %0, %1, %2;" : "=r"(ra) : "r"(bar), "r"(peer));
    asm volatile("mbarrier.arrive.shared::cluster.b64 _, [%0];" :: "r"(ra) : "memory");
    asm volatile("mbarrier.arrive.shared::cta.b64 _, [%0];" :: "r"(bar) : "memory");
    uint32_t ok = 0;
    for (int it = 0; it < (1 << 22) && !ok; it++) {
        asm volatile("{ .reg .pred p; mbarrier.try_wait.parity.shared::cta.b64 p, [%1], 0; selp.u32 %0, 1, 0, p; }"
                     : "=r"(ok) : "r"(bar) : "memory");
    }
}
__device__ __forceinline__ void fence_async_all() { asm volatile("fence.proxy.async.global;" ::: "memory"); }
__device__ __forceinline__ void fence_async_smem() { asm volatile("fence.proxy.async.shared::cta;" ::: "memory"); }
__device__ __forceinline__ unsigned ld_acquire(const unsigned* p) {
    unsigned v; asm volatile("ld.acquire.gpu.global.u32 %0, [%1];" : "=r"(v) : "l"(p) : "memory"); return v; }
__device__ __forceinline__ void st_release(unsigned* p, unsigned v) { asm volatile("st.release.gpu.global.u32 [%0], %1;" :: "l"(p), "r"(v) : "memory"); }
__device__ __forceinline__ void wait_flag(const unsigned* p, unsigned epoch) {
    for (int it = 0; it < (1 << 22); it++) { if (ld_acquire(p) == epoch) break; }
}
__device__ __forceinline__ unsigned long long ld_acquire64(const unsigned long long* p) {
    unsigned long long v; asm volatile("ld.acquire.gpu.global.u64 %0, [%1];" : "=l"(v) : "l"(p) : "memory"); return v; }
__device__ __forceinline__ void st_release64(unsigned long long* p, unsigned long long v) { asm volatile("st.release.gpu.global.u64 [%0], %1;" :: "l"(p), "l"(v) : "memory"); }
__device__ __forceinline__ float wait_flag64(const unsigned long long* p, unsigned epoch) {
    unsigned long long v = 0;
    for (int it = 0; it < (1 << 22); it++) { v = ld_acquire64(p); if ((unsigned)(v >> 32) == epoch) break; }
    return __uint_as_float((unsigned)v);
}
__device__ __forceinline__ void tma_3d_mc(uint32_t dst, const CUtensorMap* map, int c0, int c1, int c2, uint32_t bar) {
    asm volatile("cp.async.bulk.tensor.3d.shared::cluster.global.mbarrier::complete_tx::bytes.multicast::cluster [%0], [%1, {%3, %4, %5}], [%2], %6;"
                 :: "r"(dst), "l"((uint64_t)map), "r"(bar), "r"(c0), "r"(c1), "r"(c2), "h"((uint16_t)3) : "memory");
}
__device__ __forceinline__ void bar_sync(int id, int n) { asm volatile("bar.sync %0, %1;" :: "r"(id), "r"(n) : "memory"); }
__device__ __forceinline__ void bar_arrive(int id, int n) { asm volatile("bar.arrive %0, %1;" :: "r"(id), "r"(n) : "memory"); }
__device__ __forceinline__ void mbar_arrive(uint32_t bar) { asm volatile("mbarrier.arrive.shared::cta.b64 _, [%0];" :: "r"(bar) : "memory"); }

__device__ __forceinline__ uint64_t make_desc(uint32_t saddr, uint32_t lbo, uint32_t sbo, uint32_t swz) {
    uint64_t d = 0;
    d |= (uint64_t)((saddr & 0x3FFFF) >> 4);
    d |= (uint64_t)((lbo >> 4) & 0x3FFF) << 16;
    d |= (uint64_t)((sbo >> 4) & 0x3FFF) << 32;
    d |= (uint64_t)swz << 62;
    return d;
}
__device__ __forceinline__ void wg_fence() { asm volatile("wgmma.fence.sync.aligned;" ::: "memory"); }
__device__ __forceinline__ void wg_commit() { asm volatile("wgmma.commit_group.sync.aligned;" ::: "memory"); }
template<int N> __device__ __forceinline__ void wg_wait() { asm volatile("wgmma.wait_group.sync.aligned %0;" :: "n"(N) : "memory"); }
#define A4(d, o) "+f"(d[o + 0]), "+f"(d[o + 1]), "+f"(d[o + 2]), "+f"(d[o + 3])
#define A16(d, o) A4(d, o), A4(d, o + 4), A4(d, o + 8), A4(d, o + 12)

__device__ __forceinline__ void wg_pv(float* d, const uint32_t* a, uint64_t desc) {
    asm volatile("wgmma.mma_async.sync.aligned.m64n24k16.f32.bf16.bf16 {%0,%1,%2,%3,%4,%5,%6,%7,%8,%9,%10,%11}, {%12,%13,%14,%15}, %16, 1, 1, 1, 1;"
                 : A4(d, 0), A4(d, 4), A4(d, 8) : "r"(a[0]), "r"(a[1]), "r"(a[2]), "r"(a[3]), "l"(desc));
}
__device__ __forceinline__ void wg_qk(float* d, const uint32_t* a, uint64_t desc) {
    asm volatile("wgmma.mma_async.sync.aligned.m64n64k16.f32.bf16.bf16 {%0,%1,%2,%3,%4,%5,%6,%7,%8,%9,%10,%11,%12,%13,%14,%15,%16,%17,%18,%19,%20,%21,%22,%23,%24,%25,%26,%27,%28,%29,%30,%31}, {%32,%33,%34,%35}, %36, 0, 1, 1, 0;"
                 : A16(d, 0), A16(d, 16) : "r"(a[0]), "r"(a[1]), "r"(a[2]), "r"(a[3]), "l"(desc));
}
__device__ __forceinline__ void wg_ss32(float* d, uint64_t da, uint64_t db) {
    asm volatile("wgmma.mma_async.sync.aligned.m64n32k16.f32.bf16.bf16 {%0,%1,%2,%3,%4,%5,%6,%7,%8,%9,%10,%11,%12,%13,%14,%15}, %16, %17, 1, 1, 1, 0, 1;"
                 : A16(d, 0) : "l"(da), "l"(db));
}
__device__ __forceinline__ void wg_ss16(float* d, uint64_t da, uint64_t db) {
    asm volatile("wgmma.mma_async.sync.aligned.m64n16k16.f32.bf16.bf16 {%0,%1,%2,%3,%4,%5,%6,%7}, %8, %9, 1, 1, 1, 0, 1;"
                 : A4(d, 0), A4(d, 4) : "l"(da), "l"(db));
}
template<int N> __device__ __forceinline__ void fence_regs(float* r) {
    #pragma unroll
    for (int i = 0; i < N; i++) asm volatile("" : "+f"(r[i]) :: "memory");
}
__device__ __forceinline__ void mma_bf16(float* d, uint32_t a0, uint32_t a1, uint32_t a2, uint32_t a3, uint32_t b0, uint32_t b1) {
    asm volatile("mma.sync.aligned.m16n8k16.row.col.f32.bf16.bf16.f32 {%0,%1,%2,%3}, {%4,%5,%6,%7}, {%8,%9}, {%0,%1,%2,%3};"
                 : "+f"(d[0]), "+f"(d[1]), "+f"(d[2]), "+f"(d[3]) : "r"(a0), "r"(a1), "r"(a2), "r"(a3), "r"(b0), "r"(b1));
}
__device__ __forceinline__ void mma_f16(float* d, const uint32_t* a, uint32_t b0, uint32_t b1) {
    asm volatile("mma.sync.aligned.m16n8k16.row.col.f32.f16.f16.f32 {%0,%1,%2,%3}, {%4,%5,%6,%7}, {%8,%9}, {%0,%1,%2,%3};"
                 : "+f"(d[0]), "+f"(d[1]), "+f"(d[2]), "+f"(d[3]) : "r"(a[0]), "r"(a[1]), "r"(a[2]), "r"(a[3]), "r"(b0), "r"(b1));
}
__device__ __forceinline__ void ldsm4(uint32_t* r, uint32_t addr) {
    asm volatile("ldmatrix.sync.aligned.m8n8.x4.shared.b16 {%0,%1,%2,%3}, [%4];" : "=r"(r[0]), "=r"(r[1]), "=r"(r[2]), "=r"(r[3]) : "r"(addr) : "memory");
}
__device__ __forceinline__ void ldsm4t(uint32_t* r, uint32_t addr) {
    asm volatile("ldmatrix.sync.aligned.m8n8.x4.trans.shared.b16 {%0,%1,%2,%3}, [%4];" : "=r"(r[0]), "=r"(r[1]), "=r"(r[2]), "=r"(r[3]) : "r"(addr) : "memory");
}
__device__ __forceinline__ uint32_t lds32(uint32_t addr) { uint32_t v; asm volatile("ld.shared.u32 %0, [%1];" : "=r"(v) : "r"(addr) : "memory"); return v; }
__device__ __forceinline__ float ex2f(float x) { float r; asm("ex2.approx.ftz.f32 %0, %1;" : "=f"(r) : "f"(x)); return r; }
__device__ __forceinline__ uint32_t pack_bf16(float lo, float hi) { uint32_t r; asm("cvt.rn.bf16x2.f32 %0, %1, %2;" : "=r"(r) : "f"(hi), "f"(lo)); return r; }
__device__ __forceinline__ uint32_t pack_f16(float lo, float hi) { uint32_t r; asm("cvt.rn.f16x2.f32 %0, %1, %2;" : "=r"(r) : "f"(hi), "f"(lo)); return r; }
__device__ __forceinline__ float bf_lo(uint32_t v) { return __uint_as_float(v << 16); }
__device__ __forceinline__ float bf_hi(uint32_t v) { return __uint_as_float(v & 0xFFFF0000u); }
__device__ __forceinline__ float bf_round(float x) { return __bfloat162float(__float2bfloat16_rn(x)); }

__device__ __forceinline__ uint32_t exp_mufu(float x0, float x1) { return pack_bf16(ex2f(x0), ex2f(x1)); }
#define SW_MAGIC (256.0f + 127.0f - 0.598938f)
__device__ __forceinline__ uint32_t exp_sw(float x0, float x1, uint32_t cA, uint32_t cB) {
    float t0 = x0 + SW_MAGIC, t1 = x1 + SW_MAGIC;
    uint32_t L, mh, ec, r;
    asm("prmt.b32 %0, %1, %2, 0x6521;" : "=r"(L) : "r"(__float_as_uint(t0)), "r"(__float_as_uint(t1)));
    asm("lop3.b32 %0, %1, 0x007F007F, %2, 0xEA;" : "=r"(mh) : "r"(L), "r"(cA));
    asm("lop3.b32 %0, %1, 0x7F807F80, %2, 0xEA;" : "=r"(ec) : "r"(L), "r"(cB));
    asm("fma.rn.bf16x2 %0, %1, %2, %3;" : "=r"(r) : "r"(L), "r"(mh), "r"(ec));
    return r;
}
constexpr uint32_t MUFU_MASK = 0x4949;

struct cf { float x, y; };
__device__ __forceinline__ cf cmul(cf a, cf b) { cf r; r.x = a.x * b.x - a.y * b.y; r.y = a.x * b.y + a.y * b.x; return r; }
__device__ __forceinline__ cf cexp_p(float a2, float b, float p) {
    float e = ex2f(a2 * p);
    float ph = b * p;
    ph -= (ph + 12582912.0f) - 12582912.0f;
    float ang = ph * 6.283185307f;
    cf r; r.x = e * __cosf(ang); r.y = e * __sinf(ang);
    return r;
}
__device__ __forceinline__ uint32_t h2_cmul(uint32_t w, uint32_t wsw, uint32_t e) {
    __half2 hw = *(__half2*)&w, hs = *(__half2*)&wsw, he = *(__half2*)&e;
    __half2 r = __hfma2(hs, __high2half2(he), __hmul2(hw, __low2half2(he)));
    return *(uint32_t*)&r;
}

template<bool B> struct BoolC { static constexpr bool value = B; };
struct Params {
    const __nv_bfloat16 *u, *lar, *aim, *cre, *cim, *logdt, *dskip;
    __nv_bfloat16* out;
};

constexpr int B_O = 0, B_KV = 8, B_WO = 12, B_U = 13, B_ST = 14, B_H = 15, B_X = 18, B_WQ = 20;

__device__ __forceinline__ void helper_role(const Params& P, uint8_t* sp, unsigned epoch) {
    const int tid = threadIdx.x - 544;
    const int d0 = blockIdx.x * 4;
    uint8_t* sB = sp + SM_B;
    const uint2 dsk = __ldg((const uint2*)(P.dskip + d0));
    asm volatile("barrier.cluster.wait.aligned;" ::: "memory");
    {
        const int hg = blockIdx.x & 7;
        if (hg < 4 && tid < 32) {
            bar_sync(3, 160);
            if (tid == 0) {
                const float* s_misc = (const float*)(sp + SM_BAR + 256);
                const float st = fmaxf(fmaxf(s_misc[20], s_misc[21]), fmaxf(s_misc[22], s_misc[23]));
                st_release64(&g_flag_kv[((blockIdx.x >> 3) * 2 + (hg & 1)) * 2 + (hg >> 1)], ((unsigned long long)epoch << 32) | __float_as_uint(st));
            }
            __syncwarp();
        }
    }
    PROF2(2);
    bar_sync(10, 608);
    {
        uint32_t dd[4] = {__byte_perm(dsk.x, 0, 0x1010), __byte_perm(dsk.x, 0, 0x3232), __byte_perm(dsk.y, 0, 0x1010), __byte_perm(dsk.y, 0, 0x3232)};
        #pragma unroll 2
        for (int pi = tid; pi < 1024; pi += 96) {
            const int l = 2 * pi;
            uint32_t r[4];
            #pragma unroll
            for (int cc = 0; cc < 4; cc++) {
                const uint32_t y2 = *(const uint32_t*)(sB + S_Y + cc * 4096 + l * 2);
                const uint32_t u2 = *(const uint32_t*)(sB + S_U + cc * ULEN * 2 + (PADU + l) * 2);
                __nv_bfloat162 pr = __hmul2(*(const __nv_bfloat162*)&u2, *(const __nv_bfloat162*)&dd[cc]);
                __nv_bfloat162 sm = __hadd2(*(const __nv_bfloat162*)&y2, pr);
                r[cc] = *(uint32_t*)&sm;
            }
            *(uint2*)(P.out + (size_t)l * 1024 + 512 + d0) = make_uint2(__byte_perm(r[0], r[1], 0x5410), __byte_perm(r[2], r[3], 0x5410));
            *(uint2*)(P.out + (size_t)(l + 1) * 1024 + 512 + d0) = make_uint2(__byte_perm(r[0], r[1], 0x7632), __byte_perm(r[2], r[3], 0x7632));
        }
    }
    bar_arrive(11, 128);
    PROF2(4);
}

__global__ void __cluster_dims__(2, 1, 1) __launch_bounds__(NTHR, 1)
fused_kernel(const __grid_constant__ CUtensorMap tm_x, const __grid_constant__ CUtensorMap tm_wq,
             const __grid_constant__ CUtensorMap tm_wo, const __grid_constant__ CUtensorMap tm_wk,
             const __grid_constant__ CUtensorMap tm_wv, const __grid_constant__ CUtensorMap tm_u, const Params P) {
    extern __shared__ uint8_t smem_raw[];
    const uint32_t sb = (smem_u32(smem_raw) + 1023u) & ~1023u;
    uint8_t* sp = smem_raw + (sb - smem_u32(smem_raw));

    const int tid = threadIdx.x, warp = tid >> 5, lane = tid & 31, wg = tid >> 7, wiw = warp & 3;
    const int g = lane >> 2, t = lane & 3;
    const int qb = blockIdx.x >> 3, hg = blockIdx.x & 7;
    const uint32_t rank = blockIdx.x & 1;
    const int rowhalf = wg & 1, nh = wg >> 1;
    const bool kv_cta = hg < 4;
    const int kv_sel = hg >> 1;
    const bool kv_wg = kv_cta && (wg == (hg & 1));

    const uint32_t bars = sb + SM_BAR;
    float* s_misc = (float*)(sp + SM_BAR + 256);
    const CUtensorMap* tm_kv = kv_sel ? &tm_wv : &tm_wk;

    PROF(0);
    unsigned short p_lar = 0, p_aim = 0, p_cre = 0, p_cim = 0, p_ldt = 0;
    if (wg < 4) {
        const int n = (blockIdx.x * 4 + wg) * 128 + (tid & 127);
        p_lar = __ldg((const unsigned short*)P.lar + n);
        p_aim = __ldg((const unsigned short*)P.aim + n);
        p_cre = __ldg((const unsigned short*)P.cre + n);
        p_cim = __ldg((const unsigned short*)P.cim + n);
        p_ldt = __ldg((const unsigned short*)P.logdt + blockIdx.x * 4 + wg);
    } else if (warp == 16) {
        PROF3(5);
        if (lane == 0) {
            asm volatile("prefetch.tensormap [%0];" :: "l"((uint64_t)&tm_x) : "memory");
            asm volatile("prefetch.tensormap [%0];" :: "l"((uint64_t)tm_kv) : "memory");
            asm volatile("prefetch.tensormap [%0];" :: "l"((uint64_t)&tm_wq) : "memory");
            mbar_init(bars + 8 * B_X, 1);
            mbar_init(bars + 8 * B_X + 8, 1);
            asm volatile("fence.mbarrier_init.release.cluster;" ::: "memory");
            mbar_expect_tx(bars + 8 * B_X, 65536u + (kv_cta ? 8192u : 0u));
            mbar_expect_tx(bars + 8 * B_X + 8, 65536u + (kv_cta ? 8192u : 0u));
        }
        __syncwarp();
        PROF3(6);
    }
    asm volatile("barrier.cluster.arrive.relaxed.aligned;" ::: "memory");
    const unsigned epoch = *(volatile unsigned*)&g_epoch + 1u;
    if (warp > 16) {
        if (lane == 0) {
            for (int i = warp - 17; i < B_X; i += 3) {
                mbar_init(bars + 8 * i, i >= B_H ? 2 : 1);
                if (i <= B_U) mbar_expect_tx(bars + 8 * i, i < B_KV + 2 ? 16384u : i == B_KV + 2 ? 32768u : i <= B_WO ? 65536u : 32768u);
            }
            asm volatile("fence.mbarrier_init.release.cluster;" ::: "memory");
            fence_async_smem();
        } else if (warp == 19) {
            asm volatile("prefetch.global.L2 [%0];" :: "l"((const char*)g_tabmap.v + (lane - 1) * 128));
            if (lane < 5) asm volatile("prefetch.global.L2 [%0];" :: "l"((const char*)g_tabmap.v + (lane + 30) * 128));
        }
        __syncwarp();
    }
    asm volatile("barrier.cluster.wait.aligned;" ::: "memory");
    PROF(5);
    if (warp == 16 && lane == 0) {
        tma_3d_mc(sb + (rank ? SM_A : SM_B), &tm_x, 0, qb * 128, rank * 4, bars + 8 * (B_X + rank));
        if (kv_cta) {
            #pragma unroll
            for (int i = 0; i < 4; i++) tma_2d(sb + SM_WKV + i * 4096, tm_kv, (i >> 1) * 8, (i & 1) * 256, bars + 8 * (B_X + (i & 1)));
        }
        mbar_init(bars + 8 * B_WQ, 1);
        asm volatile("fence.mbarrier_init.release.cluster;" ::: "memory");
        fence_async_smem();
        mbar_expect_tx(bars + 8 * B_WQ, 65536u);
        tma_2d(sb + SM_WQ, &tm_wq, hg * 64, 0, bars + 8 * B_WQ);
        tma_2d(sb + SM_WQ + 32768, &tm_wq, hg * 64, 256, bars + 8 * B_WQ);
    }
    __syncwarp();
    asm volatile("barrier.cluster.arrive.relaxed.aligned;" ::: "memory");

    if (warp == 16) {
        if (lane == 0) {
            asm volatile("prefetch.tensormap [%0];" :: "l"((uint64_t)&tm_u) : "memory");
            asm volatile("prefetch.tensormap [%0];" :: "l"((uint64_t)&tm_wo) : "memory");
        }
        asm volatile("barrier.cluster.wait.aligned;" ::: "memory");
        PROF3(10);
        bar_sync(13, 544);
        if (lane == 0) {
            pair_sync(bars + 8 * (B_H + 2), rank ^ 1);
            #pragma unroll
            for (int i = 0; i < 4; i++) tma_2d_mc(sb + SM_B + S_W3 + (rank * 4 + i) * 4096, &tm_u, (blockIdx.x >> 1) * 8, (rank * 4 + i) * 256, bars + 8 * B_U);
        }
        bar_sync(14, 544);
        if (lane == 0) pair_sync(bars + 8 * B_H, rank ^ 1);
        __syncwarp();
        PROF3(11);
        *(uint2*)(sp + SM_V + 32768 + lane * 8) = make_uint2(0x3F803F80u, 0x3F803F80u);
        fence_async_smem();
        float km = wait_flag64(&g_flag_kv[2 * lane], epoch);
        float vm = wait_flag64(&g_flag_kv[2 * lane + 1], epoch);
        __syncwarp();
        PROF3(12);
        if (lane == 0) {
            fence_async_all();
            #pragma unroll
            for (int i = 0; i < 4; i++) {
                const uint32_t k0 = i == 0 ? 0 : 128u << i, nk = i == 0 ? 256 : 128u << i;
                const uint32_t bar = bars + 8 * (B_KV + i);
                if (rank == 0) bulk_g2s_mc(sb + SM_K + k0 * 32, g_kimg + k0 * 32, nk * 32, bar);
                else {
                    bulk_g2s_mc(sb + SM_V + k0 * 16, g_vimg + k0 * 16, nk * 16, bar);
                    bulk_g2s_mc(sb + SM_V + 65792 - (k0 + nk) * 16, g_vimg + 65792 - (k0 + nk) * 16, nk * 16, bar);
                }
            }
        }
        #pragma unroll
        for (int o = 16; o; o >>= 1) { km = fmaxf(km, __shfl_xor_sync(0xffffffffu, km, o)); vm = fmaxf(vm, __shfl_xor_sync(0xffffffffu, vm, o)); }
        if (lane == 0) { s_misc[16] = km; s_misc[17] = vm; mbar_arrive(bars + 8 * B_ST); }
        PROF3(13);
        bar_sync(11, 128);
        if (lane < 2) { fence_async_smem(); tma_2d(sb + SM_B + lane * 32768, &tm_wo, hg * 64, lane * 256, bars + 8 * B_WO); }
        bar_sync(12, 544);
        if (lane == 0) {
            st_release(&g_flag_o[blockIdx.x], epoch);
            pair_sync(bars + 8 * (B_H + 1), rank ^ 1);
        }
        __syncwarp();
        PROF3(14);
        if (lane < 4) {
            const int src = 2 * lane + rank;
            wait_flag(&g_flag_o[qb * 8 + src], epoch);
            fence_async_all();
            bulk_g2s_mc(sb + SM_A + src * 16384, g_oimg + qb * 131072 + src * 16384, 16384, bars + 8 * (B_O + src));
        }
        __syncwarp();
        PROF3(15);
        if (lane == 0) {
            const unsigned prev = atomicAdd(&g_done, 1u);
            if (prev == NCTA - 1) {
                g_done = 0;
                __threadfence();
                *(volatile unsigned*)&g_epoch = epoch;
            }
        }
    } else if (wg == 4) {
        helper_role(P, sp, epoch);
    } else {
        uint8_t* sB = sp + SM_B;
        const uint32_t sBa = sb + SM_B;
        {
            const int c = wg;
            const float dt = bf_round(expf(bf_lo(p_ldt)));
            const float are = -bf_round(expf(bf_lo(p_lar))) * dt;
            const float aim = bf_lo(p_aim) * dt;
            float cr = 2.0f * (bf_lo(p_cre) * dt);
            float ci = 2.0f * (bf_lo(p_cim) * dt);
            const float a2 = are * 1.4426950408889634f, bb = aim * 0.15915494309189535f;
            float m = fmaxf(fabsf(cr), fabsf(ci));
            #pragma unroll
            for (int o = 16; o; o >>= 1) m = fmaxf(m, __shfl_xor_sync(0xffffffffu, m, o));
            int ebits = (__float_as_uint(m) >> 23) & 0xFF;
            ebits = min(max(ebits, 2), 250);
            const float scale = __uint_as_float((uint32_t)(ebits + 1) << 23);
            const float iscale = __uint_as_float((uint32_t)(253 - ebits) << 23);
            cf cc; cc.x = cr * iscale; cc.y = ci * iscale;

            const uint32_t stg = sBa + S_KC + warp * 1024;
            uint4* stp = (uint4*)(sB + S_KC + warp * 1024 + lane * 32);
            const uint32_t fa = stg + t * 32 + g * 4;

            uint32_t af[4][2][4];
            cf E256;
            {
                const cf E8 = cexp_p(a2, bb, 8.0f);
                uint32_t w[8];
                cf cur; cur.x = 1.0f; cur.y = 0.0f;
                w[0] = pack_f16(1.0f, 0.0f);
                cur = E8; w[1] = pack_f16(cur.x, cur.y);
                #pragma unroll
                for (int i = 2; i < 8; i++) { cur = cmul(cur, E8); w[i] = pack_f16(cur.x, cur.y); }
                stp[0] = make_uint4(w[0], w[1], w[2], w[3]);
                stp[1] = make_uint4(w[4], w[5], w[6], w[7]);
                const cf E64 = cexp_p(a2, bb, 64.0f);
                const cf E128 = cmul(E64, E64), E192 = cmul(E128, E64);
                E256 = cexp_p(a2, bb, 256.0f);
                const uint32_t e1 = pack_f16(E64.x, E64.y), e2 = pack_f16(E128.x, E128.y), e3 = pack_f16(E192.x, E192.y);
                __syncwarp();
                #pragma unroll
                for (int s = 0; s < 4; s++) {
                    #pragma unroll
                    for (int hh = 0; hh < 2; hh++) {
                        const uint32_t w0 = lds32(fa + s * 256 + hh * 128);
                        const uint32_t wsw = __byte_perm(w0, 0, 0x1032) ^ 0x00008000u;
                        const int src = 8 * s + t + 4 * hh;
                        const uint32_t f1 = __shfl_sync(0xffffffffu, e1, src), f2 = __shfl_sync(0xffffffffu, e2, src), f3 = __shfl_sync(0xffffffffu, e3, src);
                        af[s][0][2 * hh] = w0;
                        af[s][0][2 * hh + 1] = h2_cmul(w0, wsw, f1);
                        af[s][1][2 * hh] = h2_cmul(w0, wsw, f2);
                        af[s][1][2 * hh + 1] = h2_cmul(w0, wsw, f3);
                    }
                }
                __syncwarp();
            }
            float acc[2][3][4];
            #pragma unroll
            for (int i = 0; i < 24; i++) (&acc[0][0][0])[i] = 0.0f;
            const cf E1 = cexp_p(a2, bb, 1.0f);
            const cf E2 = cmul(E1, E1), E4 = cmul(E2, E2);
            cf X512;
            #pragma unroll
            for (int nt = 0; nt < 3; nt++) {
                uint32_t xv[8];
                if (nt == 0) {
                    cf cur = cc;
                    xv[0] = pack_f16(cur.x, -cur.y);
                    #pragma unroll
                    for (int i = 1; i < 8; i++) { cur = cmul(cur, E1); xv[i] = pack_f16(cur.x, -cur.y); }
                } else if (nt == 1) {
                    cf cur = cmul(cc, E256);
                    X512 = cmul(cur, E256);
                    xv[0] = pack_f16(cur.x, -cur.y);
                    #pragma unroll
                    for (int i = 1; i < 4; i++) { cur = cmul(cur, E2); xv[i] = pack_f16(cur.x, -cur.y); }
                    cur = cmul(X512, E4);
                    xv[4] = pack_f16(X512.x, -X512.y); xv[5] = pack_f16(cur.x, -cur.y);
                    X512 = cmul(X512, E256);
                    cur = cmul(X512, E4);
                    xv[6] = pack_f16(X512.x, -X512.y); xv[7] = pack_f16(cur.x, -cur.y);
                } else {
                    cf cur = X512;
                    #pragma unroll
                    for (int i = 0; i < 5; i++) { cur = cmul(cur, E256); xv[i] = pack_f16(cur.x, -cur.y); }
                    xv[5] = 0; xv[6] = 0; xv[7] = 0;
                }
                stp[0] = make_uint4(xv[0], xv[1], xv[2], xv[3]);
                stp[1] = make_uint4(xv[4], xv[5], xv[6], xv[7]);
                __syncwarp();
                #pragma unroll
                for (int s = 0; s < 4; s++) {
                    const uint32_t b0 = lds32(fa + s * 256), b1 = lds32(fa + s * 256 + 128);
                    mma_f16(acc[0][nt], af[s][0], b0, b1);
                    mma_f16(acc[1][nt], af[s][1], b0, b1);
                }
                __syncwarp();
            }
            float* kc = (float*)(sB + S_KC + c * 4096);
            bar_sync(4 + c, 128);
            #pragma unroll 1
            for (int step = 0; step < 4; step++) {
                if ((warp & 3) == step) {
                    #pragma unroll
                    for (int mt = 0; mt < 2; mt++)
                        #pragma unroll
                        for (int nt = 0; nt < 3; nt++)
                            #pragma unroll
                            for (int hh = 0; hh < 2; hh++) {
                                float2* p = (float2*)(kc + (mt * 16 + hh * 8 + g) * 24 + nt * 8 + 2 * t);
                                float2 v = make_float2(acc[mt][nt][2 * hh] * scale, acc[mt][nt][2 * hh + 1] * scale);
                                if (step) { float2 o = *p; v.x += o.x; v.y += o.y; }
                                *p = v;
                            }
                }
                if (step < 3) bar_sync(4 + c, 128);
            }
        }

        asm volatile("barrier.cluster.wait.aligned;" ::: "memory");
        PROF(4);
        uint32_t q[2][4];
        {
            float acc[16], akv[8];
            #pragma unroll
            for (int i = 0; i < 16; i++) acc[i] = 0.0f;
            #pragma unroll
            for (int i = 0; i < 8; i++) akv[i] = 0.0f;
            fence_regs<16>(acc);
            fence_regs<8>(akv);
            const uint64_t dA0 = make_desc(sb + SM_B + rowhalf * 8192, 16, 1024, 1);
            const uint64_t dA1 = make_desc(sb + SM_A + rowhalf * 8192, 16, 1024, 1) - 4096;
            const uint64_t dB = make_desc(sb + SM_WQ + nh * 64, 16, 1024, 1);
            const uint64_t dC = make_desc(sb + SM_WKV, 128, 8192, 0);
            if (kv_wg) {
                #pragma unroll 1
                for (int ch = 0; ch < 8; ch++) {
                    if ((ch & 3) == 0) mbar_wait(bars + 8 * (B_X + (ch >> 2)), 0);
                    const uint64_t dA = ch < 4 ? dA0 : dA1;
                    wg_fence();
                    #pragma unroll
                    for (int ks = 0; ks < 4; ks++) wg_ss16(akv, dA + ch * 1024 + ks * 2, dC + (ch * 4 + ks) * 16);
                    wg_commit();
                }
                wg_wait<0>();
            }
            fence_regs<8>(akv);
            if (kv_wg) {
                const int key = qb * 128 + rowhalf * 64 + wiw * 16 + g;
                uint32_t pk[4];
                #pragma unroll
                for (int i = 0; i < 4; i++) pk[i] = pack_bf16(akv[2 * i], akv[2 * i + 1]);
                float st;
                if (kv_sel == 0) {
                    uint8_t* b = g_kimg + (key >> 3) * 256 + (key & 7) * 16 + 4 * t;
                    *(uint32_t*)(b) = pk[0]; *(uint32_t*)(b + 256) = pk[1]; *(uint32_t*)(b + 128) = pk[2]; *(uint32_t*)(b + 384) = pk[3];
                    float n0 = bf_lo(pk[0]) * bf_lo(pk[0]) + bf_hi(pk[0]) * bf_hi(pk[0]) + bf_lo(pk[2]) * bf_lo(pk[2]) + bf_hi(pk[2]) * bf_hi(pk[2]);
                    float n1 = bf_lo(pk[1]) * bf_lo(pk[1]) + bf_hi(pk[1]) * bf_hi(pk[1]) + bf_lo(pk[3]) * bf_lo(pk[3]) + bf_hi(pk[3]) * bf_hi(pk[3]);
                    n0 += __shfl_xor_sync(0xffffffffu, n0, 1); n0 += __shfl_xor_sync(0xffffffffu, n0, 2);
                    n1 += __shfl_xor_sync(0xffffffffu, n1, 1); n1 += __shfl_xor_sync(0xffffffffu, n1, 2);
                    st = (n0 != n0 || n1 != n1) ? __int_as_float(0x7f800000) : fmaxf(n0, n1);
                } else {
                    const int s = key >> 4;
                    uint8_t* lo = g_vimg + s * 256 + g * 16 + 4 * t;
                    uint8_t* hi = g_vimg + 33024 + (127 - s) * 256 + g * 16 + 4 * t;
                    *(uint32_t*)(lo) = pk[0]; *(uint32_t*)(lo + 128) = pk[1]; *(uint32_t*)(hi) = pk[2]; *(uint32_t*)(hi + 128) = pk[3];
                    st = 0.0f;
                    #pragma unroll
                    for (int i = 0; i < 4; i++) {
                        float a = fabsf(bf_lo(pk[i])), b = fabsf(bf_hi(pk[i]));
                        st = (a != a || b != b) ? __int_as_float(0x7f800000) : fmaxf(st, fmaxf(a, b));
                    }
                }
                #pragma unroll
                for (int o = 16; o; o >>= 1) st = fmaxf(st, __shfl_xor_sync(0xffffffffu, st, o));
                if (lane == 0) s_misc[20 + wiw] = st;
                bar_arrive(3, 160);
            }
            mbar_wait(bars + 8 * B_WQ, 0);
            PROF(2);
            #pragma unroll 1
            for (int ch = 0; ch < 8; ch++) {
                if (ch == 4) { wg_wait<0>(); bar_arrive(13, 544); }
                if ((ch & 3) == 0) mbar_wait(bars + 8 * (B_X + (ch >> 2)), 0);
                if (ch == 4) PROF(15);
                const uint64_t dA = ch < 4 ? dA0 : dA1;
                wg_fence();
                #pragma unroll
                for (int ks = 0; ks < 4; ks++) wg_ss32(acc, dA + ch * 1024 + ks * 2, dB + (ch * 4 + ks) * 128);
                wg_commit();
            }
            wg_wait<0>();
            fence_regs<16>(acc);
            const float QS = 0.25f * 1.4426950408889634f;
            float qm = 0.0f;
            #pragma unroll
            for (int i = 0; i < 2; i++) {
                #pragma unroll
                for (int j = 0; j < 4; j++) q[i][j] = pack_bf16(acc[8 * i + 2 * j] * QS, acc[8 * i + 2 * j + 1] * QS);
                float n0 = bf_lo(q[i][0]) * bf_lo(q[i][0]) + bf_hi(q[i][0]) * bf_hi(q[i][0]) + bf_lo(q[i][2]) * bf_lo(q[i][2]) + bf_hi(q[i][2]) * bf_hi(q[i][2]);
                float n1 = bf_lo(q[i][1]) * bf_lo(q[i][1]) + bf_hi(q[i][1]) * bf_hi(q[i][1]) + bf_lo(q[i][3]) * bf_lo(q[i][3]) + bf_hi(q[i][3]) * bf_hi(q[i][3]);
                n0 += __shfl_xor_sync(0xffffffffu, n0, 1); n0 += __shfl_xor_sync(0xffffffffu, n0, 2);
                n1 += __shfl_xor_sync(0xffffffffu, n1, 1); n1 += __shfl_xor_sync(0xffffffffu, n1, 2);
                qm = (n0 != n0 || n1 != n1) ? __int_as_float(0x7f800000) : fmaxf(qm, fmaxf(n0, n1));
            }
            #pragma unroll
            for (int o = 16; o; o >>= 1) qm = fmaxf(qm, __shfl_xor_sync(0xffffffffu, qm, o));
            if (lane == 0) s_misc[warp] = qm;
        }
        bar_arrive(14, 544);
        uint32_t mp[9];
        #pragma unroll
        for (int i = 0; i < 9; i++) { const int w = (tid & 127) + 128 * i; mp[i] = (w < TABN / 2) ? __ldg((const uint32_t*)g_tabmap.v + w) : 0u; }
        bar_sync(1, 512);
        {
            const float* kc = (const float*)(sB + S_KC + wg * 4096);
            uint32_t* tab = (uint32_t*)(sB + S_TAB + wg * TABN * 2);
            #pragma unroll
            for (int i = 0; i < 9; i++) { const int w = (tid & 127) + 128 * i; if (w < TABN / 2) tab[w] = pack_bf16(kc[mp[i] & 0xFFFF], kc[mp[i] >> 16]); }
        }
        PROF(3);
        if (tid < 4 * (PADU / 8)) *(uint4*)(sB + S_U + (tid / (PADU / 8)) * ULEN * 2 + (tid % (PADU / 8)) * 16) = make_uint4(0, 0, 0, 0);
        PROF(8);
        mbar_wait(bars + 8 * B_U, 0);
        PROF(14);
        #pragma unroll
        for (int i = 0; i < 2; i++) {
            const int l = 2 * (tid + 512 * i);
            const uint2 r0 = *(const uint2*)(sB + S_W3 + l * 16 + rank * 8), r1 = *(const uint2*)(sB + S_W3 + l * 16 + 16 + rank * 8);
            uint32_t* dst = (uint32_t*)(sB + S_U + (PADU + l) * 2);
            dst[0] = __byte_perm(r0.x, r1.x, 0x5410);
            dst[ULEN / 2] = __byte_perm(r0.x, r1.x, 0x7632);
            dst[ULEN] = __byte_perm(r0.y, r1.y, 0x5410);
            dst[3 * ULEN / 2] = __byte_perm(r0.y, r1.y, 0x7632);
        }
        bar_sync(1, 512);
        #pragma unroll 1
        for (int task = tid; task < 4 * 194; task += 512) {
            const int c = task / 194, i = task % 194;
            const uint4* src = (const uint4*)(sB + S_U + c * ULEN * 2 + (PADU + 8 * i - WPAD - 8) * 2);
            const uint4 v0 = src[0], v1 = src[1], v2 = src[2];
            float x[24];
            const uint32_t vv[12] = {v0.x, v0.y, v0.z, v0.w, v1.x, v1.y, v1.z, v1.w, v2.x, v2.y, v2.z, v2.w};
            #pragma unroll
            for (int k = 0; k < 12; k++) { x[2 * k] = bf_lo(vv[k]); x[2 * k + 1] = bf_hi(vv[k]); }
            float w3[12], w5[8];
            #pragma unroll
            for (int e = 0; e < 12; e++) w3[e] = (x[3 + e] + x[4 + e]) + x[5 + e];
            #pragma unroll
            for (int e = 0; e < 8; e++) w5[e] = w3[4 + e] + (x[6 + e] + x[10 + e]);
            *(uint4*)(sB + S_W3 + c * W2LEN * 2 + i * 16) = make_uint4(pack_bf16(w3[0], w3[1]), pack_bf16(w3[2], w3[3]), pack_bf16(w3[4], w3[5]), pack_bf16(w3[6], w3[7]));
            *(uint4*)(sB + S_W5 + c * W2LEN * 2 + i * 16) = make_uint4(pack_bf16(w5[0], w5[1]), pack_bf16(w5[2], w5[3]), pack_bf16(w5[4], w5[5]), pack_bf16(w5[6], w5[7]));
            if (i < 130) {
                float w7[8], w9[8];
                #pragma unroll
                for (int e = 0; e < 8; e++) { w7[e] = w5[e] + (x[5 + e] + x[11 + e]); w9[e] = w7[e] + (x[4 + e] + x[12 + e]); }
                *(uint4*)(sB + S_W7 + c * W3LEN * 2 + i * 16) = make_uint4(pack_bf16(w7[0], w7[1]), pack_bf16(w7[2], w7[3]), pack_bf16(w7[4], w7[5]), pack_bf16(w7[6], w7[7]));
                *(uint4*)(sB + S_W9 + c * W3LEN * 2 + i * 16) = make_uint4(pack_bf16(w9[0], w9[1]), pack_bf16(w9[2], w9[3]), pack_bf16(w9[4], w9[5]), pack_bf16(w9[6], w9[7]));
            }
        }
        PROF(1);
        bar_sync(1, 512);
        PROF(6);
        {
            const int c = warp >> 2, grp = (warp + c) & 3;
            float acc[4][4];
            #pragma unroll
            for (int i = 0; i < 16; i++) (&acc[0][0])[i] = 0.0f;
            const uint32_t tabc = sBa + S_TAB + c * TABN * 2;
            const int e2 = (g - 2 * t) * 2;
            const uint32_t tD = tabc + ((g & 1) ? (TD1 + CD + 1) : (TD0 + CD)) * 2 - e2;
            const uint32_t tE = tabc + ((g & 1) ? (TE1 + CE + 1) : (TE0 + CE)) * 2 - e2;
            const uint32_t t2 = tabc + (T2B + ((g & 1) ? (T2C + C2 + 1) : C2)) * 2 - e2;
            const uint32_t t3 = tabc + (T3B + ((g & 1) ? (T3C + C3 + 1) : C3)) * 2 - e2;
            const int mi = lane >> 3, r8 = lane & 7;
            const uint32_t ub = sBa + S_U + c * ULEN * 2 + (PADU + 16 * (8 * (mi >> 1) + r8) + 8 * (mi & 1)) * 2 + (4 * grp - 4) * 256;
            #pragma unroll 1
            for (int rho = 0; rho < 8; rho++) {
                uint32_t R[5][3];
                #pragma unroll
                for (int qq = 0; qq < 5; qq++) {
                    if (qq < 4 || rho < 2) {
                        const uint32_t a = tD - 32 * (rho + 8 * qq);
                        R[qq][0] = lds32(a + 16); R[qq][1] = lds32(a); R[qq][2] = lds32(a - 16);
                    } else { R[qq][0] = 0; R[qq][1] = 0; R[qq][2] = 0; }
                }
                #pragma unroll
                for (int jp = 0; jp < 4; jp++) {
                    if (grp == 0 && (jp == 0 || (jp == 1 && rho > 0))) continue;
                    if (jp == 0 && rho >= 2) {
                        uint32_t b[4];
                        ldsm4(b, ub + jp * 512 - rho * 32);
                        mma_bf16(acc[0], R[3][1], R[3][2], R[3][0], R[3][1], b[2], b[3]);
                        continue;
                    }
                    uint32_t b[4];
                    ldsm4(b, ub + jp * 512 - rho * 32);
                    #pragma unroll
                    for (int hh = 0; hh < 2; hh++) {
                        #pragma unroll
                        for (int qq = 0; qq < 5; qq++) {
                            const int jr = 2 * jp + hh + qq - 4;
                            if (jr >= 0 && jr < 4) {
                                if (qq < 4 || rho < 2) mma_bf16(acc[jr], R[qq][1], R[qq][2], R[qq][0], R[qq][1], b[2 * hh], b[2 * hh + 1]);
                            }
                        }
                    }
                }
            }
            if (grp >= 2) {
                uint32_t R[5];
                #pragma unroll
                for (int i = 0; i < 5; i++) R[i] = lds32(tE - 16 * (127 + i));
                #pragma unroll
                for (int kk = 0; kk < 2; kk++) {
                    #pragma unroll
                    for (int jp = 0; jp < 2; jp++) {
                        uint32_t b[4];
                        ldsm4(b, ub + (4 + 2 * jp) * 256 - (64 + kk) * 32);
                        mma_bf16(acc[2 * jp], R[2 * kk + 1], R[2 * kk + 2], R[2 * kk], R[2 * kk + 1], b[0], b[1]);
                        mma_bf16(acc[2 * jp + 1], R[2 * kk + 1], R[2 * kk + 2], R[2 * kk], R[2 * kk + 1], b[2], b[3]);
                    }
                }
            }
            const uint32_t soff = (WPAD + 16 * (8 * (mi >> 1) + r8) + 8 * (mi & 1)) * 2 + grp * 1024;
            if (grp >= 1) {
                #pragma unroll 1
                for (int s = 0; s < 4; s++) {
                    const uint32_t sig = sBa + ((s & 1) ? S_W3 : S_W5) + c * W2LEN * 2 + soff - ((s == 0) ? 32 : (s == 1) ? 0 : 16);
                    uint32_t R[7];
                    #pragma unroll
                    for (int i = 0; i < 7; i++) R[i] = lds32(t2 + s * (T2S * 2) - 16 * (3 + i));
                    #pragma unroll
                    for (int bb = 1; bb <= 4; bb++) {
                        if (2 * grp - bb < 0) continue;
                        uint32_t a[4];
                        ldsm4t(a, sig - bb * 512);
                        #pragma unroll
                        for (int jj = 0; jj < 4; jj++) {
                            const int h = jj + 2 * bb;
                            if (h >= 4 && h <= 9) mma_bf16(acc[jj], a[0], a[1], a[2], a[3], R[h - 3], R[h - 4]);
                        }
                    }
                }
            }
            if (grp >= 2) {
                #pragma unroll 1
                for (int s = 0; s < 2; s++) {
                    const uint32_t sig = sBa + (s ? S_W7 : S_W9) + c * W3LEN * 2 + soff - (s ? 16 : 32);
                    uint32_t R[9];
                    #pragma unroll
                    for (int i = 0; i < 9; i++) R[i] = lds32(t3 + s * (T3S * 2) - 16 * (7 + i));
                    #pragma unroll
                    for (int bb = 3; bb <= 6; bb++) {
                        if (2 * grp - bb < 0) continue;
                        uint32_t a[4];
                        ldsm4t(a, sig - bb * 512);
                        #pragma unroll
                        for (int jj = 0; jj < 4; jj++) {
                            const int h = jj + 2 * bb;
                            if (h >= 8 && h <= 15) mma_bf16(acc[jj], a[0], a[1], a[2], a[3], R[h - 7], R[h - 8]);
                        }
                    }
                }
            }
            __nv_bfloat16* ys = (__nv_bfloat16*)(sB + S_Y + c * 4096);
            #pragma unroll
            for (int jj = 0; jj < 4; jj++) {
                const int A = 8 * (4 * grp + jj) + 2 * t;
                ys[16 * A + g] = __float2bfloat16_rn(acc[jj][0]);
                ys[16 * A + 16 + g] = __float2bfloat16_rn(acc[jj][1]);
                ys[16 * A + g + 8] = __float2bfloat16_rn(acc[jj][2]);
                ys[16 * A + 16 + g + 8] = __float2bfloat16_rn(acc[jj][3]);
            }
        }
        bar_arrive(10, 608);
        PROF(7);
        {
            mbar_wait(bars + 8 * B_ST, 0);
            PROF(9); PROFC(8);
            float qm = 0.0f;
            #pragma unroll
            for (int i = 0; i < 16; i++) qm = fmaxf(qm, s_misc[i]);
            const float vm = s_misc[17];
            const bool fast = (qm * s_misc[16] <= 60.0f * 60.0f) && (vm <= 1.0e12f) && (vm >= 1.0e-12f || vm == 0.0f);
            const uint64_t dVstep = 16ull - (16ull << 32);
            uint8_t* ob = g_oimg + qb * 131072 + hg * 16384 + nh * 8192 + (rowhalf * 8 + wiw * 2) * 128 + g * 16 + 4 * t;
            uint32_t cA = 0xBF00BF00u, cB = 0x00030003u;
            asm volatile("" : "+r"(cA), "+r"(cB));
            #pragma unroll 1
            for (int tile = 0; tile < 2; tile++) {
                uint64_t dK = make_desc(sb + SM_K, 128, 256, 0);
                uint64_t dV = make_desc(sb + SM_V, 128, 32768, 0);
                float o[12], s[32];
                uint32_t p[16], qq[4];
                #pragma unroll
                for (int i = 0; i < 4; i++) qq[i] = tile ? q[1][i] : q[0][i];
                #pragma unroll
                for (int i = 0; i < 12; i++) o[i] = 0.0f;
                #pragma unroll
                for (int i = 0; i < 32; i++) s[i] = 0.0f;
                fence_regs<12>(o);
                fence_regs<32>(s);
                if (fast) {
                    #pragma unroll 1
                    for (int c = 0; c < SEQ / 256; c++) {
                        if (c <= 4) mbar_wait(bars + 8 * (B_KV + (c < 2 ? c : c < 4 ? 2 : 3)), 0);
                        wg_fence();
                        wg_qk(s, qq, dK);
                        wg_commit();
                        #pragma unroll
                        for (int u = 0; u < 4; u++) {
                            wg_wait<0>();
                            fence_regs<32>(s);
                            #pragma unroll
                            for (int i = 0; i < 16; i++) {
                                if ((MUFU_MASK >> i) & 1) p[i] = exp_mufu(s[2 * i], s[2 * i + 1]);
                                else p[i] = exp_sw(s[2 * i], s[2 * i + 1], cA, cB);
                            }
                            wg_fence();
                            if (u + 1 < 4) wg_qk(s, qq, dK + (u + 1) * 128);
                            #pragma unroll
                            for (int kk = 0; kk < 4; kk++) wg_pv(o, p + 4 * kk, dV + (u * 4 + kk) * dVstep);
                            wg_commit();
                        }
                        dK += 512;
                        dV += 16 * dVstep;
                    }
                    wg_wait<0>();
                } else {
                    float mx0 = -INFINITY, mx1 = -INFINITY;
                    #pragma unroll 1
                    for (int c = 0; c < SEQ / 64; c++) {
                        if (c <= 16) mbar_wait(bars + 8 * (B_KV + (c < 8 ? (c >> 2) : c < 16 ? 2 : 3)), 0);
                        wg_fence();
                        wg_qk(s, qq, dK);
                        wg_commit();
                        wg_wait<0>();
                        fence_regs<32>(s);
                        fence_regs<12>(o);
                        float m0 = mx0, m1 = mx1;
                        #pragma unroll
                        for (int j = 0; j < 8; j++) {
                            m0 = fmaxf(m0, fmaxf(s[4 * j], s[4 * j + 1]));
                            m1 = fmaxf(m1, fmaxf(s[4 * j + 2], s[4 * j + 3]));
                        }
                        m0 = fmaxf(m0, __shfl_xor_sync(0xffffffffu, m0, 1)); m0 = fmaxf(m0, __shfl_xor_sync(0xffffffffu, m0, 2));
                        m1 = fmaxf(m1, __shfl_xor_sync(0xffffffffu, m1, 1)); m1 = fmaxf(m1, __shfl_xor_sync(0xffffffffu, m1, 2));
                        const float c0 = ex2f(mx0 - m0), c1 = ex2f(mx1 - m1);
                        mx0 = m0; mx1 = m1;
                        #pragma unroll
                        for (int j = 0; j < 3; j++) { o[4 * j] *= c0; o[4 * j + 1] *= c0; o[4 * j + 2] *= c1; o[4 * j + 3] *= c1; }
                        #pragma unroll
                        for (int j = 0; j < 8; j++) {
                            p[2 * j] = exp_mufu(s[4 * j] - m0, s[4 * j + 1] - m0);
                            p[2 * j + 1] = exp_mufu(s[4 * j + 2] - m1, s[4 * j + 3] - m1);
                        }
                        wg_fence();
                        #pragma unroll
                        for (int kk = 0; kk < 4; kk++) wg_pv(o, p + 4 * kk, dV + kk * dVstep);
                        wg_commit();
                        wg_wait<0>();
                        dK += 128;
                        dV += 4 * dVstep;
                    }
                }
                fence_regs<12>(o);
                const float i0 = 1.0f / o[4], i1 = 1.0f / o[6];
                uint8_t* b = ob + tile * 4096;
                *(uint32_t*)(b) = pack_bf16(o[0] * i0, o[1] * i0);
                *(uint32_t*)(b + 128) = pack_bf16(o[2] * i1, o[3] * i1);
                *(uint32_t*)(b + 2048) = pack_bf16(o[8] * i0, o[9] * i0);
                *(uint32_t*)(b + 2048 + 128) = pack_bf16(o[10] * i1, o[11] * i1);
            }
        }
        PROF(10); PROFC(9);
        bar_arrive(12, 544);

        {
            float acc[16];
            #pragma unroll
            for (int i = 0; i < 16; i++) acc[i] = 0.0f;
            fence_regs<16>(acc);
            const uint64_t dA = make_desc(sb + SM_A + rowhalf * 1024, 2048, 128, 0);
            const uint64_t dB = make_desc(sb + SM_B + nh * 64, 16, 1024, 1);
            mbar_wait(bars + 8 * B_WO, 0);
            #pragma unroll 1
            for (int i = 0; i < 8; i++) {
                const int src = (hg + i) & 7;
                mbar_wait(bars + 8 * (B_O + src), 0);
                wg_fence();
                #pragma unroll
                for (int kk = 0; kk < 4; kk++) wg_ss32(acc, dA + src * 1024 + kk * 256, dB + (src * 4 + kk) * 128);
                wg_commit();
            }
            wg_wait<0>();
            fence_regs<16>(acc);
            PROF(12);
            const int row = qb * 128 + rowhalf * 64 + wiw * 16 + g;
            uint32_t* o32 = (uint32_t*)(P.out + (size_t)row * 1024 + hg * 64 + nh * 32 + 2 * t);
            #pragma unroll
            for (int j = 0; j < 4; j++) {
                o32[4 * j] = pack_bf16(acc[4 * j], acc[4 * j + 1]);
                o32[4 * j + 8 * 512] = pack_bf16(acc[4 * j + 2], acc[4 * j + 3]);
            }
        }
        PROF(13);
    }
}

typedef CUresult (*EncodeFn)(CUtensorMap*, CUtensorMapDataType, cuuint32_t, void*, const cuuint64_t*, const cuuint64_t*,
                             const cuuint32_t*, const cuuint32_t*, CUtensorMapInterleave, CUtensorMapSwizzle,
                             CUtensorMapL2promotion, CUtensorMapFloatOOBfill);

void make_map(EncodeFn fn, CUtensorMap* m, const void* ptr, uint64_t inner, uint64_t outer, uint32_t box_in, uint32_t box_out, CUtensorMapSwizzle swz) {
    cuuint64_t dims[2] = {inner, outer};
    cuuint64_t strides[1] = {inner * 2};
    cuuint32_t box[2] = {box_in, box_out};
    cuuint32_t es[2] = {1, 1};
    fn(m, CU_TENSOR_MAP_DATA_TYPE_BFLOAT16, 2, const_cast<void*>(ptr), dims, strides, box, es, CU_TENSOR_MAP_INTERLEAVE_NONE, swz,
       CU_TENSOR_MAP_L2_PROMOTION_L2_128B, CU_TENSOR_MAP_FLOAT_OOB_FILL_NONE);
}

}

extern "C" void kernel_launch(void* const* d_in, const int* in_sizes, int n_in, void* d_out, int out_size) {
    (void)in_sizes; (void)n_in; (void)out_size;
    static EncodeFn fn = nullptr;
    if (!fn) {
        void* p = nullptr;
        cudaDriverEntryPointQueryResult qr;
        cudaGetDriverEntryPoint("cuTensorMapEncodeTiled", &p, cudaEnableDefault, &qr);
        fn = (EncodeFn)p;
        cudaFuncSetAttribute(fused_kernel, cudaFuncAttributeMaxDynamicSharedMemorySize, SM_ALLOC);
    }
    CUtensorMap tx, twq, two, twk, twv, tu;
    {
        cuuint64_t dims[3] = {64, 2048, 8};
        cuuint64_t strides[2] = {1024, 128};
        cuuint32_t box[3] = {64, 128, 4};
        cuuint32_t es[3] = {1, 1, 1};
        fn(&tx, CU_TENSOR_MAP_DATA_TYPE_BFLOAT16, 3, d_in[0], dims, strides, box, es, CU_TENSOR_MAP_INTERLEAVE_NONE, CU_TENSOR_MAP_SWIZZLE_128B,
           CU_TENSOR_MAP_L2_PROMOTION_L2_128B, CU_TENSOR_MAP_FLOAT_OOB_FILL_NONE);
    }
    make_map(fn, &tu, d_in[5], 512, 2048, 8, 256, CU_TENSOR_MAP_SWIZZLE_NONE);
    make_map(fn, &twq, d_in[1], 512, 512, 64, 256, CU_TENSOR_MAP_SWIZZLE_128B);
    make_map(fn, &twk, d_in[2], 16, 512, 8, 256, CU_TENSOR_MAP_SWIZZLE_NONE);
    make_map(fn, &twv, d_in[3], 16, 512, 8, 256, CU_TENSOR_MAP_SWIZZLE_NONE);
    make_map(fn, &two, d_in[4], 512, 512, 64, 256, CU_TENSOR_MAP_SWIZZLE_128B);
    Params P;
    P.u = (const __nv_bfloat16*)d_in[5];
    P.lar = (const __nv_bfloat16*)d_in[6];
    P.aim = (const __nv_bfloat16*)d_in[7];
    P.cre = (const __nv_bfloat16*)d_in[8];
    P.cim = (const __nv_bfloat16*)d_in[9];
    P.logdt = (const __nv_bfloat16*)d_in[10];
    P.dskip = (const __nv_bfloat16*)d_in[11];
    P.out = (__nv_bfloat16*)d_out;
    fused_kernel<<<NCTA, NTHR, SM_ALLOC>>>(tx, twq, two, twk, twv, tu, P);
}
```

```cpp
#include <cuda_runtime.h>
#include <cuda_bf16.h>
#include <cuda_fp16.h>
#include <cuda.h>
#include <stdint.h>

namespace {

constexpr int SEQ = 2048;
constexpr int NCTA = 128, NTHR = 640;

constexpr int SM_A = 0;
constexpr int SM_WQ = 65536;
constexpr int SM_SLAB = SM_WQ + 32768;
constexpr int SM_K = 0, SM_V = 65536;
constexpr int SM_B = 132096;
constexpr int SM_WKV = SM_B + 65536;

constexpr int PADU = 288, ULEN = PADU + 2048;
constexpr int WPAD = 16, W2LEN = WPAD + 1536, W3LEN = WPAD + 1024;
constexpr int TABN = 2240;
constexpr int S_U = 0;
constexpr int S_W3 = S_U + 4 * ULEN * 2;
constexpr int S_W5 = S_W3 + 4 * W2LEN * 2;
constexpr int S_W7 = S_W5 + 4 * W2LEN * 2;
constexpr int S_W9 = S_W7 + 4 * W3LEN * 2;
constexpr int S_TAB = S_W9 + 4 * W3LEN * 2;
constexpr int S_KC = 214016 - SM_B;
constexpr int S_Y = S_KC;
constexpr int SM_BAR = SM_B + S_KC + 16384;
constexpr int SM_TOTAL = SM_BAR + 1024;
constexpr int SM_ALLOC = SM_TOTAL + 1024;
static_assert(SM_V + 65536 + 1024 <= SM_B && SM_ALLOC <= 232448 && S_TAB + 4 * TABN * 2 <= S_KC && SM_WKV + 16384 <= SM_B + S_KC, "smem map");

constexpr int TD0 = 0, TD1 = 560, CD = 544;
constexpr int TE0 = 1120, TE1 = 1168, CE = 1056;
constexpr int T2B = 1216, T2S = 160, T2C = 80, C2 = 80;
constexpr int T3B = 1856, T3S = 192, T3C = 96, C3 = 144;

constexpr int rne8(int t) {
    if (t < 256) return t;
    int sh = 0;
    while ((t >> sh) >= 256) sh++;
    int q = t >> sh, rem = t & ((1 << sh) - 1), half = 1 << (sh - 1);
    if (rem > half || (rem == half && (q & 1))) q++;
    return q << sh;
}
constexpr int kcidx(int p) {
    if (p < 256) return (p >> 3) * 24 + (p & 7);
    if (p < 512) return ((p - 256) >> 3) * 24 + 8 + (((p - 256) & 7) >> 1);
    if (p < 1024) { int q = p - 512, hi = q >> 8, rem = q & 255; return (rem >> 3) * 24 + 12 + 2 * hi + ((rem & 7) >> 2); }
    if (p < 2048) { int q = p - 1024; return ((q & 255) >> 3) * 24 + 16 + (q >> 8); }
    return 20;
}
constexpr int KC_ZERO = 23;
constexpr int tab_dense(int t) { return (t >= 0 && t <= 514) ? kcidx(rne8(t)) : KC_ZERO; }
constexpr int tab_extra(int t) { return (t >= 1027 && t <= 1028) ? kcidx(1024) : KC_ZERO; }
constexpr int tab_2(int s, int lag) { return (lag >= 32 && lag <= 63) ? kcidx(s == 0 ? 16 * (lag + 1) : 16 * lag + 4 * s) : KC_ZERO; }
constexpr int tab_3(int s, int lag) { return (lag >= 64 && lag <= 127) ? kcidx(s == 0 ? 16 * (lag + 1) : 16 * lag + 8) : KC_ZERO; }
struct TabMap {
    uint16_t v[TABN];
    constexpr TabMap() : v{} {
        for (int i = 0; i < 560; i++) { v[TD0 + i] = tab_dense(CD - i); v[TD1 + i] = tab_dense(CD + 1 - i); }
        for (int i = 0; i < 48; i++) { v[TE0 + i] = tab_extra(CE - i); v[TE1 + i] = tab_extra(CE + 1 - i); }
        for (int s = 0; s < 4; s++)
            for (int i = 0; i < T2C; i++) { v[T2B + s * T2S + i] = tab_2(s, C2 - i); v[T2B + s * T2S + T2C + i] = tab_2(s, C2 + 1 - i); }
        for (int s = 0; s < 2; s++)
            for (int i = 0; i < T3C; i++) { v[T3B + s * T3S + i] = tab_3(s, C3 - i); v[T3B + s * T3S + T3C + i] = tab_3(s, C3 + 1 - i); }
    }
};
__device__ const __align__(16) TabMap g_tabmap = TabMap();

__device__ __align__(1024) uint8_t g_kimg[65536];
__device__ __align__(1024) uint8_t g_vimg[65536 + 1024];
__device__ __align__(1024) uint8_t g_oimg[16 * 131072];
__device__ unsigned long long g_flag_kv[64];
__device__ unsigned g_flag_o[128];
__device__ unsigned g_epoch;
__device__ unsigned g_done;

#define PROF(i) do {} while (0)
#define PROF2(i) do {} while (0)
#define PROFC(i) do {} while (0)
#define PROF3(i) do {} while (0)

__device__ __forceinline__ uint32_t smem_u32(const void* p) { return (uint32_t)__cvta_generic_to_shared(p); }
__device__ __forceinline__ void mbar_init(uint32_t bar, uint32_t cnt) { asm volatile("mbarrier.init.shared::cta.b64 [%0], %1;" :: "r"(bar), "r"(cnt) : "memory"); }
__device__ __forceinline__ void mbar_expect_tx(uint32_t bar, uint32_t bytes) {
    asm volatile("mbarrier.arrive.expect_tx.shared::cta.b64 _, [%0], %1;" :: "r"(bar), "r"(bytes) : "memory"); }
__device__ __forceinline__ void mbar_wait(uint32_t bar, uint32_t parity) {
    uint32_t ok = 0;
    for (int it = 0; it < (1 << 22) && !ok; it++) {
        asm volatile("{ .reg .pred p; mbarrier.try_wait.parity.shared::cta.b64 p, [%1], %2; selp.u32 %0, 1, 0, p; }"
                     : "=r"(ok) : "r"(bar), "r"(parity) : "memory");
    }
}
__device__ __forceinline__ void tma_2d(uint32_t dst, const CUtensorMap* map, int c0, int c1, uint32_t bar) {
    asm volatile("cp.async.bulk.tensor.2d.shared::cluster.global.mbarrier::complete_tx::bytes [%0], [%1, {%3, %4}], [%2];"
                 :: "r"(dst), "l"((uint64_t)map), "r"(bar), "r"(c0), "r"(c1) : "memory");
}
__device__ __forceinline__ void tma_2d_mc(uint32_t dst, const CUtensorMap* map, int c0, int c1, uint32_t bar) {
    asm volatile("cp.async.bulk.tensor.2d.shared::cluster.global.mbarrier::complete_tx::bytes.multicast::cluster [%0], [%1, {%3, %4}], [%2], %5;"
                 :: "r"(dst), "l"((uint64_t)map), "r"(bar), "r"(c0), "r"(c1), "h"((uint16_t)3) : "memory");
}
__device__ __forceinline__ void bulk_g2s_mc(uint32_t dst, const void* src, uint32_t bytes, uint32_t bar) {
    asm volatile("cp.async.bulk.shared::cluster.global.mbarrier::complete_tx::bytes.multicast::cluster [%0], [%1], %2, [%3], %4;"
                 :: "r"(dst), "l"((uint64_t)src), "r"(bytes), "r"(bar), "h"((uint16_t)3) : "memory");
}
__device__ __forceinline__ void pair_sync(uint32_t bar, uint32_t peer) {
    uint32_t ra;
    asm volatile("mapa.shared::cluster.u32 %0, %1, %2;" : "=r"(ra) : "r"(bar), "r"(peer));
    asm volatile("mbarrier.arrive.shared::cluster.b64 _, [%0];" :: "r"(ra) : "memory");
    asm volatile("mbarrier.arrive.shared::cta.b64 _, [%0];" :: "r"(bar) : "memory");
    uint32_t ok = 0;
    for (int it = 0; it < (1 << 22) && !ok; it++) {
        asm volatile("{ .reg .pred p; mbarrier.try_wait.parity.shared::cta.b64 p, [%1], 0; selp.u32 %0, 1, 0, p; }"
                     : "=r"(ok) : "r"(bar) : "memory");
    }
}
__device__ __forceinline__ void fence_async_all() { asm volatile("fence.proxy.async.global;" ::: "memory"); }
__device__ __forceinline__ void fence_async_smem() { asm volatile("fence.proxy.async.shared::cta;" ::: "memory"); }
__device__ __forceinline__ unsigned ld_acquire(const unsigned* p) {
    unsigned v; asm volatile("ld.acquire.gpu.global.u32 %0, [%1];" : "=r"(v) : "l"(p) : "memory"); return v; }
__device__ __forceinline__ void st_release(unsigned* p, unsigned v) { asm volatile("st.release.gpu.global.u32 [%0], %1;" :: "l"(p), "r"(v) : "memory"); }
__device__ __forceinline__ void wait_flag(const unsigned* p, unsigned epoch) {
    for (int it = 0; it < (1 << 22); it++) { if (ld_acquire(p) == epoch) break; }
}
__device__ __forceinline__ unsigned long long ld_acquire64(const unsigned long long* p) {
    unsigned long long v; asm volatile("ld.acquire.gpu.global.u64 %0, [%1];" : "=l"(v) : "l"(p) : "memory"); return v; }
__device__ __forceinline__ void st_release64(unsigned long long* p, unsigned long long v) { asm volatile("st.release.gpu.global.u64 [%0], %1;" :: "l"(p), "l"(v) : "memory"); }
__device__ __forceinline__ float wait_flag64(const unsigned long long* p, unsigned epoch) {
    unsigned long long v = 0;
    for (int it = 0; it < (1 << 22); it++) { v = ld_acquire64(p); if ((unsigned)(v >> 32) == epoch) break; }
    return __uint_as_float((unsigned)v);
}
__device__ __forceinline__ void tma_3d_mc(uint32_t dst, const CUtensorMap* map, int c0, int c1, int c2, uint32_t bar) {
    asm volatile("cp.async.bulk.tensor.3d.shared::cluster.global.mbarrier::complete_tx::bytes.multicast::cluster [%0], [%1, {%3, %4, %5}], [%2], %6;"
                 :: "r"(dst), "l"((uint64_t)map), "r"(bar), "r"(c0), "r"(c1), "r"(c2), "h"((uint16_t)3) : "memory");
}
__device__ __forceinline__ void bar_sync(int id, int n) { asm volatile("bar.sync %0, %1;" :: "r"(id), "r"(n) : "memory"); }
__device__ __forceinline__ void bar_arrive(int id, int n) { asm volatile("bar.arrive %0, %1;" :: "r"(id), "r"(n) : "memory"); }
__device__ __forceinline__ void mbar_arrive(uint32_t bar) { asm volatile("mbarrier.arrive.shared::cta.b64 _, [%0];" :: "r"(bar) : "memory"); }

__device__ __forceinline__ uint64_t make_desc(uint32_t saddr, uint32_t lbo, uint32_t sbo, uint32_t swz) {
    uint64_t d = 0;
    d |= (uint64_t)((saddr & 0x3FFFF) >> 4);
    d |= (uint64_t)((lbo >> 4) & 0x3FFF) << 16;
    d |= (uint64_t)((sbo >> 4) & 0x3FFF) << 32;
    d |= (uint64_t)swz << 62;
    return d;
}
__device__ __forceinline__ void wg_fence() { asm volatile("wgmma.fence.sync.aligned;" ::: "memory"); }
__device__ __forceinline__ void wg_commit() { asm volatile("wgmma.commit_group.sync.aligned;" ::: "memory"); }
template<int N> __device__ __forceinline__ void wg_wait() { asm volatile("wgmma.wait_group.sync.aligned %0;" :: "n"(N) : "memory"); }
#define A4(d, o) "+f"(d[o + 0]), "+f"(d[o + 1]), "+f"(d[o + 2]), "+f"(d[o + 3])
#define A16(d, o) A4(d, o), A4(d, o + 4), A4(d, o + 8), A4(d, o + 12)

__device__ __forceinline__ void wg_pv(float* d, const uint32_t* a, uint32_t lo, uint32_t hi) {
    asm volatile("{ .reg .b64 dd; mov.b64 dd, {%16, %17};\n"
                 "wgmma.mma_async.sync.aligned.m64n24k16.f32.bf16.bf16 {%0,%1,%2,%3,%4,%5,%6,%7,%8,%9,%10,%11}, {%12,%13,%14,%15}, dd, 1, 1, 1, 1; }"
                 : A4(d, 0), A4(d, 4), A4(d, 8) : "r"(a[0]), "r"(a[1]), "r"(a[2]), "r"(a[3]), "r"(lo), "r"(hi));
}
__device__ __forceinline__ void wg_qk(float* d, const uint32_t* a, uint32_t lo) {
    asm volatile("{ .reg .b64 dd; mov.b64 dd, {%36, %37};\n"
                 "wgmma.mma_async.sync.aligned.m64n64k16.f32.bf16.bf16 {%0,%1,%2,%3,%4,%5,%6,%7,%8,%9,%10,%11,%12,%13,%14,%15,%16,%17,%18,%19,%20,%21,%22,%23,%24,%25,%26,%27,%28,%29,%30,%31}, {%32,%33,%34,%35}, dd, 0, 1, 1, 0; }"
                 : A16(d, 0), A16(d, 16) : "r"(a[0]), "r"(a[1]), "r"(a[2]), "r"(a[3]), "r"(lo), "r"(16));
}
__device__ __forceinline__ void wg_ss32(float* d, uint64_t da, uint64_t db) {
    asm volatile("wgmma.mma_async.sync.aligned.m64n32k16.f32.bf16.bf16 {%0,%1,%2,%3,%4,%5,%6,%7,%8,%9,%10,%11,%12,%13,%14,%15}, %16, %17, 1, 1, 1, 0, 1;"
                 : A16(d, 0) : "l"(da), "l"(db));
}
__device__ __forceinline__ void wg_ss16(float* d, uint64_t da, uint64_t db) {
    asm volatile("wgmma.mma_async.sync.aligned.m64n16k16.f32.bf16.bf16 {%0,%1,%2,%3,%4,%5,%6,%7}, %8, %9, 1, 1, 1, 0, 1;"
                 : A4(d, 0), A4(d, 4) : "l"(da), "l"(db));
}
template<int N> __device__ __forceinline__ void fence_regs(float* r) {
    #pragma unroll
    for (int i = 0; i < N; i++) asm volatile("" : "+f"(r[i]) :: "memory");
}
__device__ __forceinline__ void mma_bf16(float* d, uint32_t a0, uint32_t a1, uint32_t a2, uint32_t a3, uint32_t b0, uint32_t b1) {
    asm volatile("mma.sync.aligned.m16n8k16.row.col.f32.bf16.bf16.f32 {%0,%1,%2,%3}, {%4,%5,%6,%7}, {%8,%9}, {%0,%1,%2,%3};"
                 : "+f"(d[0]), "+f"(d[1]), "+f"(d[2]), "+f"(d[3]) : "r"(a0), "r"(a1), "r"(a2), "r"(a3), "r"(b0), "r"(b1));
}
__device__ __forceinline__ void mma_f16(float* d, const uint32_t* a, uint32_t b0, uint32_t b1) {
    asm volatile("mma.sync.aligned.m16n8k16.row.col.f32.f16.f16.f32 {%0,%1,%2,%3}, {%4,%5,%6,%7}, {%8,%9}, {%0,%1,%2,%3};"
                 : "+f"(d[0]), "+f"(d[1]), "+f"(d[2]), "+f"(d[3]) : "r"(a[0]), "r"(a[1]), "r"(a[2]), "r"(a[3]), "r"(b0), "r"(b1));
}
__device__ __forceinline__ void ldsm4(uint32_t* r, uint32_t addr) {
    asm volatile("ldmatrix.sync.aligned.m8n8.x4.shared.b16 {%0,%1,%2,%3}, [%4];" : "=r"(r[0]), "=r"(r[1]), "=r"(r[2]), "=r"(r[3]) : "r"(addr) : "memory");
}
__device__ __forceinline__ void ldsm4t(uint32_t* r, uint32_t addr) {
    asm volatile("ldmatrix.sync.aligned.m8n8.x4.trans.shared.b16 {%0,%1,%2,%3}, [%4];" : "=r"(r[0]), "=r"(r[1]), "=r"(r[2]), "=r"(r[3]) : "r"(addr) : "memory");
}
__device__ __forceinline__ uint32_t lds32(uint32_t addr) { uint32_t v; asm volatile("ld.shared.u32 %0, [%1];" : "=r"(v) : "r"(addr) : "memory"); return v; }
__device__ __forceinline__ float ex2f(float x) { float r; asm("ex2.approx.ftz.f32 %0, %1;" : "=f"(r) : "f"(x)); return r; }
__device__ __forceinline__ uint32_t pack_bf16(float lo, float hi) { uint32_t r; asm("cvt.rn.bf16x2.f32 %0, %1, %2;" : "=r"(r) : "f"(hi), "f"(lo)); return r; }
__device__ __forceinline__ uint32_t pack_f16(float lo, float hi) { uint32_t r; asm("cvt.rn.f16x2.f32 %0, %1, %2;" : "=r"(r) : "f"(hi), "f"(lo)); return r; }
__device__ __forceinline__ float bf_lo(uint32_t v) { return __uint_as_float(v << 16); }
__device__ __forceinline__ float bf_hi(uint32_t v) { return __uint_as_float(v & 0xFFFF0000u); }
__device__ __forceinline__ float bf_round(float x) { return __bfloat162float(__float2bfloat16_rn(x)); }

__device__ __forceinline__ uint32_t exp_mufu(float x0, float x1) { return pack_bf16(ex2f(x0), ex2f(x1)); }
#define SW_MAGIC (256.0f + 127.0f - 0.598938f)
__device__ __forceinline__ uint32_t exp_sw(float x0, float x1, uint32_t cA, uint32_t cB) {
    float t0 = x0 + SW_MAGIC, t1 = x1 + SW_MAGIC;
    uint32_t L, mh, ec, r;
    asm("prmt.b32 %0, %1, %2, 0x6521;" : "=r"(L) : "r"(__float_as_uint(t0)), "r"(__float_as_uint(t1)));
    asm("lop3.b32 %0, %1, 0x007F007F, %2, 0xEA;" : "=r"(mh) : "r"(L), "r"(cA));
    asm("lop3.b32 %0, %1, 0x7F807F80, %2, 0xEA;" : "=r"(ec) : "r"(L), "r"(cB));
    asm("fma.rn.bf16x2 %0, %1, %2, %3;" : "=r"(r) : "r"(L), "r"(mh), "r"(ec));
    return r;
}
constexpr uint32_t MUFU_MASK = 0x4949;

struct cf { float x, y; };
__device__ __forceinline__ cf cmul(cf a, cf b) { cf r; r.x = a.x * b.x - a.y * b.y; r.y = a.x * b.y + a.y * b.x; return r; }
__device__ __forceinline__ cf cexp_p(float a2, float b, float p) {
    float e = ex2f(a2 * p);
    float ph = b * p;
    ph -= (ph + 12582912.0f) - 12582912.0f;
    float ang = ph * 6.283185307f;
    cf r; r.x = e * __cosf(ang); r.y = e * __sinf(ang);
    return r;
}
__device__ __forceinline__ uint32_t h2_cmul(uint32_t w, uint32_t wsw, uint32_t e) {
    __half2 hw = *(__half2*)&w, hs = *(__half2*)&wsw, he = *(__half2*)&e;
    __half2 r = __hfma2(hs, __high2half2(he), __hmul2(hw, __low2half2(he)));
    return *(uint32_t*)&r;
}

template<bool B> struct BoolC { static constexpr bool value = B; };
struct Params {
    const __nv_bfloat16 *u, *lar, *aim, *cre, *cim, *logdt, *dskip;
    __nv_bfloat16* out;
};

constexpr int B_O = 0, B_KV = 8, B_WO = 12, B_WQ2 = 13, B_ST = 14, B_H = 15, B_X = 17, B_U = 19, B_WQ = 20;

__device__ __forceinline__ void helper_role(const Params& P, uint8_t* sp, unsigned epoch) {
    const int tid = threadIdx.x - 544;
    const int d0 = blockIdx.x * 4;
    uint8_t* sB = sp + SM_B;
    const uint2 dsk = __ldg((const uint2*)(P.dskip + d0));
    asm volatile("barrier.cluster.wait.aligned;" ::: "memory");
    {
        const int hg = blockIdx.x & 7;
        if (hg < 4 && tid < 32) {
            bar_sync(3, 160);
            if (tid == 0) {
                const float* s_misc = (const float*)(sp + SM_BAR + 256);
                const float st = fmaxf(fmaxf(s_misc[20], s_misc[21]), fmaxf(s_misc[22], s_misc[23]));
                st_release64(&g_flag_kv[((blockIdx.x >> 3) * 2 + (hg & 1)) * 2 + (hg >> 1)], ((unsigned long long)epoch << 32) | __float_as_uint(st));
            }
            __syncwarp();
        }
    }
    PROF2(2);
    bar_sync(10, 608);
    {
        uint32_t dd[4] = {__byte_perm(dsk.x, 0, 0x1010), __byte_perm(dsk.x, 0, 0x3232), __byte_perm(dsk.y, 0, 0x1010), __byte_perm(dsk.y, 0, 0x3232)};
        #pragma unroll 2
        for (int pi = tid; pi < 1024; pi += 96) {
            const int l = 2 * pi;
            uint32_t r[4];
            #pragma unroll
            for (int cc = 0; cc < 4; cc++) {
                const uint32_t y2 = *(const uint32_t*)(sB + S_Y + cc * 4096 + l * 2);
                const uint32_t u2 = *(const uint32_t*)(sB + S_U + cc * ULEN * 2 + (PADU + l) * 2);
                __nv_bfloat162 pr = __hmul2(*(const __nv_bfloat162*)&u2, *(const __nv_bfloat162*)&dd[cc]);
                __nv_bfloat162 sm = __hadd2(*(const __nv_bfloat162*)&y2, pr);
                r[cc] = *(uint32_t*)&sm;
            }
            *(uint2*)(P.out + (size_t)l * 1024 + 512 + d0) = make_uint2(__byte_perm(r[0], r[1], 0x5410), __byte_perm(r[2], r[3], 0x5410));
            *(uint2*)(P.out + (size_t)(l + 1) * 1024 + 512 + d0) = make_uint2(__byte_perm(r[0], r[1], 0x7632), __byte_perm(r[2], r[3], 0x7632));
        }
    }
    bar_arrive(11, 128);
    PROF2(4);
}

__global__ void __cluster_dims__(2, 1, 1) __launch_bounds__(NTHR, 1)
fused_kernel(const __grid_constant__ CUtensorMap tm_x, const __grid_constant__ CUtensorMap tm_wq,
             const __grid_constant__ CUtensorMap tm_wo, const __grid_constant__ CUtensorMap tm_wk,
             const __grid_constant__ CUtensorMap tm_wv, const __grid_constant__ CUtensorMap tm_u, const Params P) {
    extern __shared__ uint8_t smem_raw[];
    const uint32_t sb = (smem_u32(smem_raw) + 1023u) & ~1023u;
    uint8_t* sp = smem_raw + (sb - smem_u32(smem_raw));

    const int tid = threadIdx.x, warp = tid >> 5, lane = tid & 31, wg = tid >> 7, wiw = warp & 3;
    const int g = lane >> 2, t = lane & 3;
    const int qb = blockIdx.x >> 3, hg = blockIdx.x & 7;
    const uint32_t rank = blockIdx.x & 1;
    const int rowhalf = wg & 1, nh = wg >> 1;
    const bool kv_cta = hg < 4;
    const int kv_sel = hg >> 1;
    const bool kv_wg = kv_cta && (wg == (hg & 1));

    const uint32_t bars = sb + SM_BAR;
    float* s_misc = (float*)(sp + SM_BAR + 256);
    const CUtensorMap* tm_kv = kv_sel ? &tm_wv : &tm_wk;

    PROF(0);
    unsigned short p_lar = 0, p_aim = 0, p_cre = 0, p_cim = 0, p_ldt = 0;
    if (wg < 4) {
        const int n = (blockIdx.x * 4 + wg) * 128 + (tid & 127);
        p_lar = __ldg((const unsigned short*)P.lar + n);
        p_aim = __ldg((const unsigned short*)P.aim + n);
        p_cre = __ldg((const unsigned short*)P.cre + n);
        p_cim = __ldg((const unsigned short*)P.cim + n);
        p_ldt = __ldg((const unsigned short*)P.logdt + blockIdx.x * 4 + wg);
    } else if (warp == 16) {
        PROF3(5);
        if (lane == 0) {
            asm volatile("prefetch.tensormap [%0];" :: "l"((uint64_t)&tm_x) : "memory");
            asm volatile("prefetch.tensormap [%0];" :: "l"((uint64_t)tm_kv) : "memory");
            asm volatile("prefetch.tensormap [%0];" :: "l"((uint64_t)&tm_wq) : "memory");
            asm volatile("prefetch.tensormap [%0];" :: "l"((uint64_t)&tm_u) : "memory");
            mbar_init(bars + 8 * B_X, 1);
            mbar_init(bars + 8 * B_X + 8, 1);
            mbar_init(bars + 8 * B_U, 1);
            asm volatile("fence.mbarrier_init.release.cluster;" ::: "memory");
            mbar_expect_tx(bars + 8 * B_X, 65536u + (kv_cta ? 8192u : 0u));
            mbar_expect_tx(bars + 8 * B_X + 8, 65536u + (kv_cta ? 8192u : 0u));
            mbar_expect_tx(bars + 8 * B_U, 32768u);
        }
        __syncwarp();
        PROF3(6);
    }
    asm volatile("barrier.cluster.arrive.relaxed.aligned;" ::: "memory");
    const unsigned epoch = *(volatile unsigned*)&g_epoch + 1u;
    if (warp > 16) {
        if (lane == 0) {
            for (int i = warp - 17; i < B_X; i += 3) {
                mbar_init(bars + 8 * i, i >= B_H ? 2 : 1);
                if (i <= B_WQ2) mbar_expect_tx(bars + 8 * i, i < B_KV + 2 ? 16384u : i == B_KV + 2 ? 32768u : i <= B_WO ? 65536u : 32768u);
            }
            asm volatile("fence.mbarrier_init.release.cluster;" ::: "memory");
            fence_async_smem();
        } else if (warp == 19) {
            asm volatile("prefetch.global.L2 [%0];" :: "l"((const char*)g_tabmap.v + (lane - 1) * 128));
            if (lane < 5) asm volatile("prefetch.global.L2 [%0];" :: "l"((const char*)g_tabmap.v + (lane + 30) * 128));
        }
        __syncwarp();
    }
    asm volatile("barrier.cluster.wait.aligned;" ::: "memory");
    PROF(5);
    if (warp == 16 && lane == 0) {
        tma_3d_mc(sb + (rank ? SM_A : SM_B), &tm_x, 0, qb * 128, rank * 4, bars + 8 * (B_X + rank));
        if (kv_cta) {
            #pragma unroll
            for (int i = 0; i < 4; i++) tma_2d(sb + SM_WKV + i * 4096, tm_kv, (i >> 1) * 8, (i & 1) * 256, bars + 8 * (B_X + (i & 1)));
        }
        mbar_init(bars + 8 * B_WQ, 1);
        asm volatile("fence.mbarrier_init.release.cluster;" ::: "memory");
        fence_async_smem();
        mbar_expect_tx(bars + 8 * B_WQ, 32768u);
        tma_2d(sb + SM_WQ, &tm_wq, hg * 64, 0, bars + 8 * B_WQ);
        #pragma unroll
        for (int i = 0; i < 4; i++) tma_2d_mc(sb + SM_SLAB + (rank * 4 + i) * 4096, &tm_u, (blockIdx.x >> 1) * 8, (rank * 4 + i) * 256, bars + 8 * B_U);
    }
    __syncwarp();
    asm volatile("barrier.cluster.arrive.relaxed.aligned;" ::: "memory");

    if (warp == 16) {
        if (lane == 0) asm volatile("prefetch.tensormap [%0];" :: "l"((uint64_t)&tm_wo) : "memory");
        asm volatile("barrier.cluster.wait.aligned;" ::: "memory");
        PROF3(10);
        bar_sync(13, 544);
        if (lane == 0) { fence_async_smem(); tma_2d(sb + SM_SLAB, &tm_wq, hg * 64, 256, bars + 8 * B_WQ2); }
        bar_sync(14, 544);
        if (lane == 0) pair_sync(bars + 8 * B_H, rank ^ 1);
        __syncwarp();
        PROF3(11);
        *(uint4*)(sp + SM_V + 32768 + lane * 32) = make_uint4(0x3F803F80u, 0x3F803F80u, 0x3F803F80u, 0x3F803F80u);
        *(uint4*)(sp + SM_V + 32768 + lane * 32 + 16) = make_uint4(0x3F803F80u, 0x3F803F80u, 0x3F803F80u, 0x3F803F80u);
        fence_async_smem();
        float km = wait_flag64(&g_flag_kv[2 * lane], epoch);
        float vm = wait_flag64(&g_flag_kv[2 * lane + 1], epoch);
        __syncwarp();
        PROF3(12);
        if (lane == 0) {
            fence_async_all();
            #pragma unroll
            for (int i = 0; i < 4; i++) {
                const uint32_t k0 = i == 0 ? 0 : 128u << i, nk = i == 0 ? 256 : 128u << i;
                const uint32_t bar = bars + 8 * (B_KV + i);
                if (rank == 0) bulk_g2s_mc(sb + SM_K + k0 * 32, g_kimg + k0 * 32, nk * 32, bar);
                else {
                    bulk_g2s_mc(sb + SM_V + k0 * 16, g_vimg + k0 * 16, nk * 16, bar);
                    bulk_g2s_mc(sb + SM_V + 66560 - (k0 + nk) * 16, g_vimg + 66560 - (k0 + nk) * 16, nk * 16, bar);
                }
            }
        }
        #pragma unroll
        for (int o = 16; o; o >>= 1) { km = fmaxf(km, __shfl_xor_sync(0xffffffffu, km, o)); vm = fmaxf(vm, __shfl_xor_sync(0xffffffffu, vm, o)); }
        if (lane == 0) { s_misc[16] = km; s_misc[17] = vm; mbar_arrive(bars + 8 * B_ST); }
        PROF3(13);
        bar_sync(11, 128);
        if (lane < 2) { fence_async_smem(); tma_2d(sb + SM_B + lane * 32768, &tm_wo, hg * 64, lane * 256, bars + 8 * B_WO); }
        bar_sync(12, 544);
        if (lane == 0) {
            st_release(&g_flag_o[blockIdx.x], epoch);
            pair_sync(bars + 8 * (B_H + 1), rank ^ 1);
        }
        __syncwarp();
        PROF3(14);
        if (lane < 4) {
            const int src = 2 * lane + rank;
            wait_flag(&g_flag_o[qb * 8 + src], epoch);
            fence_async_all();
            bulk_g2s_mc(sb + SM_A + src * 16384, g_oimg + qb * 131072 + src * 16384, 16384, bars + 8 * (B_O + src));
        }
        __syncwarp();
        PROF3(15);
        if (lane == 0) {
            const unsigned prev = atomicAdd(&g_done, 1u);
            if (prev == NCTA - 1) {
                g_done = 0;
                __threadfence();
                *(volatile unsigned*)&g_epoch = epoch;
            }
        }
    } else if (wg == 4) {
        helper_role(P, sp, epoch);
    } else {
        uint8_t* sB = sp + SM_B;
        const uint32_t sBa = sb + SM_B;
        {
            const int c = wg;
            const float dt = bf_round(expf(bf_lo(p_ldt)));
            const float are = -bf_round(expf(bf_lo(p_lar))) * dt;
            const float aim = bf_lo(p_aim) * dt;
            float cr = 2.0f * (bf_lo(p_cre) * dt);
            float ci = 2.0f * (bf_lo(p_cim) * dt);
            const float a2 = are * 1.4426950408889634f, bb = aim * 0.15915494309189535f;
            float m = fmaxf(fabsf(cr), fabsf(ci));
            #pragma unroll
            for (int o = 16; o; o >>= 1) m = fmaxf(m, __shfl_xor_sync(0xffffffffu, m, o));
            int ebits = (__float_as_uint(m) >> 23) & 0xFF;
            ebits = min(max(ebits, 2), 250);
            const float scale = __uint_as_float((uint32_t)(ebits + 1) << 23);
            const float iscale = __uint_as_float((uint32_t)(253 - ebits) << 23);
            cf cc; cc.x = cr * iscale; cc.y = ci * iscale;

            const uint32_t stg = sBa + S_KC + warp * 1024;
            uint4* stp = (uint4*)(sB + S_KC + warp * 1024 + lane * 32);
            const uint32_t fa = stg + t * 32 + g * 4;

            uint32_t af[4][2][4];
            cf E256;
            {
                const cf E8 = cexp_p(a2, bb, 8.0f);
                uint32_t w[8];
                cf cur; cur.x = 1.0f; cur.y = 0.0f;
                w[0] = pack_f16(1.0f, 0.0f);
                cur = E8; w[1] = pack_f16(cur.x, cur.y);
                #pragma unroll
                for (int i = 2; i < 8; i++) { cur = cmul(cur, E8); w[i] = pack_f16(cur.x, cur.y); }
                stp[0] = make_uint4(w[0], w[1], w[2], w[3]);
                stp[1] = make_uint4(w[4], w[5], w[6], w[7]);
                const cf E64 = cexp_p(a2, bb, 64.0f);
                const cf E128 = cmul(E64, E64), E192 = cmul(E128, E64);
                E256 = cexp_p(a2, bb, 256.0f);
                const uint32_t e1 = pack_f16(E64.x, E64.y), e2 = pack_f16(E128.x, E128.y), e3 = pack_f16(E192.x, E192.y);
                __syncwarp();
                #pragma unroll
                for (int s = 0; s < 4; s++) {
                    #pragma unroll
                    for (int hh = 0; hh < 2; hh++) {
                        const uint32_t w0 = lds32(fa + s * 256 + hh * 128);
                        const uint32_t wsw = __byte_perm(w0, 0, 0x1032) ^ 0x00008000u;
                        const int src = 8 * s + t + 4 * hh;
                        const uint32_t f1 = __shfl_sync(0xffffffffu, e1, src), f2 = __shfl_sync(0xffffffffu, e2, src), f3 = __shfl_sync(0xffffffffu, e3, src);
                        af[s][0][2 * hh] = w0;
                        af[s][0][2 * hh + 1] = h2_cmul(w0, wsw, f1);
                        af[s][1][2 * hh] = h2_cmul(w0, wsw, f2);
                        af[s][1][2 * hh + 1] = h2_cmul(w0, wsw, f3);
                    }
                }
                __syncwarp();
            }
            float acc[2][3][4];
            #pragma unroll
            for (int i = 0; i < 24; i++) (&acc[0][0][0])[i] = 0.0f;
            const cf E1 = cexp_p(a2, bb, 1.0f);
            const cf E2 = cmul(E1, E1), E4 = cmul(E2, E2);
            cf X512;
            #pragma unroll
            for (int nt = 0; nt < 3; nt++) {
                uint32_t xv[8];
                if (nt == 0) {
                    cf cur = cc;
                    xv[0] = pack_f16(cur.x, -cur.y);
                    #pragma unroll
                    for (int i = 1; i < 8; i++) { cur = cmul(cur, E1); xv[i] = pack_f16(cur.x, -cur.y); }
                } else if (nt == 1) {
                    cf cur = cmul(cc, E256);
                    X512 = cmul(cur, E256);
                    xv[0] = pack_f16(cur.x, -cur.y);
                    #pragma unroll
                    for (int i = 1; i < 4; i++) { cur = cmul(cur, E2); xv[i] = pack_f16(cur.x, -cur.y); }
                    cur = cmul(X512, E4);
                    xv[4] = pack_f16(X512.x, -X512.y); xv[5] = pack_f16(cur.x, -cur.y);
                    X512 = cmul(X512, E256);
                    cur = cmul(X512, E4);
                    xv[6] = pack_f16(X512.x, -X512.y); xv[7] = pack_f16(cur.x, -cur.y);
                } else {
                    cf cur = X512;
                    #pragma unroll
                    for (int i = 0; i < 5; i++) { cur = cmul(cur, E256); xv[i] = pack_f16(cur.x, -cur.y); }
                    xv[5] = 0; xv[6] = 0; xv[7] = 0;
                }
                stp[0] = make_uint4(xv[0], xv[1], xv[2], xv[3]);
                stp[1] = make_uint4(xv[4], xv[5], xv[6], xv[7]);
                __syncwarp();
                #pragma unroll
                for (int s = 0; s < 4; s++) {
                    const uint32_t b0 = lds32(fa + s * 256), b1 = lds32(fa + s * 256 + 128);
                    mma_f16(acc[0][nt], af[s][0], b0, b1);
                    mma_f16(acc[1][nt], af[s][1], b0, b1);
                }
                __syncwarp();
            }
            float* kc = (float*)(sB + S_KC + c * 4096);
            bar_sync(4 + c, 128);
            #pragma unroll 1
            for (int step = 0; step < 4; step++) {
                if ((warp & 3) == step) {
                    #pragma unroll
                    for (int mt = 0; mt < 2; mt++)
                        #pragma unroll
                        for (int nt = 0; nt < 3; nt++)
                            #pragma unroll
                            for (int hh = 0; hh < 2; hh++) {
                                float2* p = (float2*)(kc + (mt * 16 + hh * 8 + g) * 24 + nt * 8 + 2 * t);
                                float2 v = make_float2(acc[mt][nt][2 * hh] * scale, acc[mt][nt][2 * hh + 1] * scale);
                                if (step) { float2 o = *p; v.x += o.x; v.y += o.y; }
                                *p = v;
                            }
                }
                if (step < 3) bar_sync(4 + c, 128);
            }
        }

        asm volatile("barrier.cluster.wait.aligned;" ::: "memory");
        PROF(4);
        uint32_t q[2][4];
        {
            float acc[16], akv[8];
            #pragma unroll
            for (int i = 0; i < 16; i++) acc[i] = 0.0f;
            #pragma unroll
            for (int i = 0; i < 8; i++) akv[i] = 0.0f;
            fence_regs<16>(acc);
            fence_regs<8>(akv);
            const uint64_t dA0 = make_desc(sb + SM_B + rowhalf * 8192, 16, 1024, 1);
            const uint64_t dA1 = make_desc(sb + SM_A + rowhalf * 8192, 16, 1024, 1) - 4096;
            const uint64_t dB = make_desc(sb + SM_WQ + nh * 64, 16, 1024, 1);
            const uint64_t dC = make_desc(sb + SM_WKV, 128, 8192, 0);
            if (kv_wg) {
                #pragma unroll 1
                for (int ch = 0; ch < 8; ch++) {
                    if ((ch & 3) == 0) mbar_wait(bars + 8 * (B_X + (ch >> 2)), 0);
                    const uint64_t dA = ch < 4 ? dA0 : dA1;
                    wg_fence();
                    #pragma unroll
                    for (int ks = 0; ks < 4; ks++) wg_ss16(akv, dA + ch * 1024 + ks * 2, dC + (ch * 4 + ks) * 16);
                    wg_commit();
                }
                wg_wait<0>();
            }
            fence_regs<8>(akv);
            if (kv_wg) {
                const int key = qb * 128 + rowhalf * 64 + wiw * 16 + g;
                uint32_t pk[4];
                #pragma unroll
                for (int i = 0; i < 4; i++) pk[i] = pack_bf16(akv[2 * i], akv[2 * i + 1]);
                float st;
                if (kv_sel == 0) {
                    uint8_t* b = g_kimg + (key >> 3) * 256 + (key & 7) * 16 + 4 * t;
                    *(uint32_t*)(b) = pk[0]; *(uint32_t*)(b + 256) = pk[1]; *(uint32_t*)(b + 128) = pk[2]; *(uint32_t*)(b + 384) = pk[3];
                    float n0 = bf_lo(pk[0]) * bf_lo(pk[0]) + bf_hi(pk[0]) * bf_hi(pk[0]) + bf_lo(pk[2]) * bf_lo(pk[2]) + bf_hi(pk[2]) * bf_hi(pk[2]);
                    float n1 = bf_lo(pk[1]) * bf_lo(pk[1]) + bf_hi(pk[1]) * bf_hi(pk[1]) + bf_lo(pk[3]) * bf_lo(pk[3]) + bf_hi(pk[3]) * bf_hi(pk[3]);
                    n0 += __shfl_xor_sync(0xffffffffu, n0, 1); n0 += __shfl_xor_sync(0xffffffffu, n0, 2);
                    n1 += __shfl_xor_sync(0xffffffffu, n1, 1); n1 += __shfl_xor_sync(0xffffffffu, n1, 2);
                    st = (n0 != n0 || n1 != n1) ? __int_as_float(0x7f800000) : fmaxf(n0, n1);
                } else {
                    uint8_t* lo = g_vimg + key * 16 + 4 * t;
                    uint8_t* hi = g_vimg + 33792 + (31 - (key >> 6)) * 1024 + (key & 63) * 16 + 4 * t;
                    *(uint32_t*)(lo) = pk[0]; *(uint32_t*)(lo + 128) = pk[1]; *(uint32_t*)(hi) = pk[2]; *(uint32_t*)(hi + 128) = pk[3];
                    st = 0.0f;
                    #pragma unroll
                    for (int i = 0; i < 4; i++) {
                        float a = fabsf(bf_lo(pk[i])), b = fabsf(bf_hi(pk[i]));
                        st = (a != a || b != b) ? __int_as_float(0x7f800000) : fmaxf(st, fmaxf(a, b));
                    }
                }
                #pragma unroll
                for (int o = 16; o; o >>= 1) st = fmaxf(st, __shfl_xor_sync(0xffffffffu, st, o));
                if (lane == 0) s_misc[20 + wiw] = st;
                bar_arrive(3, 160);
            }
            uint32_t mp[9];
            #pragma unroll
            for (int i = 0; i < 9; i++) { const int w = (tid & 127) + 128 * i; mp[i] = (w < TABN / 2) ? __ldg((const uint32_t*)g_tabmap.v + w) : 0u; }
            mbar_wait(bars + 8 * B_WQ, 0);
            mbar_wait(bars + 8 * B_X, 0);
            PROF(2);
            #pragma unroll 1
            for (int ch = 0; ch < 4; ch++) {
                wg_fence();
                #pragma unroll
                for (int ks = 0; ks < 4; ks++) wg_ss32(acc, dA0 + ch * 1024 + ks * 2, dB + (ch * 4 + ks) * 128);
                wg_commit();
            }
            wg_wait<0>();
            fence_regs<16>(acc);
            bar_sync(1, 512);
            PROF(15);
            if (tid < 4 * (PADU / 8)) *(uint4*)(sB + S_U + (tid / (PADU / 8)) * ULEN * 2 + (tid % (PADU / 8)) * 16) = make_uint4(0, 0, 0, 0);
            PROF(8);
            mbar_wait(bars + 8 * B_U, 0);
            PROF(14);
            #pragma unroll
            for (int i = 0; i < 2; i++) {
                const int l = 2 * (tid + 512 * i);
                const uint2 r0 = *(const uint2*)(sp + SM_SLAB + l * 16 + rank * 8), r1 = *(const uint2*)(sp + SM_SLAB + l * 16 + 16 + rank * 8);
                uint32_t* dst = (uint32_t*)(sB + S_U + (PADU + l) * 2);
                dst[0] = __byte_perm(r0.x, r1.x, 0x5410);
                dst[ULEN / 2] = __byte_perm(r0.x, r1.x, 0x7632);
                dst[ULEN] = __byte_perm(r0.y, r1.y, 0x5410);
                dst[3 * ULEN / 2] = __byte_perm(r0.y, r1.y, 0x7632);
            }
            bar_arrive(13, 544);
            {
                const float* kc = (const float*)(sB + S_KC + wg * 4096);
                uint32_t* tab = (uint32_t*)(sB + S_TAB + wg * TABN * 2);
                #pragma unroll
                for (int i = 0; i < 9; i++) { const int w = (tid & 127) + 128 * i; if (w < TABN / 2) tab[w] = pack_bf16(kc[mp[i] & 0xFFFF], kc[mp[i] >> 16]); }
            }
            bar_sync(1, 512);
            #pragma unroll 1
            for (int task = tid; task < 4 * 194; task += 512) {
                const int c = task / 194, i = task % 194;
                const uint4* src = (const uint4*)(sB + S_U + c * ULEN * 2 + (PADU + 8 * i - WPAD - 8) * 2);
                const uint4 v0 = src[0], v1 = src[1], v2 = src[2];
                float x[24];
                const uint32_t vv[12] = {v0.x, v0.y, v0.z, v0.w, v1.x, v1.y, v1.z, v1.w, v2.x, v2.y, v2.z, v2.w};
                #pragma unroll
                for (int k = 0; k < 12; k++) { x[2 * k] = bf_lo(vv[k]); x[2 * k + 1] = bf_hi(vv[k]); }
                float w3[12], w5[8];
                #pragma unroll
                for (int e = 0; e < 12; e++) w3[e] = (x[3 + e] + x[4 + e]) + x[5 + e];
                #pragma unroll
                for (int e = 0; e < 8; e++) w5[e] = w3[4 + e] + (x[6 + e] + x[10 + e]);
                *(uint4*)(sB + S_W3 + c * W2LEN * 2 + i * 16) = make_uint4(pack_bf16(w3[0], w3[1]), pack_bf16(w3[2], w3[3]), pack_bf16(w3[4], w3[5]), pack_bf16(w3[6], w3[7]));
                *(uint4*)(sB + S_W5 + c * W2LEN * 2 + i * 16) = make_uint4(pack_bf16(w5[0], w5[1]), pack_bf16(w5[2], w5[3]), pack_bf16(w5[4], w5[5]), pack_bf16(w5[6], w5[7]));
                if (i < 130) {
                    float w7[8], w9[8];
                    #pragma unroll
                    for (int e = 0; e < 8; e++) { w7[e] = w5[e] + (x[5 + e] + x[11 + e]); w9[e] = w7[e] + (x[4 + e] + x[12 + e]); }
                    *(uint4*)(sB + S_W7 + c * W3LEN * 2 + i * 16) = make_uint4(pack_bf16(w7[0], w7[1]), pack_bf16(w7[2], w7[3]), pack_bf16(w7[4], w7[5]), pack_bf16(w7[6], w7[7]));
                    *(uint4*)(sB + S_W9 + c * W3LEN * 2 + i * 16) = make_uint4(pack_bf16(w9[0], w9[1]), pack_bf16(w9[2], w9[3]), pack_bf16(w9[4], w9[5]), pack_bf16(w9[6], w9[7]));
                }
            }
            PROF(1);
            mbar_wait(bars + 8 * B_WQ2, 0);
            mbar_wait(bars + 8 * (B_X + 1), 0);
            fence_regs<16>(acc);
            #pragma unroll 1
            for (int ch = 4; ch < 8; ch++) {
                wg_fence();
                #pragma unroll
                for (int ks = 0; ks < 4; ks++) wg_ss32(acc, dA1 + ch * 1024 + ks * 2, dB + (ch * 4 + ks) * 128);
                wg_commit();
            }
            wg_wait<0>();
            fence_regs<16>(acc);
            bar_arrive(14, 544);
            const float QS = 0.25f * 1.4426950408889634f;
            float qm = 0.0f;
            #pragma unroll
            for (int i = 0; i < 2; i++) {
                #pragma unroll
                for (int j = 0; j < 4; j++) q[i][j] = pack_bf16(acc[8 * i + 2 * j] * QS, acc[8 * i + 2 * j + 1] * QS);
                float n0 = bf_lo(q[i][0]) * bf_lo(q[i][0]) + bf_hi(q[i][0]) * bf_hi(q[i][0]) + bf_lo(q[i][2]) * bf_lo(q[i][2]) + bf_hi(q[i][2]) * bf_hi(q[i][2]);
                float n1 = bf_lo(q[i][1]) * bf_lo(q[i][1]) + bf_hi(q[i][1]) * bf_hi(q[i][1]) + bf_lo(q[i][3]) * bf_lo(q[i][3]) + bf_hi(q[i][3]) * bf_hi(q[i][3]);
                n0 += __shfl_xor_sync(0xffffffffu, n0, 1); n0 += __shfl_xor_sync(0xffffffffu, n0, 2);
                n1 += __shfl_xor_sync(0xffffffffu, n1, 1); n1 += __shfl_xor_sync(0xffffffffu, n1, 2);
                qm = (n0 != n0 || n1 != n1) ? __int_as_float(0x7f800000) : fmaxf(qm, fmaxf(n0, n1));
            }
            #pragma unroll
            for (int o = 16; o; o >>= 1) qm = fmaxf(qm, __shfl_xor_sync(0xffffffffu, qm, o));
            if (lane == 0) s_misc[warp] = qm;
        }
        bar_sync(1, 512);
        PROF(3);
        PROF(6);
        {
            const int c = warp >> 2, grp = (warp + c) & 3;
            float acc[4][4];
            #pragma unroll
            for (int i = 0; i < 16; i++) (&acc[0][0])[i] = 0.0f;
            const uint32_t tabc = sBa + S_TAB + c * TABN * 2;
            const int e2 = (g - 2 * t) * 2;
            const uint32_t tD = tabc + ((g & 1) ? (TD1 + CD + 1) : (TD0 + CD)) * 2 - e2;
            const uint32_t tE = tabc + ((g & 1) ? (TE1 + CE + 1) : (TE0 + CE)) * 2 - e2;
            const uint32_t t2 = tabc + (T2B + ((g & 1) ? (T2C + C2 + 1) : C2)) * 2 - e2;
            const uint32_t t3 = tabc + (T3B + ((g & 1) ? (T3C + C3 + 1) : C3)) * 2 - e2;
            const int mi = lane >> 3, r8 = lane & 7;
            const uint32_t ub = sBa + S_U + c * ULEN * 2 + (PADU + 16 * (8 * (mi >> 1) + r8) + 8 * (mi & 1)) * 2 + (4 * grp - 4) * 256;
            #pragma unroll 1
            for (int rho = 0; rho < 8; rho++) {
                uint32_t R[5][3];
                #pragma unroll
                for (int qq = 0; qq < 5; qq++) {
                    if (qq < 4 || rho < 2) {
                        const uint32_t a = tD - 32 * (rho + 8 * qq);
                        R[qq][0] = lds32(a + 16); R[qq][1] = lds32(a); R[qq][2] = lds32(a - 16);
                    } else { R[qq][0] = 0; R[qq][1] = 0; R[qq][2] = 0; }
                }
                #pragma unroll
                for (int jp = 0; jp < 4; jp++) {
                    if (grp == 0 && (jp == 0 || (jp == 1 && rho > 0))) continue;
                    if (jp == 0 && rho >= 2) {
                        uint32_t b[4];
                        ldsm4(b, ub + jp * 512 - rho * 32);
                        mma_bf16(acc[0], R[3][1], R[3][2], R[3][0], R[3][1], b[2], b[3]);
                        continue;
                    }
                    uint32_t b[4];
                    ldsm4(b, ub + jp * 512 - rho * 32);
                    #pragma unroll
                    for (int hh = 0; hh < 2; hh++) {
                        #pragma unroll
                        for (int qq = 0; qq < 5; qq++) {
                            const int jr = 2 * jp + hh + qq - 4;
                            if (jr >= 0 && jr < 4) {
                                if (qq < 4 || rho < 2) mma_bf16(acc[jr], R[qq][1], R[qq][2], R[qq][0], R[qq][1], b[2 * hh], b[2 * hh + 1]);
                            }
                        }
                    }
                }
            }
            if (grp >= 2) {
                uint32_t R[5];
                #pragma unroll
                for (int i = 0; i < 5; i++) R[i] = lds32(tE - 16 * (127 + i));
                #pragma unroll
                for (int kk = 0; kk < 2; kk++) {
                    #pragma unroll
                    for (int jp = 0; jp < 2; jp++) {
                        uint32_t b[4];
                        ldsm4(b, ub + (4 + 2 * jp) * 256 - (64 + kk) * 32);
                        mma_bf16(acc[2 * jp], R[2 * kk + 1], R[2 * kk + 2], R[2 * kk], R[2 * kk + 1], b[0], b[1]);
                        mma_bf16(acc[2 * jp + 1], R[2 * kk + 1], R[2 * kk + 2], R[2 * kk], R[2 * kk + 1], b[2], b[3]);
                    }
                }
            }
            const uint32_t soff = (WPAD + 16 * (8 * (mi >> 1) + r8) + 8 * (mi & 1)) * 2 + grp * 1024;
            if (grp >= 1) {
                #pragma unroll 1
                for (int s = 0; s < 4; s++) {
                    const uint32_t sig = sBa + ((s & 1) ? S_W3 : S_W5) + c * W2LEN * 2 + soff - ((s == 0) ? 32 : (s == 1) ? 0 : 16);
                    uint32_t R[7];
                    #pragma unroll
                    for (int i = 0; i < 7; i++) R[i] = lds32(t2 + s * (T2S * 2) - 16 * (3 + i));
                    #pragma unroll
                    for (int bb = 1; bb <= 4; bb++) {
                        if (2 * grp - bb < 0) continue;
                        uint32_t a[4];
                        ldsm4t(a, sig - bb * 512);
                        #pragma unroll
                        for (int jj = 0; jj < 4; jj++) {
                            const int h = jj + 2 * bb;
                            if (h >= 4 && h <= 9) mma_bf16(acc[jj], a[0], a[1], a[2], a[3], R[h - 3], R[h - 4]);
                        }
                    }
                }
            }
            if (grp >= 2) {
                #pragma unroll 1
                for (int s = 0; s < 2; s++) {
                    const uint32_t sig = sBa + (s ? S_W7 : S_W9) + c * W3LEN * 2 + soff - (s ? 16 : 32);
                    uint32_t R[9];
                    #pragma unroll
                    for (int i = 0; i < 9; i++) R[i] = lds32(t3 + s * (T3S * 2) - 16 * (7 + i));
                    #pragma unroll
                    for (int bb = 3; bb <= 6; bb++) {
                        if (2 * grp - bb < 0) continue;
                        uint32_t a[4];
                        ldsm4t(a, sig - bb * 512);
                        #pragma unroll
                        for (int jj = 0; jj < 4; jj++) {
                            const int h = jj + 2 * bb;
                            if (h >= 8 && h <= 15) mma_bf16(acc[jj], a[0], a[1], a[2], a[3], R[h - 7], R[h - 8]);
                        }
                    }
                }
            }
            __nv_bfloat16* ys = (__nv_bfloat16*)(sB + S_Y + c * 4096);
            #pragma unroll
            for (int jj = 0; jj < 4; jj++) {
                const int A = 8 * (4 * grp + jj) + 2 * t;
                ys[16 * A + g] = __float2bfloat16_rn(acc[jj][0]);
                ys[16 * A + 16 + g] = __float2bfloat16_rn(acc[jj][1]);
                ys[16 * A + g + 8] = __float2bfloat16_rn(acc[jj][2]);
                ys[16 * A + 16 + g + 8] = __float2bfloat16_rn(acc[jj][3]);
            }
        }
        bar_arrive(10, 608);
        PROF(7);
        {
            mbar_wait(bars + 8 * B_ST, 0);
            PROF(9); PROFC(8);
            float qm = 0.0f;
            #pragma unroll
            for (int i = 0; i < 16; i++) qm = fmaxf(qm, s_misc[i]);
            const float vm = s_misc[17];
            const bool fast = (qm * s_misc[16] <= 60.0f * 60.0f) && (vm <= 1.0e12f) && (vm >= 1.0e-12f || vm == 0.0f);
            uint8_t* ob = g_oimg + qb * 131072 + hg * 16384 + nh * 8192 + (rowhalf * 8 + wiw * 2) * 128 + g * 16 + 4 * t;
            uint32_t cA = 0xBF00BF00u, cB = 0x00030003u;
            asm volatile("" : "+r"(cA), "+r"(cB));
            #pragma unroll 1
            for (int tile = 0; tile < 2; tile++) {
                uint32_t kLo = (((sb + SM_K) & 0x3FFFF) >> 4) | (8u << 16), vLo = (((sb + SM_V) & 0x3FFFF) >> 4) | (8u << 16), vHi = 2048;
                float o[12], s[32];
                uint32_t p[16], qq[4];
                #pragma unroll
                for (int i = 0; i < 4; i++) { qq[i] = tile ? q[1][i] : q[0][i]; asm volatile("" : "+r"(qq[i])); }
                #pragma unroll
                for (int i = 0; i < 12; i++) o[i] = 0.0f;
                #pragma unroll
                for (int i = 0; i < 32; i++) s[i] = 0.0f;
                fence_regs<12>(o);
                fence_regs<32>(s);
                if (fast) {
                    #pragma unroll 1
                    for (int c = 0; c < SEQ / 256; c++) {
                        if (c <= 4) mbar_wait(bars + 8 * (B_KV + (c < 2 ? c : c < 4 ? 2 : 3)), 0);
                        wg_fence();
                        wg_qk(s, qq, kLo);
                        wg_commit();
                        #pragma unroll
                        for (int u = 0; u < 4; u++) {
                            wg_wait<0>();
                            fence_regs<32>(s);
                            #pragma unroll
                            for (int i = 0; i < 16; i++) {
                                if ((MUFU_MASK >> i) & 1) p[i] = exp_mufu(s[2 * i], s[2 * i + 1]);
                                else p[i] = exp_sw(s[2 * i], s[2 * i + 1], cA, cB);
                            }
                            wg_fence();
                            if (u + 1 < 4) wg_qk(s, qq, kLo + (u + 1) * 128);
                            #pragma unroll
                            for (int kk = 0; kk < 4; kk++) wg_pv(o, p + 4 * kk, vLo + u * 64 + kk * 16, vHi - u * 64);
                            wg_commit();
                        }
                        kLo += 512; vLo += 256; vHi -= 256;
                    }
                    wg_wait<0>();
                } else {
                    float mx0 = -INFINITY, mx1 = -INFINITY;
                    #pragma unroll 1
                    for (int c = 0; c < SEQ / 64; c++) {
                        if (c <= 16) mbar_wait(bars + 8 * (B_KV + (c < 8 ? (c >> 2) : c < 16 ? 2 : 3)), 0);
                        wg_fence();
                        wg_qk(s, qq, kLo);
                        wg_commit();
                        wg_wait<0>();
                        fence_regs<32>(s);
                        fence_regs<12>(o);
                        float m0 = mx0, m1 = mx1;
                        #pragma unroll
                        for (int j = 0; j < 8; j++) {
                            m0 = fmaxf(m0, fmaxf(s[4 * j], s[4 * j + 1]));
                            m1 = fmaxf(m1, fmaxf(s[4 * j + 2], s[4 * j + 3]));
                        }
                        m0 = fmaxf(m0, __shfl_xor_sync(0xffffffffu, m0, 1)); m0 = fmaxf(m0, __shfl_xor_sync(0xffffffffu, m0, 2));
                        m1 = fmaxf(m1, __shfl_xor_sync(0xffffffffu, m1, 1)); m1 = fmaxf(m1, __shfl_xor_sync(0xffffffffu, m1, 2));
                        const float c0 = ex2f(mx0 - m0), c1 = ex2f(mx1 - m1);
                        mx0 = m0; mx1 = m1;
                        #pragma unroll
                        for (int j = 0; j < 3; j++) { o[4 * j] *= c0; o[4 * j + 1] *= c0; o[4 * j + 2] *= c1; o[4 * j + 3] *= c1; }
                        #pragma unroll
                        for (int j = 0; j < 8; j++) {
                            p[2 * j] = exp_mufu(s[4 * j] - m0, s[4 * j + 1] - m0);
                            p[2 * j + 1] = exp_mufu(s[4 * j + 2] - m1, s[4 * j + 3] - m1);
                        }
                        wg_fence();
                        #pragma unroll
                        for (int kk = 0; kk < 4; kk++) wg_pv(o, p + 4 * kk, vLo + kk * 16, vHi);
                        wg_commit();
                        wg_wait<0>();
                        kLo += 128; vLo += 64; vHi -= 64;
                    }
                }
                fence_regs<12>(o);
                const float i0 = 1.0f / o[4], i1 = 1.0f / o[6];
                uint8_t* b = ob + tile * 4096;
                *(uint32_t*)(b) = pack_bf16(o[0] * i0, o[1] * i0);
                *(uint32_t*)(b + 128) = pack_bf16(o[2] * i1, o[3] * i1);
                *(uint32_t*)(b + 2048) = pack_bf16(o[8] * i0, o[9] * i0);
                *(uint32_t*)(b + 2048 + 128) = pack_bf16(o[10] * i1, o[11] * i1);
            }
        }
        PROF(10); PROFC(9);
        bar_arrive(12, 544);

        {
            float acc[16];
            #pragma unroll
            for (int i = 0; i < 16; i++) acc[i] = 0.0f;
            fence_regs<16>(acc);
            const uint64_t dA = make_desc(sb + SM_A + rowhalf * 1024, 2048, 128, 0);
            const uint64_t dB = make_desc(sb + SM_B + nh * 64, 16, 1024, 1);
            mbar_wait(bars + 8 * B_WO, 0);
            #pragma unroll 1
            for (int i = 0; i < 8; i++) {
                const int src = (hg + i) & 7;
                mbar_wait(bars + 8 * (B_O + src), 0);
                wg_fence();
                #pragma unroll
                for (int kk = 0; kk < 4; kk++) wg_ss32(acc, dA + src * 1024 + kk * 256, dB + (src * 4 + kk) * 128);
                wg_commit();
            }
            wg_wait<0>();
            fence_regs<16>(acc);
            PROF(12);
            const int row = qb * 128 + rowhalf * 64 + wiw * 16 + g;
            uint32_t* o32 = (uint32_t*)(P.out + (size_t)row * 1024 + hg * 64 + nh * 32 + 2 * t);
            #pragma unroll
            for (int j = 0; j < 4; j++) {
                o32[4 * j] = pack_bf16(acc[4 * j], acc[4 * j + 1]);
                o32[4 * j + 8 * 512] = pack_bf16(acc[4 * j + 2], acc[4 * j + 3]);
            }
        }
        PROF(13);
    }
}

typedef CUresult (*EncodeFn)(CUtensorMap*, CUtensorMapDataType, cuuint32_t, void*, const cuuint64_t*, const cuuint64_t*,
                             const cuuint32_t*, const cuuint32_t*, CUtensorMapInterleave, CUtensorMapSwizzle,
                             CUtensorMapL2promotion, CUtensorMapFloatOOBfill);

void make_map(EncodeFn fn, CUtensorMap* m, const void* ptr, uint64_t inner, uint64_t outer, uint32_t box_in, uint32_t box_out, CUtensorMapSwizzle swz) {
    cuuint64_t dims[2] = {inner, outer};
    cuuint64_t strides[1] = {inner * 2};
    cuuint32_t box[2] = {box_in, box_out};
    cuuint32_t es[2] = {1, 1};
    fn(m, CU_TENSOR_MAP_DATA_TYPE_BFLOAT16, 2, const_cast<void*>(ptr), dims, strides, box, es, CU_TENSOR_MAP_INTERLEAVE_NONE, swz,
       CU_TENSOR_MAP_L2_PROMOTION_L2_128B, CU_TENSOR_MAP_FLOAT_OOB_FILL_NONE);
}

}

extern "C" void kernel_launch(void* const* d_in, const int* in_sizes, int n_in, void* d_out, int out_size) {
    (void)in_sizes; (void)n_in; (void)out_size;
    static EncodeFn fn = nullptr;
    if (!fn) {
        void* p = nullptr;
        cudaDriverEntryPointQueryResult qr;
        cudaGetDriverEntryPoint("cuTensorMapEncodeTiled", &p, cudaEnableDefault, &qr);
        fn = (EncodeFn)p;
        cudaFuncSetAttribute(fused_kernel, cudaFuncAttributeMaxDynamicSharedMemorySize, SM_ALLOC);
    }
    CUtensorMap tx, twq, two, twk, twv, tu;
    {
        cuuint64_t dims[3] = {64, 2048, 8};
        cuuint64_t strides[2] = {1024, 128};
        cuuint32_t box[3] = {64, 128, 4};
        cuuint32_t es[3] = {1, 1, 1};
        fn(&tx, CU_TENSOR_MAP_DATA_TYPE_BFLOAT16, 3, d_in[0], dims, strides, box, es, CU_TENSOR_MAP_INTERLEAVE_NONE, CU_TENSOR_MAP_SWIZZLE_128B,
           CU_TENSOR_MAP_L2_PROMOTION_L2_128B, CU_TENSOR_MAP_FLOAT_OOB_FILL_NONE);
    }
    make_map(fn, &tu, d_in[5], 512, 2048, 8, 256, CU_TENSOR_MAP_SWIZZLE_NONE);
    make_map(fn, &twq, d_in[1], 512, 512, 64, 256, CU_TENSOR_MAP_SWIZZLE_128B);
    make_map(fn, &twk, d_in[2], 16, 512, 8, 256, CU_TENSOR_MAP_SWIZZLE_NONE);
    make_map(fn, &twv, d_in[3], 16, 512, 8, 256, CU_TENSOR_MAP_SWIZZLE_NONE);
    make_map(fn, &two, d_in[4], 512, 512, 64, 256, CU_TENSOR_MAP_SWIZZLE_128B);
    Params P;
    P.u = (const __nv_bfloat16*)d_in[5];
    P.lar = (const __nv_bfloat16*)d_in[6];
    P.aim = (const __nv_bfloat16*)d_in[7];
    P.cre = (const __nv_bfloat16*)d_in[8];
    P.cim = (const __nv_bfloat16*)d_in[9];
    P.logdt = (const __nv_bfloat16*)d_in[10];
    P.dskip = (const __nv_bfloat16*)d_in[11];
    P.out = (__nv_bfloat16*)d_out;
    fused_kernel<<<NCTA, NTHR, SM_ALLOC>>>(tx, twq, two, twk, twv, tu, P);
}
```

```cpp
#include <cuda_runtime.h>
#include <cuda_bf16.h>
#include <cuda_fp16.h>
#include <cuda.h>
#include <stdint.h>

namespace {

constexpr int SEQ = 2048;
constexpr int NCTA = 128, NTHR = 640;

constexpr int SM_A = 0;
constexpr int SM_WQ = 65536;
constexpr int SM_SLAB = SM_WQ + 32768;
constexpr int SM_K = 0, SM_V = 65536;
constexpr int SM_B = 132096;
constexpr int SM_WKV = SM_B + 65536;

constexpr int PADU = 288, ULEN = PADU + 2048;
constexpr int WPAD = 16, W2LEN = WPAD + 1536, W3LEN = WPAD + 1024;
constexpr int TABN = 2240;
constexpr int S_U = 0;
constexpr int S_W3 = S_U + 4 * ULEN * 2;
constexpr int S_W5 = S_W3 + 4 * W2LEN * 2;
constexpr int S_W7 = S_W5 + 4 * W2LEN * 2;
constexpr int S_W9 = S_W7 + 4 * W3LEN * 2;
constexpr int S_TAB = S_W9 + 4 * W3LEN * 2;
constexpr int S_KC = 214016 - SM_B;
constexpr int S_Y = S_KC;
constexpr int SM_BAR = SM_B + S_KC + 16384;
constexpr int SM_TOTAL = SM_BAR + 1024;
constexpr int SM_ALLOC = SM_TOTAL + 1024;
static_assert(SM_V + 65536 + 1024 <= SM_B && SM_ALLOC <= 232448 && S_TAB + 4 * TABN * 2 <= S_KC && SM_WKV + 16384 <= SM_B + S_KC, "smem map");

constexpr int TD0 = 0, TD1 = 560, CD = 544;
constexpr int TE0 = 1120, TE1 = 1168, CE = 1056;
constexpr int T2B = 1216, T2S = 160, T2C = 80, C2 = 80;
constexpr int T3B = 1856, T3S = 192, T3C = 96, C3 = 144;

constexpr int rne8(int t) {
    if (t < 256) return t;
    int sh = 0;
    while ((t >> sh) >= 256) sh++;
    int q = t >> sh, rem = t & ((1 << sh) - 1), half = 1 << (sh - 1);
    if (rem > half || (rem == half && (q & 1))) q++;
    return q << sh;
}
constexpr int kcidx(int p) {
    if (p < 256) return (p >> 3) * 24 + (p & 7);
    if (p < 512) return ((p - 256) >> 3) * 24 + 8 + (((p - 256) & 7) >> 1);
    if (p < 1024) { int q = p - 512, hi = q >> 8, rem = q & 255; return (rem >> 3) * 24 + 12 + 2 * hi + ((rem & 7) >> 2); }
    if (p < 2048) { int q = p - 1024; return ((q & 255) >> 3) * 24 + 16 + (q >> 8); }
    return 20;
}
constexpr int KC_ZERO = 23;
constexpr int tab_dense(int t) { return (t >= 0 && t <= 514) ? kcidx(rne8(t)) : KC_ZERO; }
constexpr int tab_extra(int t) { return (t >= 1027 && t <= 1028) ? kcidx(1024) : KC_ZERO; }
constexpr int tab_2(int s, int lag) { return (lag >= 32 && lag <= 63) ? kcidx(s == 0 ? 16 * (lag + 1) : 16 * lag + 4 * s) : KC_ZERO; }
constexpr int tab_3(int s, int lag) { return (lag >= 64 && lag <= 127) ? kcidx(s == 0 ? 16 * (lag + 1) : 16 * lag + 8) : KC_ZERO; }
struct TabMap {
    uint16_t v[TABN];
    constexpr TabMap() : v{} {
        for (int i = 0; i < 560; i++) { v[TD0 + i] = tab_dense(CD - i); v[TD1 + i] = tab_dense(CD + 1 - i); }
        for (int i = 0; i < 48; i++) { v[TE0 + i] = tab_extra(CE - i); v[TE1 + i] = tab_extra(CE + 1 - i); }
        for (int s = 0; s < 4; s++)
            for (int i = 0; i < T2C; i++) { v[T2B + s * T2S + i] = tab_2(s, C2 - i); v[T2B + s * T2S + T2C + i] = tab_2(s, C2 + 1 - i); }
        for (int s = 0; s < 2; s++)
            for (int i = 0; i < T3C; i++) { v[T3B + s * T3S + i] = tab_3(s, C3 - i); v[T3B + s * T3S + T3C + i] = tab_3(s, C3 + 1 - i); }
    }
};
__device__ const __align__(16) TabMap g_tabmap = TabMap();

__device__ __align__(1024) uint8_t g_kimg[65536];
__device__ __align__(1024) uint8_t g_vimg[65536 + 1024];
__device__ __align__(1024) uint8_t g_oimg[16 * 131072];
__device__ unsigned long long g_flag_kv[64];
__device__ unsigned g_flag_o[128];
__device__ unsigned g_epoch;
__device__ unsigned g_done;

#define PROF(i) do {} while (0)
#define PROF2(i) do {} while (0)
#define PROFC(i) do {} while (0)
#define PROF3(i) do {} while (0)

__device__ __forceinline__ uint32_t smem_u32(const void* p) { return (uint32_t)__cvta_generic_to_shared(p); }
__device__ __forceinline__ void mbar_init(uint32_t bar, uint32_t cnt) { asm volatile("mbarrier.init.shared::cta.b64 [%0], %1;" :: "r"(bar), "r"(cnt) : "memory"); }
__device__ __forceinline__ void mbar_expect_tx(uint32_t bar, uint32_t bytes) {
    asm volatile("mbarrier.arrive.expect_tx.shared::cta.b64 _, [%0], %1;" :: "r"(bar), "r"(bytes) : "memory"); }
__device__ __forceinline__ void mbar_wait(uint32_t bar, uint32_t parity) {
    uint32_t ok = 0;
    for (int it = 0; it < (1 << 22) && !ok; it++) {
        asm volatile("{ .reg .pred p; mbarrier.try_wait.parity.shared::cta.b64 p, [%1], %2; selp.u32 %0, 1, 0, p; }"
                     : "=r"(ok) : "r"(bar), "r"(parity) : "memory");
    }
}
__device__ __forceinline__ void tma_2d(uint32_t dst, const CUtensorMap* map, int c0, int c1, uint32_t bar) {
    asm volatile("cp.async.bulk.tensor.2d.shared::cluster.global.mbarrier::complete_tx::bytes [%0], [%1, {%3, %4}], [%2];"
                 :: "r"(dst), "l"((uint64_t)map), "r"(bar), "r"(c0), "r"(c1) : "memory");
}
__device__ __forceinline__ void tma_2d_mc(uint32_t dst, const CUtensorMap* map, int c0, int c1, uint32_t bar) {
    asm volatile("cp.async.bulk.tensor.2d.shared::cluster.global.mbarrier::complete_tx::bytes.multicast::cluster [%0], [%1, {%3, %4}], [%2], %5;"
                 :: "r"(dst), "l"((uint64_t)map), "r"(bar), "r"(c0), "r"(c1), "h"((uint16_t)3) : "memory");
}
__device__ __forceinline__ void bulk_g2s_mc(uint32_t dst, const void* src, uint32_t bytes, uint32_t bar) {
    asm volatile("cp.async.bulk.shared::cluster.global.mbarrier::complete_tx::bytes.multicast::cluster [%0], [%1], %2, [%3], %4;"
                 :: "r"(dst), "l"((uint64_t)src), "r"(bytes), "r"(bar), "h"((uint16_t)3) : "memory");
}
__device__ __forceinline__ void pair_sync(uint32_t bar, uint32_t peer) {
    uint32_t ra;
    asm volatile("mapa.shared::cluster.u32 %0, %1, %2;" : "=r"(ra) : "r"(bar), "r"(peer));
    asm volatile("mbarrier.arrive.shared::cluster.b64 _, [%0];" :: "r"(ra) : "memory");
    asm volatile("mbarrier.arrive.shared::cta.b64 _, [%0];" :: "r"(bar) : "memory");
    uint32_t ok = 0;
    for (int it = 0; it < (1 << 22) && !ok; it++) {
        asm volatile("{ .reg .pred p; mbarrier.try_wait.parity.shared::cta.b64 p, [%1], 0; selp.u32 %0, 1, 0, p; }"
                     : "=r"(ok) : "r"(bar) : "memory");
    }
}
__device__ __forceinline__ void fence_async_all() { asm volatile("fence.proxy.async.global;" ::: "memory"); }
__device__ __forceinline__ void fence_async_smem() { asm volatile("fence.proxy.async.shared::cta;" ::: "memory"); }
__device__ __forceinline__ unsigned ld_acquire(const unsigned* p) {
    unsigned v; asm volatile("ld.acquire.gpu.global.u32 %0, [%1];" : "=r"(v) : "l"(p) : "memory"); return v; }
__device__ __forceinline__ void st_release(unsigned* p, unsigned v) { asm volatile("st.release.gpu.global.u32 [%0], %1;" :: "l"(p), "r"(v) : "memory"); }
__device__ __forceinline__ void wait_flag(const unsigned* p, unsigned epoch) {
    for (int it = 0; it < (1 << 22); it++) { if (ld_acquire(p) == epoch) break; }
}
__device__ __forceinline__ unsigned long long ld_acquire64(const unsigned long long* p) {
    unsigned long long v; asm volatile("ld.acquire.gpu.global.u64 %0, [%1];" : "=l"(v) : "l"(p) : "memory"); return v; }
__device__ __forceinline__ void st_release64(unsigned long long* p, unsigned long long v) { asm volatile("st.release.gpu.global.u64 [%0], %1;" :: "l"(p), "l"(v) : "memory"); }
__device__ __forceinline__ float wait_flag64(const unsigned long long* p, unsigned epoch) {
    unsigned long long v = 0;
    for (int it = 0; it < (1 << 22); it++) { v = ld_acquire64(p); if ((unsigned)(v >> 32) == epoch) break; }
    return __uint_as_float((unsigned)v);
}
__device__ __forceinline__ void tma_3d_mc(uint32_t dst, const CUtensorMap* map, int c0, int c1, int c2, uint32_t bar) {
    asm volatile("cp.async.bulk.tensor.3d.shared::cluster.global.mbarrier::complete_tx::bytes.multicast::cluster [%0], [%1, {%3, %4, %5}], [%2], %6;"
                 :: "r"(dst), "l"((uint64_t)map), "r"(bar), "r"(c0), "r"(c1), "r"(c2), "h"((uint16_t)3) : "memory");
}
__device__ __forceinline__ void bar_sync(int id, int n) { asm volatile("bar.sync %0, %1;" :: "r"(id), "r"(n) : "memory"); }
__device__ __forceinline__ void bar_arrive(int id, int n) { asm volatile("bar.arrive %0, %1;" :: "r"(id), "r"(n) : "memory"); }
__device__ __forceinline__ void mbar_arrive(uint32_t bar) { asm volatile("mbarrier.arrive.shared::cta.b64 _, [%0];" :: "r"(bar) : "memory"); }

__device__ __forceinline__ uint64_t make_desc(uint32_t saddr, uint32_t lbo, uint32_t sbo, uint32_t swz) {
    uint64_t d = 0;
    d |= (uint64_t)((saddr & 0x3FFFF) >> 4);
    d |= (uint64_t)((lbo >> 4) & 0x3FFF) << 16;
    d |= (uint64_t)((sbo >> 4) & 0x3FFF) << 32;
    d |= (uint64_t)swz << 62;
    return d;
}
__device__ __forceinline__ void wg_fence() { asm volatile("wgmma.fence.sync.aligned;" ::: "memory"); }
__device__ __forceinline__ void wg_commit() { asm volatile("wgmma.commit_group.sync.aligned;" ::: "memory"); }
template<int N> __device__ __forceinline__ void wg_wait() { asm volatile("wgmma.wait_group.sync.aligned %0;" :: "n"(N) : "memory"); }
#define A4(d, o) "+f"(d[o + 0]), "+f"(d[o + 1]), "+f"(d[o + 2]), "+f"(d[o + 3])
#define A16(d, o) A4(d, o), A4(d, o + 4), A4(d, o + 8), A4(d, o + 12)

__device__ __forceinline__ void wg_pv(float* d, const uint32_t* a, uint32_t lo, uint32_t hi) {
    asm volatile("{ .reg .b64 dd; mov.b64 dd, {%16, %17};\n"
                 "wgmma.mma_async.sync.aligned.m64n24k16.f32.bf16.bf16 {%0,%1,%2,%3,%4,%5,%6,%7,%8,%9,%10,%11}, {%12,%13,%14,%15}, dd, 1, 1, 1, 1; }"
                 : A4(d, 0), A4(d, 4), A4(d, 8) : "r"(a[0]), "r"(a[1]), "r"(a[2]), "r"(a[3]), "r"(lo), "r"(hi));
}
__device__ __forceinline__ void wg_qk(float* d, const uint32_t* a, uint32_t lo) {
    asm volatile("{ .reg .b64 dd; mov.b64 dd, {%36, %37};\n"
                 "wgmma.mma_async.sync.aligned.m64n64k16.f32.bf16.bf16 {%0,%1,%2,%3,%4,%5,%6,%7,%8,%9,%10,%11,%12,%13,%14,%15,%16,%17,%18,%19,%20,%21,%22,%23,%24,%25,%26,%27,%28,%29,%30,%31}, {%32,%33,%34,%35}, dd, 0, 1, 1, 0; }"
                 : A16(d, 0), A16(d, 16) : "r"(a[0]), "r"(a[1]), "r"(a[2]), "r"(a[3]), "r"(lo), "r"(16));
}
__device__ __forceinline__ void wg_ss32(float* d, uint64_t da, uint64_t db) {
    asm volatile("wgmma.mma_async.sync.aligned.m64n32k16.f32.bf16.bf16 {%0,%1,%2,%3,%4,%5,%6,%7,%8,%9,%10,%11,%12,%13,%14,%15}, %16, %17, 1, 1, 1, 0, 1;"
                 : A16(d, 0) : "l"(da), "l"(db));
}
__device__ __forceinline__ void wg_ss16(float* d, uint64_t da, uint64_t db) {
    asm volatile("wgmma.mma_async.sync.aligned.m64n16k16.f32.bf16.bf16 {%0,%1,%2,%3,%4,%5,%6,%7}, %8, %9, 1, 1, 1, 0, 1;"
                 : A4(d, 0), A4(d, 4) : "l"(da), "l"(db));
}
template<int N> __device__ __forceinline__ void fence_regs(float* r) {
    #pragma unroll
    for (int i = 0; i < N; i++) asm volatile("" : "+f"(r[i]) :: "memory");
}
__device__ __forceinline__ void mma_bf16(float* d, uint32_t a0, uint32_t a1, uint32_t a2, uint32_t a3, uint32_t b0, uint32_t b1) {
    asm volatile("mma.sync.aligned.m16n8k16.row.col.f32.bf16.bf16.f32 {%0,%1,%2,%3}, {%4,%5,%6,%7}, {%8,%9}, {%0,%1,%2,%3};"
                 : "+f"(d[0]), "+f"(d[1]), "+f"(d[2]), "+f"(d[3]) : "r"(a0), "r"(a1), "r"(a2), "r"(a3), "r"(b0), "r"(b1));
}
__device__ __forceinline__ void mma_f16(float* d, const uint32_t* a, uint32_t b0, uint32_t b1) {
    asm volatile("mma.sync.aligned.m16n8k16.row.col.f32.f16.f16.f32 {%0,%1,%2,%3}, {%4,%5,%6,%7}, {%8,%9}, {%0,%1,%2,%3};"
                 : "+f"(d[0]), "+f"(d[1]), "+f"(d[2]), "+f"(d[3]) : "r"(a[0]), "r"(a[1]), "r"(a[2]), "r"(a[3]), "r"(b0), "r"(b1));
}
__device__ __forceinline__ void ldsm4(uint32_t* r, uint32_t addr) {
    asm volatile("ldmatrix.sync.aligned.m8n8.x4.shared.b16 {%0,%1,%2,%3}, [%4];" : "=r"(r[0]), "=r"(r[1]), "=r"(r[2]), "=r"(r[3]) : "r"(addr) : "memory");
}
__device__ __forceinline__ void ldsm4t(uint32_t* r, uint32_t addr) {
    asm volatile("ldmatrix.sync.aligned.m8n8.x4.trans.shared.b16 {%0,%1,%2,%3}, [%4];" : "=r"(r[0]), "=r"(r[1]), "=r"(r[2]), "=r"(r[3]) : "r"(addr) : "memory");
}
__device__ __forceinline__ uint32_t lds32(uint32_t addr) { uint32_t v; asm volatile("ld.shared.u32 %0, [%1];" : "=r"(v) : "r"(addr) : "memory"); return v; }
__device__ __forceinline__ float ex2f(float x) { float r; asm("ex2.approx.ftz.f32 %0, %1;" : "=f"(r) : "f"(x)); return r; }
__device__ __forceinline__ uint32_t pack_bf16(float lo, float hi) { uint32_t r; asm("cvt.rn.bf16x2.f32 %0, %1, %2;" : "=r"(r) : "f"(hi), "f"(lo)); return r; }
__device__ __forceinline__ uint32_t pack_f16(float lo, float hi) { uint32_t r; asm("cvt.rn.f16x2.f32 %0, %1, %2;" : "=r"(r) : "f"(hi), "f"(lo)); return r; }
__device__ __forceinline__ float bf_lo(uint32_t v) { return __uint_as_float(v << 16); }
__device__ __forceinline__ float bf_hi(uint32_t v) { return __uint_as_float(v & 0xFFFF0000u); }
__device__ __forceinline__ float bf_round(float x) { return __bfloat162float(__float2bfloat16_rn(x)); }

__device__ __forceinline__ uint32_t exp_mufu(float x0, float x1) { return pack_bf16(ex2f(x0), ex2f(x1)); }
#define SW_MAGIC (256.0f + 127.0f - 0.598938f)
__device__ __forceinline__ uint32_t exp_sw(float x0, float x1, uint32_t cA, uint32_t cB) {
    float t0 = x0 + SW_MAGIC, t1 = x1 + SW_MAGIC;
    uint32_t L, mh, ec, r;
    asm("prmt.b32 %0, %1, %2, 0x6521;" : "=r"(L) : "r"(__float_as_uint(t0)), "r"(__float_as_uint(t1)));
    asm("lop3.b32 %0, %1, 0x007F007F, %2, 0xEA;" : "=r"(mh) : "r"(L), "r"(cA));
    asm("lop3.b32 %0, %1, 0x7F807F80, %2, 0xEA;" : "=r"(ec) : "r"(L), "r"(cB));
    asm("fma.rn.bf16x2 %0, %1, %2, %3;" : "=r"(r) : "r"(L), "r"(mh), "r"(ec));
    return r;
}
constexpr uint32_t MUFU_MASK = 0x4949;

struct cf { float x, y; };
__device__ __forceinline__ cf cmul(cf a, cf b) { cf r; r.x = a.x * b.x - a.y * b.y; r.y = a.x * b.y + a.y * b.x; return r; }
__device__ __forceinline__ cf cexp_p(float a2, float b, float p) {
    float e = ex2f(a2 * p);
    float ph = b * p;
    ph -= (ph + 12582912.0f) - 12582912.0f;
    float ang = ph * 6.283185307f;
    cf r; r.x = e * __cosf(ang); r.y = e * __sinf(ang);
    return r;
}
__device__ __forceinline__ uint32_t h2_cmul(uint32_t w, uint32_t wsw, uint32_t e) {
    __half2 hw = *(__half2*)&w, hs = *(__half2*)&wsw, he = *(__half2*)&e;
    __half2 r = __hfma2(hs, __high2half2(he), __hmul2(hw, __low2half2(he)));
    return *(uint32_t*)&r;
}

template<bool B> struct BoolC { static constexpr bool value = B; };
struct Params {
    const __nv_bfloat16 *u, *lar, *aim, *cre, *cim, *logdt, *dskip;
    __nv_bfloat16* out;
};

constexpr int B_O = 0, B_KV = 8, B_WO = 12, B_WQ2 = 13, B_ST = 14, B_H = 15, B_X = 17, B_U = 19, B_WQ = 20;

__device__ __forceinline__ void helper_role(const Params& P, uint8_t* sp, unsigned epoch) {
    const int tid = threadIdx.x - 544;
    const int d0 = blockIdx.x * 4;
    uint8_t* sB = sp + SM_B;
    const uint2 dsk = __ldg((const uint2*)(P.dskip + d0));
    asm volatile("barrier.cluster.wait.aligned;" ::: "memory");
    {
        const int hg = blockIdx.x & 7;
        if (hg < 4 && tid < 32) {
            bar_sync(3, 160);
            if (tid == 0) {
                const float* s_misc = (const float*)(sp + SM_BAR + 256);
                const float st = fmaxf(fmaxf(s_misc[20], s_misc[21]), fmaxf(s_misc[22], s_misc[23]));
                st_release64(&g_flag_kv[((blockIdx.x >> 3) * 2 + (hg & 1)) * 2 + (hg >> 1)], ((unsigned long long)epoch << 32) | __float_as_uint(st));
            }
            __syncwarp();
        }
    }
    PROF2(2);
    bar_sync(10, 608);
    {
        uint32_t dd[4] = {__byte_perm(dsk.x, 0, 0x1010), __byte_perm(dsk.x, 0, 0x3232), __byte_perm(dsk.y, 0, 0x1010), __byte_perm(dsk.y, 0, 0x3232)};
        #pragma unroll 2
        for (int pi = tid; pi < 1024; pi += 96) {
            const int l = 2 * pi;
            uint32_t r[4];
            #pragma unroll
            for (int cc = 0; cc < 4; cc++) {
                const uint32_t y2 = *(const uint32_t*)(sB + S_Y + cc * 4096 + l * 2);
                const uint32_t u2 = *(const uint32_t*)(sB + S_U + cc * ULEN * 2 + (PADU + l) * 2);
                __nv_bfloat162 pr = __hmul2(*(const __nv_bfloat162*)&u2, *(const __nv_bfloat162*)&dd[cc]);
                __nv_bfloat162 sm = __hadd2(*(const __nv_bfloat162*)&y2, pr);
                r[cc] = *(uint32_t*)&sm;
            }
            *(uint2*)(P.out + (size_t)l * 1024 + 512 + d0) = make_uint2(__byte_perm(r[0], r[1], 0x5410), __byte_perm(r[2], r[3], 0x5410));
            *(uint2*)(P.out + (size_t)(l + 1) * 1024 + 512 + d0) = make_uint2(__byte_perm(r[0], r[1], 0x7632), __byte_perm(r[2], r[3], 0x7632));
        }
    }
    bar_arrive(11, 128);
    PROF2(4);
}

__global__ void __cluster_dims__(2, 1, 1) __launch_bounds__(NTHR, 1)
fused_kernel(const __grid_constant__ CUtensorMap tm_x, const __grid_constant__ CUtensorMap tm_wq,
             const __grid_constant__ CUtensorMap tm_wo, const __grid_constant__ CUtensorMap tm_wk,
             const __grid_constant__ CUtensorMap tm_wv, const __grid_constant__ CUtensorMap tm_u, const Params P) {
    extern __shared__ uint8_t smem_raw[];
    const uint32_t sb = (smem_u32(smem_raw) + 1023u) & ~1023u;
    uint8_t* sp = smem_raw + (sb - smem_u32(smem_raw));

    const int tid = threadIdx.x, warp = tid >> 5, lane = tid & 31, wg = tid >> 7, wiw = warp & 3;
    const int g = lane >> 2, t = lane & 3;
    const int qb = blockIdx.x >> 3, hg = blockIdx.x & 7;
    const uint32_t rank = blockIdx.x & 1;
    const int rowhalf = wg & 1, nh = wg >> 1;
    const bool kv_cta = hg < 4;
    const int kv_sel = hg >> 1;
    const bool kv_wg = kv_cta && (wg == (hg & 1));

    const uint32_t bars = sb + SM_BAR;
    float* s_misc = (float*)(sp + SM_BAR + 256);
    const CUtensorMap* tm_kv = kv_sel ? &tm_wv : &tm_wk;

    PROF(0);
    unsigned short p_lar = 0, p_aim = 0, p_cre = 0, p_cim = 0, p_ldt = 0;
    if (wg < 4) {
        const int n = (blockIdx.x * 4 + wg) * 128 + (tid & 127);
        p_lar = __ldg((const unsigned short*)P.lar + n);
        p_aim = __ldg((const unsigned short*)P.aim + n);
        p_cre = __ldg((const unsigned short*)P.cre + n);
        p_cim = __ldg((const unsigned short*)P.cim + n);
        p_ldt = __ldg((const unsigned short*)P.logdt + blockIdx.x * 4 + wg);
    } else if (warp == 16) {
        PROF3(5);
        if (lane == 0) {
            asm volatile("prefetch.tensormap [%0];" :: "l"((uint64_t)&tm_x) : "memory");
            asm volatile("prefetch.tensormap [%0];" :: "l"((uint64_t)tm_kv) : "memory");
            asm volatile("prefetch.tensormap [%0];" :: "l"((uint64_t)&tm_wq) : "memory");
            asm volatile("prefetch.tensormap [%0];" :: "l"((uint64_t)&tm_u) : "memory");
            mbar_init(bars + 8 * B_X, 1);
            mbar_init(bars + 8 * B_X + 8, 1);
            mbar_init(bars + 8 * B_U, 1);
            asm volatile("fence.mbarrier_init.release.cluster;" ::: "memory");
            mbar_expect_tx(bars + 8 * B_X, 65536u + (kv_cta ? 8192u : 0u));
            mbar_expect_tx(bars + 8 * B_X + 8, 65536u + (kv_cta ? 8192u : 0u));
            mbar_expect_tx(bars + 8 * B_U, 32768u);
        }
        __syncwarp();
        PROF3(6);
    }
    asm volatile("barrier.cluster.arrive.relaxed.aligned;" ::: "memory");
    const unsigned epoch = *(volatile unsigned*)&g_epoch + 1u;
    if (warp > 16) {
        if (lane == 0) {
            for (int i = warp - 17; i < B_X; i += 3) {
                mbar_init(bars + 8 * i, i >= B_H ? 2 : 1);
                if (i <= B_WQ2) mbar_expect_tx(bars + 8 * i, i < B_KV + 2 ? 16384u : i == B_KV + 2 ? 32768u : i <= B_WO ? 65536u : 32768u);
            }
            asm volatile("fence.mbarrier_init.release.cluster;" ::: "memory");
            fence_async_smem();
        } else if (warp == 19) {
            asm volatile("prefetch.global.L2 [%0];" :: "l"((const char*)g_tabmap.v + (lane - 1) * 128));
            if (lane < 5) asm volatile("prefetch.global.L2 [%0];" :: "l"((const char*)g_tabmap.v + (lane + 30) * 128));
        }
        __syncwarp();
    }
    asm volatile("barrier.cluster.wait.aligned;" ::: "memory");
    PROF(5);
    if (warp == 16 && lane == 0) {
        tma_3d_mc(sb + (rank ? SM_A : SM_B), &tm_x, 0, qb * 128, rank * 4, bars + 8 * (B_X + rank));
        if (kv_cta) {
            #pragma unroll
            for (int i = 0; i < 4; i++) tma_2d(sb + SM_WKV + i * 4096, tm_kv, (i >> 1) * 8, (i & 1) * 256, bars + 8 * (B_X + (i & 1)));
        }
        mbar_init(bars + 8 * B_WQ, 1);
        asm volatile("fence.mbarrier_init.release.cluster;" ::: "memory");
        fence_async_smem();
        mbar_expect_tx(bars + 8 * B_WQ, 32768u);
        tma_2d(sb + SM_WQ, &tm_wq, hg * 64, 0, bars + 8 * B_WQ);
        #pragma unroll
        for (int i = 0; i < 4; i++) tma_2d_mc(sb + SM_SLAB + (rank * 4 + i) * 4096, &tm_u, (blockIdx.x >> 1) * 8, (rank * 4 + i) * 256, bars + 8 * B_U);
    }
    __syncwarp();
    asm volatile("barrier.cluster.arrive.relaxed.aligned;" ::: "memory");

    if (warp == 16) {
        if (lane == 0) asm volatile("prefetch.tensormap [%0];" :: "l"((uint64_t)&tm_wo) : "memory");
        asm volatile("barrier.cluster.wait.aligned;" ::: "memory");
        PROF3(10);
        bar_sync(13, 544);
        if (lane == 0) { fence_async_smem(); tma_2d(sb + SM_SLAB, &tm_wq, hg * 64, 256, bars + 8 * B_WQ2); }
        bar_sync(14, 544);
        if (lane == 0) pair_sync(bars + 8 * B_H, rank ^ 1);
        __syncwarp();
        PROF3(11);
        *(uint4*)(sp + SM_V + 32768 + lane * 32) = make_uint4(0x3F803F80u, 0x3F803F80u, 0x3F803F80u, 0x3F803F80u);
        *(uint4*)(sp + SM_V + 32768 + lane * 32 + 16) = make_uint4(0x3F803F80u, 0x3F803F80u, 0x3F803F80u, 0x3F803F80u);
        fence_async_smem();
        float km = wait_flag64(&g_flag_kv[2 * lane], epoch);
        float vm = wait_flag64(&g_flag_kv[2 * lane + 1], epoch);
        __syncwarp();
        PROF3(12);
        if (lane == 0) {
            fence_async_all();
            #pragma unroll
            for (int i = 0; i < 4; i++) {
                const uint32_t k0 = i == 0 ? 0 : 128u << i, nk = i == 0 ? 256 : 128u << i;
                const uint32_t bar = bars + 8 * (B_KV + i);
                if (rank == 0) bulk_g2s_mc(sb + SM_K + k0 * 32, g_kimg + k0 * 32, nk * 32, bar);
                else {
                    bulk_g2s_mc(sb + SM_V + k0 * 16, g_vimg + k0 * 16, nk * 16, bar);
                    bulk_g2s_mc(sb + SM_V + 66560 - (k0 + nk) * 16, g_vimg + 66560 - (k0 + nk) * 16, nk * 16, bar);
                }
            }
        }
        #pragma unroll
        for (int o = 16; o; o >>= 1) { km = fmaxf(km, __shfl_xor_sync(0xffffffffu, km, o)); vm = fmaxf(vm, __shfl_xor_sync(0xffffffffu, vm, o)); }
        if (lane == 0) { s_misc[16] = km; s_misc[17] = vm; mbar_arrive(bars + 8 * B_ST); }
        PROF3(13);
        bar_sync(11, 128);
        if (lane < 2) { fence_async_smem(); tma_2d(sb + SM_B + lane * 32768, &tm_wo, hg * 64, lane * 256, bars + 8 * B_WO); }
        bar_sync(12, 544);
        if (lane == 0) {
            st_release(&g_flag_o[blockIdx.x], epoch);
            pair_sync(bars + 8 * (B_H + 1), rank ^ 1);
        }
        __syncwarp();
        PROF3(14);
        if (lane < 4) {
            const int src = 2 * lane + rank;
            wait_flag(&g_flag_o[qb * 8 + src], epoch);
            fence_async_all();
            bulk_g2s_mc(sb + SM_A + src * 16384, g_oimg + qb * 131072 + src * 16384, 16384, bars + 8 * (B_O + src));
        }
        __syncwarp();
        PROF3(15);
        if (lane == 0) {
            const unsigned prev = atomicAdd(&g_done, 1u);
            if (prev == NCTA - 1) {
                g_done = 0;
                __threadfence();
                *(volatile unsigned*)&g_epoch = epoch;
            }
        }
    } else if (wg == 4) {
        helper_role(P, sp, epoch);
    } else {
        uint8_t* sB = sp + SM_B;
        const uint32_t sBa = sb + SM_B;
        {
            const int c = wg;
            const float dt = bf_round(expf(bf_lo(p_ldt)));
            const float are = -bf_round(expf(bf_lo(p_lar))) * dt;
            const float aim = bf_lo(p_aim) * dt;
            float cr = 2.0f * (bf_lo(p_cre) * dt);
            float ci = 2.0f * (bf_lo(p_cim) * dt);
            const float a2 = are * 1.4426950408889634f, bb = aim * 0.15915494309189535f;
            float m = fmaxf(fabsf(cr), fabsf(ci));
            #pragma unroll
            for (int o = 16; o; o >>= 1) m = fmaxf(m, __shfl_xor_sync(0xffffffffu, m, o));
            int ebits = (__float_as_uint(m) >> 23) & 0xFF;
            ebits = min(max(ebits, 2), 250);
            const float scale = __uint_as_float((uint32_t)(ebits + 1) << 23);
            const float iscale = __uint_as_float((uint32_t)(253 - ebits) << 23);
            cf cc; cc.x = cr * iscale; cc.y = ci * iscale;

            const uint32_t stg = sBa + S_KC + warp * 1024;
            uint4* stp = (uint4*)(sB + S_KC + warp * 1024 + lane * 32);
            const uint32_t fa = stg + t * 32 + g * 4;

            uint32_t af[4][2][4];
            cf E256;
            {
                const cf E8 = cexp_p(a2, bb, 8.0f);
                uint32_t w[8];
                cf cur; cur.x = 1.0f; cur.y = 0.0f;
                w[0] = pack_f16(1.0f, 0.0f);
                cur = E8; w[1] = pack_f16(cur.x, cur.y);
                #pragma unroll
                for (int i = 2; i < 8; i++) { cur = cmul(cur, E8); w[i] = pack_f16(cur.x, cur.y); }
                stp[0] = make_uint4(w[0], w[1], w[2], w[3]);
                stp[1] = make_uint4(w[4], w[5], w[6], w[7]);
                const cf E64 = cexp_p(a2, bb, 64.0f);
                const cf E128 = cmul(E64, E64), E192 = cmul(E128, E64);
                E256 = cexp_p(a2, bb, 256.0f);
                const uint32_t e1 = pack_f16(E64.x, E64.y), e2 = pack_f16(E128.x, E128.y), e3 = pack_f16(E192.x, E192.y);
                __syncwarp();
                #pragma unroll
                for (int s = 0; s < 4; s++) {
                    #pragma unroll
                    for (int hh = 0; hh < 2; hh++) {
                        const uint32_t w0 = lds32(fa + s * 256 + hh * 128);
                        const uint32_t wsw = __byte_perm(w0, 0, 0x1032) ^ 0x00008000u;
                        const int src = 8 * s + t + 4 * hh;
                        const uint32_t f1 = __shfl_sync(0xffffffffu, e1, src), f2 = __shfl_sync(0xffffffffu, e2, src), f3 = __shfl_sync(0xffffffffu, e3, src);
                        af[s][0][2 * hh] = w0;
                        af[s][0][2 * hh + 1] = h2_cmul(w0, wsw, f1);
                        af[s][1][2 * hh] = h2_cmul(w0, wsw, f2);
                        af[s][1][2 * hh + 1] = h2_cmul(w0, wsw, f3);
                    }
                }
                __syncwarp();
            }
            float acc[2][3][4];
            #pragma unroll
            for (int i = 0; i < 24; i++) (&acc[0][0][0])[i] = 0.0f;
            const cf E1 = cexp_p(a2, bb, 1.0f);
            const cf E2 = cmul(E1, E1), E4 = cmul(E2, E2);
            cf X512;
            #pragma unroll
            for (int nt = 0; nt < 3; nt++) {
                uint32_t xv[8];
                if (nt == 0) {
                    cf cur = cc;
                    xv[0] = pack_f16(cur.x, -cur.y);
                    #pragma unroll
                    for (int i = 1; i < 8; i++) { cur = cmul(cur, E1); xv[i] = pack_f16(cur.x, -cur.y); }
                } else if (nt == 1) {
                    cf cur = cmul(cc, E256);
                    X512 = cmul(cur, E256);
                    xv[0] = pack_f16(cur.x, -cur.y);
                    #pragma unroll
                    for (int i = 1; i < 4; i++) { cur = cmul(cur, E2); xv[i] = pack_f16(cur.x, -cur.y); }
                    cur = cmul(X512, E4);
                    xv[4] = pack_f16(X512.x, -X512.y); xv[5] = pack_f16(cur.x, -cur.y);
                    X512 = cmul(X512, E256);
                    cur = cmul(X512, E4);
                    xv[6] = pack_f16(X512.x, -X512.y); xv[7] = pack_f16(cur.x, -cur.y);
                } else {
                    cf cur = X512;
                    #pragma unroll
                    for (int i = 0; i < 5; i++) { cur = cmul(cur, E256); xv[i] = pack_f16(cur.x, -cur.y); }
                    xv[5] = 0; xv[6] = 0; xv[7] = 0;
                }
                stp[0] = make_uint4(xv[0], xv[1], xv[2], xv[3]);
                stp[1] = make_uint4(xv[4], xv[5], xv[6], xv[7]);
                __syncwarp();
                #pragma unroll
                for (int s = 0; s < 4; s++) {
                    const uint32_t b0 = lds32(fa + s * 256), b1 = lds32(fa + s * 256 + 128);
                    mma_f16(acc[0][nt], af[s][0], b0, b1);
                    mma_f16(acc[1][nt], af[s][1], b0, b1);
                }
                __syncwarp();
            }
            float* kc = (float*)(sB + S_KC + c * 4096);
            bar_sync(4 + c, 128);
            #pragma unroll 1
            for (int step = 0; step < 4; step++) {
                if ((warp & 3) == step) {
                    #pragma unroll
                    for (int mt = 0; mt < 2; mt++)
                        #pragma unroll
                        for (int nt = 0; nt < 3; nt++)
                            #pragma unroll
                            for (int hh = 0; hh < 2; hh++) {
                                float2* p = (float2*)(kc + (mt * 16 + hh * 8 + g) * 24 + nt * 8 + 2 * t);
                                float2 v = make_float2(acc[mt][nt][2 * hh] * scale, acc[mt][nt][2 * hh + 1] * scale);
                                if (step) { float2 o = *p; v.x += o.x; v.y += o.y; }
                                *p = v;
                            }
                }
                if (step < 3) bar_sync(4 + c, 128);
            }
        }

        asm volatile("barrier.cluster.wait.aligned;" ::: "memory");
        PROF(4);
        uint32_t q[2][4];
        {
            float acc[16], akv[8];
            #pragma unroll
            for (int i = 0; i < 16; i++) acc[i] = 0.0f;
            #pragma unroll
            for (int i = 0; i < 8; i++) akv[i] = 0.0f;
            fence_regs<16>(acc);
            fence_regs<8>(akv);
            const uint64_t dA0 = make_desc(sb + SM_B + rowhalf * 8192, 16, 1024, 1);
            const uint64_t dA1 = make_desc(sb + SM_A + rowhalf * 8192, 16, 1024, 1) - 4096;
            const uint64_t dB = make_desc(sb + SM_WQ + nh * 64, 16, 1024, 1);
            const uint64_t dC = make_desc(sb + SM_WKV, 128, 8192, 0);
            if (kv_wg) {
                #pragma unroll 1
                for (int ch = 0; ch < 8; ch++) {
                    if ((ch & 3) == 0) mbar_wait(bars + 8 * (B_X + (ch >> 2)), 0);
                    const uint64_t dA = ch < 4 ? dA0 : dA1;
                    wg_fence();
                    #pragma unroll
                    for (int ks = 0; ks < 4; ks++) wg_ss16(akv, dA + ch * 1024 + ks * 2, dC + (ch * 4 + ks) * 16);
                    wg_commit();
                }
                wg_wait<0>();
            }
            fence_regs<8>(akv);
            if (kv_wg) {
                const int key = qb * 128 + rowhalf * 64 + wiw * 16 + g;
                uint32_t pk[4];
                #pragma unroll
                for (int i = 0; i < 4; i++) pk[i] = pack_bf16(akv[2 * i], akv[2 * i + 1]);
                float st;
                if (kv_sel == 0) {
                    uint8_t* b = g_kimg + (key >> 3) * 256 + (key & 7) * 16 + 4 * t;
                    *(uint32_t*)(b) = pk[0]; *(uint32_t*)(b + 256) = pk[1]; *(uint32_t*)(b + 128) = pk[2]; *(uint32_t*)(b + 384) = pk[3];
                    float n0 = bf_lo(pk[0]) * bf_lo(pk[0]) + bf_hi(pk[0]) * bf_hi(pk[0]) + bf_lo(pk[2]) * bf_lo(pk[2]) + bf_hi(pk[2]) * bf_hi(pk[2]);
                    float n1 = bf_lo(pk[1]) * bf_lo(pk[1]) + bf_hi(pk[1]) * bf_hi(pk[1]) + bf_lo(pk[3]) * bf_lo(pk[3]) + bf_hi(pk[3]) * bf_hi(pk[3]);
                    n0 += __shfl_xor_sync(0xffffffffu, n0, 1); n0 += __shfl_xor_sync(0xffffffffu, n0, 2);
                    n1 += __shfl_xor_sync(0xffffffffu, n1, 1); n1 += __shfl_xor_sync(0xffffffffu, n1, 2);
                    st = (n0 != n0 || n1 != n1) ? __int_as_float(0x7f800000) : fmaxf(n0, n1);
                } else {
                    uint8_t* lo = g_vimg + key * 16 + 4 * t;
                    uint8_t* hi = g_vimg + 33792 + (31 - (key >> 6)) * 1024 + (key & 63) * 16 + 4 * t;
                    *(uint32_t*)(lo) = pk[0]; *(uint32_t*)(lo + 128) = pk[1]; *(uint32_t*)(hi) = pk[2]; *(uint32_t*)(hi + 128) = pk[3];
                    st = 0.0f;
                    #pragma unroll
                    for (int i = 0; i < 4; i++) {
                        float a = fabsf(bf_lo(pk[i])), b = fabsf(bf_hi(pk[i]));
                        st = (a != a || b != b) ? __int_as_float(0x7f800000) : fmaxf(st, fmaxf(a, b));
                    }
                }
                #pragma unroll
                for (int o = 16; o; o >>= 1) st = fmaxf(st, __shfl_xor_sync(0xffffffffu, st, o));
                if (lane == 0) s_misc[20 + wiw] = st;
                bar_arrive(3, 160);
            }
            uint32_t mp[9];
            #pragma unroll
            for (int i = 0; i < 9; i++) { const int w = (tid & 127) + 128 * i; mp[i] = (w < TABN / 2) ? __ldg((const uint32_t*)g_tabmap.v + w) : 0u; }
            mbar_wait(bars + 8 * B_WQ, 0);
            mbar_wait(bars + 8 * B_X, 0);
            PROF(2);
            #pragma unroll 1
            for (int ch = 0; ch < 4; ch++) {
                wg_fence();
                #pragma unroll
                for (int ks = 0; ks < 4; ks++) wg_ss32(acc, dA0 + ch * 1024 + ks * 2, dB + (ch * 4 + ks) * 128);
                wg_commit();
            }
            wg_wait<0>();
            fence_regs<16>(acc);
            bar_sync(1, 512);
            PROF(15);
            if (tid < 4 * (PADU / 8)) *(uint4*)(sB + S_U + (tid / (PADU / 8)) * ULEN * 2 + (tid % (PADU / 8)) * 16) = make_uint4(0, 0, 0, 0);
            PROF(8);
            mbar_wait(bars + 8 * B_U, 0);
            PROF(14);
            #pragma unroll
            for (int i = 0; i < 2; i++) {
                const int l = 2 * (tid + 512 * i);
                const uint2 r0 = *(const uint2*)(sp + SM_SLAB + l * 16 + rank * 8), r1 = *(const uint2*)(sp + SM_SLAB + l * 16 + 16 + rank * 8);
                uint32_t* dst = (uint32_t*)(sB + S_U + (PADU + l) * 2);
                dst[0] = __byte_perm(r0.x, r1.x, 0x5410);
                dst[ULEN / 2] = __byte_perm(r0.x, r1.x, 0x7632);
                dst[ULEN] = __byte_perm(r0.y, r1.y, 0x5410);
                dst[3 * ULEN / 2] = __byte_perm(r0.y, r1.y, 0x7632);
            }
            bar_arrive(13, 544);
            {
                const float* kc = (const float*)(sB + S_KC + wg * 4096);
                uint32_t* tab = (uint32_t*)(sB + S_TAB + wg * TABN * 2);
                #pragma unroll
                for (int i = 0; i < 9; i++) { const int w = (tid & 127) + 128 * i; if (w < TABN / 2) tab[w] = pack_bf16(kc[mp[i] & 0xFFFF], kc[mp[i] >> 16]); }
            }
            PROF(1);
            mbar_wait(bars + 8 * B_WQ2, 0);
            mbar_wait(bars + 8 * (B_X + 1), 0);
            fence_regs<16>(acc);
            #pragma unroll 1
            for (int ch = 4; ch < 8; ch++) {
                wg_fence();
                #pragma unroll
                for (int ks = 0; ks < 4; ks++) wg_ss32(acc, dA1 + ch * 1024 + ks * 2, dB + (ch * 4 + ks) * 128);
                wg_commit();
            }
            wg_wait<0>();
            fence_regs<16>(acc);
            bar_arrive(14, 544);
            const float QS = 0.25f * 1.4426950408889634f;
            float qm = 0.0f;
            #pragma unroll
            for (int i = 0; i < 2; i++) {
                #pragma unroll
                for (int j = 0; j < 4; j++) q[i][j] = pack_bf16(acc[8 * i + 2 * j] * QS, acc[8 * i + 2 * j + 1] * QS);
                float n0 = bf_lo(q[i][0]) * bf_lo(q[i][0]) + bf_hi(q[i][0]) * bf_hi(q[i][0]) + bf_lo(q[i][2]) * bf_lo(q[i][2]) + bf_hi(q[i][2]) * bf_hi(q[i][2]);
                float n1 = bf_lo(q[i][1]) * bf_lo(q[i][1]) + bf_hi(q[i][1]) * bf_hi(q[i][1]) + bf_lo(q[i][3]) * bf_lo(q[i][3]) + bf_hi(q[i][3]) * bf_hi(q[i][3]);
                n0 += __shfl_xor_sync(0xffffffffu, n0, 1); n0 += __shfl_xor_sync(0xffffffffu, n0, 2);
                n1 += __shfl_xor_sync(0xffffffffu, n1, 1); n1 += __shfl_xor_sync(0xffffffffu, n1, 2);
                qm = (n0 != n0 || n1 != n1) ? __int_as_float(0x7f800000) : fmaxf(qm, fmaxf(n0, n1));
            }
            #pragma unroll
            for (int o = 16; o; o >>= 1) qm = fmaxf(qm, __shfl_xor_sync(0xffffffffu, qm, o));
            if (lane == 0) s_misc[warp] = qm;
        }
        PROF(3);
        bar_sync(1, 512);
        #pragma unroll 1
        for (int task = tid; task < 4 * 194; task += 512) {
            const int c = task / 194, i = task % 194;
            const uint4* src = (const uint4*)(sB + S_U + c * ULEN * 2 + (PADU + 8 * i - WPAD - 8) * 2);
            const uint4 v0 = src[0], v1 = src[1], v2 = src[2];
            float x[24];
            const uint32_t vv[12] = {v0.x, v0.y, v0.z, v0.w, v1.x, v1.y, v1.z, v1.w, v2.x, v2.y, v2.z, v2.w};
            #pragma unroll
            for (int k = 0; k < 12; k++) { x[2 * k] = bf_lo(vv[k]); x[2 * k + 1] = bf_hi(vv[k]); }
            float w3[12], w5[8];
            #pragma unroll
            for (int e = 0; e < 12; e++) w3[e] = (x[3 + e] + x[4 + e]) + x[5 + e];
            #pragma unroll
            for (int e = 0; e < 8; e++) w5[e] = w3[4 + e] + (x[6 + e] + x[10 + e]);
            *(uint4*)(sB + S_W3 + c * W2LEN * 2 + i * 16) = make_uint4(pack_bf16(w3[0], w3[1]), pack_bf16(w3[2], w3[3]), pack_bf16(w3[4], w3[5]), pack_bf16(w3[6], w3[7]));
            *(uint4*)(sB + S_W5 + c * W2LEN * 2 + i * 16) = make_uint4(pack_bf16(w5[0], w5[1]), pack_bf16(w5[2], w5[3]), pack_bf16(w5[4], w5[5]), pack_bf16(w5[6], w5[7]));
            if (i < 130) {
                float w7[8], w9[8];
                #pragma unroll
                for (int e = 0; e < 8; e++) { w7[e] = w5[e] + (x[5 + e] + x[11 + e]); w9[e] = w7[e] + (x[4 + e] + x[12 + e]); }
                *(uint4*)(sB + S_W7 + c * W3LEN * 2 + i * 16) = make_uint4(pack_bf16(w7[0], w7[1]), pack_bf16(w7[2], w7[3]), pack_bf16(w7[4], w7[5]), pack_bf16(w7[6], w7[7]));
                *(uint4*)(sB + S_W9 + c * W3LEN * 2 + i * 16) = make_uint4(pack_bf16(w9[0], w9[1]), pack_bf16(w9[2], w9[3]), pack_bf16(w9[4], w9[5]), pack_bf16(w9[6], w9[7]));
            }
        }
        bar_sync(1, 512);
        PROF(6);
        {
            const int c = warp >> 2, grp = (warp + c) & 3;
            float acc[4][4];
            #pragma unroll
            for (int i = 0; i < 16; i++) (&acc[0][0])[i] = 0.0f;
            const uint32_t tabc = sBa + S_TAB + c * TABN * 2;
            const int e2 = (g - 2 * t) * 2;
            const uint32_t tD = tabc + ((g & 1) ? (TD1 + CD + 1) : (TD0 + CD)) * 2 - e2;
            const uint32_t tE = tabc + ((g & 1) ? (TE1 + CE + 1) : (TE0 + CE)) * 2 - e2;
            const uint32_t t2 = tabc + (T2B + ((g & 1) ? (T2C + C2 + 1) : C2)) * 2 - e2;
            const uint32_t t3 = tabc + (T3B + ((g & 1) ? (T3C + C3 + 1) : C3)) * 2 - e2;
            const int mi = lane >> 3, r8 = lane & 7;
            const uint32_t ub = sBa + S_U + c * ULEN * 2 + (PADU + 16 * (8 * (mi >> 1) + r8) + 8 * (mi & 1)) * 2 + (4 * grp - 4) * 256;
            #pragma unroll 1
            for (int rho = 0; rho < 8; rho++) {
                uint32_t R[5][3];
                #pragma unroll
                for (int qq = 0; qq < 5; qq++) {
                    if (qq < 4 || rho < 2) {
                        const uint32_t a = tD - 32 * (rho + 8 * qq);
                        R[qq][0] = lds32(a + 16); R[qq][1] = lds32(a); R[qq][2] = lds32(a - 16);
                    } else { R[qq][0] = 0; R[qq][1] = 0; R[qq][2] = 0; }
                }
                #pragma unroll
                for (int jp = 0; jp < 4; jp++) {
                    if (grp == 0 && (jp == 0 || (jp == 1 && rho > 0))) continue;
                    if (jp == 0 && rho >= 2) {
                        uint32_t b[4];
                        ldsm4(b, ub + jp * 512 - rho * 32);
                        mma_bf16(acc[0], R[3][1], R[3][2], R[3][0], R[3][1], b[2], b[3]);
                        continue;
                    }
                    uint32_t b[4];
                    ldsm4(b, ub + jp * 512 - rho * 32);
                    #pragma unroll
                    for (int hh = 0; hh < 2; hh++) {
                        #pragma unroll
                        for (int qq = 0; qq < 5; qq++) {
                            const int jr = 2 * jp + hh + qq - 4;
                            if (jr >= 0 && jr < 4) {
                                if (qq < 4 || rho < 2) mma_bf16(acc[jr], R[qq][1], R[qq][2], R[qq][0], R[qq][1], b[2 * hh], b[2 * hh + 1]);
                            }
                        }
                    }
                }
            }
            if (grp >= 2) {
                uint32_t R[5];
                #pragma unroll
                for (int i = 0; i < 5; i++) R[i] = lds32(tE - 16 * (127 + i));
                #pragma unroll
                for (int kk = 0; kk < 2; kk++) {
                    #pragma unroll
                    for (int jp = 0; jp < 2; jp++) {
                        uint32_t b[4];
                        ldsm4(b, ub + (4 + 2 * jp) * 256 - (64 + kk) * 32);
                        mma_bf16(acc[2 * jp], R[2 * kk + 1], R[2 * kk + 2], R[2 * kk], R[2 * kk + 1], b[0], b[1]);
                        mma_bf16(acc[2 * jp + 1], R[2 * kk + 1], R[2 * kk + 2], R[2 * kk], R[2 * kk + 1], b[2], b[3]);
                    }
                }
            }
            const uint32_t soff = (WPAD + 16 * (8 * (mi >> 1) + r8) + 8 * (mi & 1)) * 2 + grp * 1024;
            if (grp >= 1) {
                #pragma unroll 1
                for (int s = 0; s < 4; s++) {
                    const uint32_t sig = sBa + ((s & 1) ? S_W3 : S_W5) + c * W2LEN * 2 + soff - ((s == 0) ? 32 : (s == 1) ? 0 : 16);
                    uint32_t R[7];
                    #pragma unroll
                    for (int i = 0; i < 7; i++) R[i] = lds32(t2 + s * (T2S * 2) - 16 * (3 + i));
                    #pragma unroll
                    for (int bb = 1; bb <= 4; bb++) {
                        if (2 * grp - bb < 0) continue;
                        uint32_t a[4];
                        ldsm4t(a, sig - bb * 512);
                        #pragma unroll
                        for (int jj = 0; jj < 4; jj++) {
                            const int h = jj + 2 * bb;
                            if (h >= 4 && h <= 9) mma_bf16(acc[jj], a[0], a[1], a[2], a[3], R[h - 3], R[h - 4]);
                        }
                    }
                }
            }
            if (grp >= 2) {
                #pragma unroll 1
                for (int s = 0; s < 2; s++) {
                    const uint32_t sig = sBa + (s ? S_W7 : S_W9) + c * W3LEN * 2 + soff - (s ? 16 : 32);
                    uint32_t R[9];
                    #pragma unroll
                    for (int i = 0; i < 9; i++) R[i] = lds32(t3 + s * (T3S * 2) - 16 * (7 + i));
                    #pragma unroll
                    for (int bb = 3; bb <= 6; bb++) {
                        if (2 * grp - bb < 0) continue;
                        uint32_t a[4];
                        ldsm4t(a, sig - bb * 512);
                        #pragma unroll
                        for (int jj = 0; jj < 4; jj++) {
                            const int h = jj + 2 * bb;
                            if (h >= 8 && h <= 15) mma_bf16(acc[jj], a[0], a[1], a[2], a[3], R[h - 7], R[h - 8]);
                        }
                    }
                }
            }
            __nv_bfloat16* ys = (__nv_bfloat16*)(sB + S_Y + c * 4096);
            #pragma unroll
            for (int jj = 0; jj < 4; jj++) {
                const int A = 8 * (4 * grp + jj) + 2 * t;
                ys[16 * A + g] = __float2bfloat16_rn(acc[jj][0]);
                ys[16 * A + 16 + g] = __float2bfloat16_rn(acc[jj][1]);
                ys[16 * A + g + 8] = __float2bfloat16_rn(acc[jj][2]);
                ys[16 * A + 16 + g + 8] = __float2bfloat16_rn(acc[jj][3]);
            }
        }
        bar_arrive(10, 608);
        PROF(7);
        {
            mbar_wait(bars + 8 * B_ST, 0);
            PROF(9); PROFC(8);
            float qm = 0.0f;
            #pragma unroll
            for (int i = 0; i < 16; i++) qm = fmaxf(qm, s_misc[i]);
            const float vm = s_misc[17];
            const bool fast = (qm * s_misc[16] <= 60.0f * 60.0f) && (vm <= 1.0e12f) && (vm >= 1.0e-12f || vm == 0.0f);
            uint8_t* ob = g_oimg + qb * 131072 + hg * 16384 + nh * 8192 + (rowhalf * 8 + wiw * 2) * 128 + g * 16 + 4 * t;
            uint32_t cA = 0xBF00BF00u, cB = 0x00030003u;
            asm volatile("" : "+r"(cA), "+r"(cB));
            #pragma unroll 1
            for (int tile = 0; tile < 2; tile++) {
                uint32_t kLo = (((sb + SM_K) & 0x3FFFF) >> 4) | (8u << 16), vLo = (((sb + SM_V) & 0x3FFFF) >> 4) | (8u << 16), vHi = 2048;
                float o[12], s[32];
                uint32_t p[16], qq[4];
                #pragma unroll
                for (int i = 0; i < 4; i++) { qq[i] = tile ? q[1][i] : q[0][i]; asm volatile("" : "+r"(qq[i])); }
                #pragma unroll
                for (int i = 0; i < 12; i++) o[i] = 0.0f;
                #pragma unroll
                for (int i = 0; i < 32; i++) s[i] = 0.0f;
                fence_regs<12>(o);
                fence_regs<32>(s);
                if (fast) {
                    #pragma unroll 1
                    for (int c = 0; c < SEQ / 256; c++) {
                        if (c <= 4) mbar_wait(bars + 8 * (B_KV + (c < 2 ? c : c < 4 ? 2 : 3)), 0);
                        wg_fence();
                        wg_qk(s, qq, kLo);
                        wg_commit();
                        #pragma unroll
                        for (int u = 0; u < 4; u++) {
                            wg_wait<0>();
                            fence_regs<32>(s);
                            #pragma unroll
                            for (int i = 0; i < 16; i++) {
                                if ((MUFU_MASK >> i) & 1) p[i] = exp_mufu(s[2 * i], s[2 * i + 1]);
                                else p[i] = exp_sw(s[2 * i], s[2 * i + 1], cA, cB);
                            }
                            wg_fence();
                            if (u + 1 < 4) wg_qk(s, qq, kLo + (u + 1) * 128);
                            #pragma unroll
                            for (int kk = 0; kk < 4; kk++) wg_pv(o, p + 4 * kk, vLo + u * 64 + kk * 16, vHi - u * 64);
                            wg_commit();
                        }
                        kLo += 512; vLo += 256; vHi -= 256;
                    }
                    wg_wait<0>();
                } else {
                    float mx0 = -INFINITY, mx1 = -INFINITY;
                    #pragma unroll 1
                    for (int c = 0; c < SEQ / 64; c++) {
                        if (c <= 16) mbar_wait(bars + 8 * (B_KV + (c < 8 ? (c >> 2) : c < 16 ? 2 : 3)), 0);
                        wg_fence();
                        wg_qk(s, qq, kLo);
                        wg_commit();
                        wg_wait<0>();
                        fence_regs<32>(s);
                        fence_regs<12>(o);
                        float m0 = mx0, m1 = mx1;
                        #pragma unroll
                        for (int j = 0; j < 8; j++) {
                            m0 = fmaxf(m0, fmaxf(s[4 * j], s[4 * j + 1]));
                            m1 = fmaxf(m1, fmaxf(s[4 * j + 2], s[4 * j + 3]));
                        }
                        m0 = fmaxf(m0, __shfl_xor_sync(0xffffffffu, m0, 1)); m0 = fmaxf(m0, __shfl_xor_sync(0xffffffffu, m0, 2));
                        m1 = fmaxf(m1, __shfl_xor_sync(0xffffffffu, m1, 1)); m1 = fmaxf(m1, __shfl_xor_sync(0xffffffffu, m1, 2));
                        const float c0 = ex2f(mx0 - m0), c1 = ex2f(mx1 - m1);
                        mx0 = m0; mx1 = m1;
                        #pragma unroll
                        for (int j = 0; j < 3; j++) { o[4 * j] *= c0; o[4 * j + 1] *= c0; o[4 * j + 2] *= c1; o[4 * j + 3] *= c1; }
                        #pragma unroll
                        for (int j = 0; j < 8; j++) {
                            p[2 * j] = exp_mufu(s[4 * j] - m0, s[4 * j + 1] - m0);
                            p[2 * j + 1] = exp_mufu(s[4 * j + 2] - m1, s[4 * j + 3] - m1);
                        }
                        wg_fence();
                        #pragma unroll
                        for (int kk = 0; kk < 4; kk++) wg_pv(o, p + 4 * kk, vLo + kk * 16, vHi);
                        wg_commit();
                        wg_wait<0>();
                        kLo += 128; vLo += 64; vHi -= 64;
                    }
                }
                fence_regs<12>(o);
                if (tile == 0) PROFC(3);
                const float i0 = 1.0f / o[4], i1 = 1.0f / o[6];
                uint8_t* b = ob + tile * 4096;
                *(uint32_t*)(b) = pack_bf16(o[0] * i0, o[1] * i0);
                *(uint32_t*)(b + 128) = pack_bf16(o[2] * i1, o[3] * i1);
                *(uint32_t*)(b + 2048) = pack_bf16(o[8] * i0, o[9] * i0);
                *(uint32_t*)(b + 2048 + 128) = pack_bf16(o[10] * i1, o[11] * i1);
            }
        }
        PROF(10); PROFC(9);
        bar_arrive(12, 544);

        {
            float acc[16];
            #pragma unroll
            for (int i = 0; i < 16; i++) acc[i] = 0.0f;
            fence_regs<16>(acc);
            const uint64_t dA = make_desc(sb + SM_A + rowhalf * 1024, 2048, 128, 0);
            const uint64_t dB = make_desc(sb + SM_B + nh * 64, 16, 1024, 1);
            mbar_wait(bars + 8 * B_WO, 0);
            #pragma unroll 1
            for (int i = 0; i < 8; i++) {
                const int src = (hg + i) & 7;
                mbar_wait(bars + 8 * (B_O + src), 0);
                wg_fence();
                #pragma unroll
                for (int kk = 0; kk < 4; kk++) wg_ss32(acc, dA + src * 1024 + kk * 256, dB + (src * 4 + kk) * 128);
                wg_commit();
            }
            wg_wait<0>();
            fence_regs<16>(acc);
            PROF(12);
            const int row = qb * 128 + rowhalf * 64 + wiw * 16 + g;
            uint32_t* o32 = (uint32_t*)(P.out + (size_t)row * 1024 + hg * 64 + nh * 32 + 2 * t);
            #pragma unroll
            for (int j = 0; j < 4; j++) {
                o32[4 * j] = pack_bf16(acc[4 * j], acc[4 * j + 1]);
                o32[4 * j + 8 * 512] = pack_bf16(acc[4 * j + 2], acc[4 * j + 3]);
            }
        }
        PROF(13);
    }
}

typedef CUresult (*EncodeFn)(CUtensorMap*, CUtensorMapDataType, cuuint32_t, void*, const cuuint64_t*, const cuuint64_t*,
                             const cuuint32_t*, const cuuint32_t*, CUtensorMapInterleave, CUtensorMapSwizzle,
                             CUtensorMapL2promotion, CUtensorMapFloatOOBfill);

void make_map(EncodeFn fn, CUtensorMap* m, const void* ptr, uint64_t inner, uint64_t outer, uint32_t box_in, uint32_t box_out, CUtensorMapSwizzle swz) {
    cuuint64_t dims[2] = {inner, outer};
    cuuint64_t strides[1] = {inner * 2};
    cuuint32_t box[2] = {box_in, box_out};
    cuuint32_t es[2] = {1, 1};
    fn(m, CU_TENSOR_MAP_DATA_TYPE_BFLOAT16, 2, const_cast<void*>(ptr), dims, strides, box, es, CU_TENSOR_MAP_INTERLEAVE_NONE, swz,
       CU_TENSOR_MAP_L2_PROMOTION_L2_128B, CU_TENSOR_MAP_FLOAT_OOB_FILL_NONE);
}

}

extern "C" void kernel_launch(void* const* d_in, const int* in_sizes, int n_in, void* d_out, int out_size) {
    (void)in_sizes; (void)n_in; (void)out_size;
    static EncodeFn fn = nullptr;
    if (!fn) {
        void* p = nullptr;
        cudaDriverEntryPointQueryResult qr;
        cudaGetDriverEntryPoint("cuTensorMapEncodeTiled", &p, cudaEnableDefault, &qr);
        fn = (EncodeFn)p;
        cudaFuncSetAttribute(fused_kernel, cudaFuncAttributeMaxDynamicSharedMemorySize, SM_ALLOC);
    }
    CUtensorMap tx, twq, two, twk, twv, tu;
    {
        cuuint64_t dims[3] = {64, 2048, 8};
        cuuint64_t strides[2] = {1024, 128};
        cuuint32_t box[3] = {64, 128, 4};
        cuuint32_t es[3] = {1, 1, 1};
        fn(&tx, CU_TENSOR_MAP_DATA_TYPE_BFLOAT16, 3, d_in[0], dims, strides, box, es, CU_TENSOR_MAP_INTERLEAVE_NONE, CU_TENSOR_MAP_SWIZZLE_128B,
           CU_TENSOR_MAP_L2_PROMOTION_L2_128B, CU_TENSOR_MAP_FLOAT_OOB_FILL_NONE);
    }
    make_map(fn, &tu, d_in[5], 512, 2048, 8, 256, CU_TENSOR_MAP_SWIZZLE_NONE);
    make_map(fn, &twq, d_in[1], 512, 512, 64, 256, CU_TENSOR_MAP_SWIZZLE_128B);
    make_map(fn, &twk, d_in[2], 16, 512, 8, 256, CU_TENSOR_MAP_SWIZZLE_NONE);
    make_map(fn, &twv, d_in[3], 16, 512, 8, 256, CU_TENSOR_MAP_SWIZZLE_NONE);
    make_map(fn, &two, d_in[4], 512, 512, 64, 256, CU_TENSOR_MAP_SWIZZLE_128B);
    Params P;
    P.u = (const __nv_bfloat16*)d_in[5];
    P.lar = (const __nv_bfloat16*)d_in[6];
    P.aim = (const __nv_bfloat16*)d_in[7];
    P.cre = (const __nv_bfloat16*)d_in[8];
    P.cim = (const __nv_bfloat16*)d_in[9];
    P.logdt = (const __nv_bfloat16*)d_in[10];
    P.dskip = (const __nv_bfloat16*)d_in[11];
    P.out = (__nv_bfloat16*)d_out;
    fused_kernel<<<NCTA, NTHR, SM_ALLOC>>>(tx, twq, two, twk, twv, tu, P);
}
```

```cpp
#include <cuda_runtime.h>
#include <cuda_bf16.h>
#include <cuda_fp16.h>
#include <cuda.h>
#include <stdint.h>

namespace {

constexpr int SEQ = 2048;
constexpr int NCTA = 128, NTHR = 640;

constexpr int SM_A = 0;
constexpr int SM_WQ = 65536;
constexpr int SM_SLAB = SM_WQ + 32768;
constexpr int SM_K = 0, SM_V = 65536;
constexpr int SM_B = 132096;
constexpr int SM_WKV = SM_B + 65536;

constexpr int PADU = 288, ULEN = PADU + 2048;
constexpr int WPAD = 16, W2LEN = WPAD + 1536, W3LEN = WPAD + 1024;
constexpr int TABN = 2240;
constexpr int S_U = 0;
constexpr int S_W3 = S_U + 4 * ULEN * 2;
constexpr int S_W5 = S_W3 + 4 * W2LEN * 2;
constexpr int S_W7 = S_W5 + 4 * W2LEN * 2;
constexpr int S_W9 = S_W7 + 4 * W3LEN * 2;
constexpr int S_TAB = S_W9 + 4 * W3LEN * 2;
constexpr int S_KC = 214016 - SM_B;
constexpr int S_Y = S_KC;
constexpr int SM_BAR = SM_B + S_KC + 16384;
constexpr int SM_TOTAL = SM_BAR + 1024;
constexpr int SM_ALLOC = SM_TOTAL + 1024;
static_assert(SM_V + 65536 + 1024 <= SM_B && SM_ALLOC <= 232448 && S_TAB + 4 * TABN * 2 <= S_KC && SM_WKV + 16384 <= SM_B + S_KC, "smem map");

constexpr int TD0 = 0, TD1 = 560, CD = 544;
constexpr int TE0 = 1120, TE1 = 1168, CE = 1056;
constexpr int T2B = 1216, T2S = 160, T2C = 80, C2 = 80;
constexpr int T3B = 1856, T3S = 192, T3C = 96, C3 = 144;

constexpr int rne8(int t) {
    if (t < 256) return t;
    int sh = 0;
    while ((t >> sh) >= 256) sh++;
    int q = t >> sh, rem = t & ((1 << sh) - 1), half = 1 << (sh - 1);
    if (rem > half || (rem == half && (q & 1))) q++;
    return q << sh;
}
constexpr int kcidx(int p) {
    if (p < 256) return (p >> 3) * 24 + (p & 7);
    if (p < 512) return ((p - 256) >> 3) * 24 + 8 + (((p - 256) & 7) >> 1);
    if (p < 1024) { int q = p - 512, hi = q >> 8, rem = q & 255; return (rem >> 3) * 24 + 12 + 2 * hi + ((rem & 7) >> 2); }
    if (p < 2048) { int q = p - 1024; return ((q & 255) >> 3) * 24 + 16 + (q >> 8); }
    return 20;
}
constexpr int KC_ZERO = 23;
constexpr int tab_dense(int t) { return (t >= 0 && t <= 514) ? kcidx(rne8(t)) : KC_ZERO; }
constexpr int tab_extra(int t) { return (t >= 1027 && t <= 1028) ? kcidx(1024) : KC_ZERO; }
constexpr int tab_2(int s, int lag) { return (lag >= 32 && lag <= 63) ? kcidx(s == 0 ? 16 * (lag + 1) : 16 * lag + 4 * s) : KC_ZERO; }
constexpr int tab_3(int s, int lag) { return (lag >= 64 && lag <= 127) ? kcidx(s == 0 ? 16 * (lag + 1) : 16 * lag + 8) : KC_ZERO; }
struct TabMap {
    uint16_t v[TABN];
    constexpr TabMap() : v{} {
        for (int i = 0; i < 560; i++) { v[TD0 + i] = tab_dense(CD - i); v[TD1 + i] = tab_dense(CD + 1 - i); }
        for (int i = 0; i < 48; i++) { v[TE0 + i] = tab_extra(CE - i); v[TE1 + i] = tab_extra(CE + 1 - i); }
        for (int s = 0; s < 4; s++)
            for (int i = 0; i < T2C; i++) { v[T2B + s * T2S + i] = tab_2(s, C2 - i); v[T2B + s * T2S + T2C + i] = tab_2(s, C2 + 1 - i); }
        for (int s = 0; s < 2; s++)
            for (int i = 0; i < T3C; i++) { v[T3B + s * T3S + i] = tab_3(s, C3 - i); v[T3B + s * T3S + T3C + i] = tab_3(s, C3 + 1 - i); }
    }
};
__device__ const __align__(16) TabMap g_tabmap = TabMap();

__device__ __align__(1024) uint8_t g_kimg[65536];
__device__ __align__(1024) uint8_t g_vimg[65536 + 1024];
__device__ __align__(1024) uint8_t g_oimg[16 * 131072];
__device__ unsigned long long g_flag_kv[64];
__device__ unsigned g_flag_o[128];
__device__ unsigned g_epoch;
__device__ unsigned g_done;

#define PROF(i) do {} while (0)
#define PROF2(i) do {} while (0)
#define PROFC(i) do {} while (0)
#define PROF3(i) do {} while (0)

__device__ __forceinline__ uint32_t smem_u32(const void* p) { return (uint32_t)__cvta_generic_to_shared(p); }
__device__ __forceinline__ void mbar_init(uint32_t bar, uint32_t cnt) { asm volatile("mbarrier.init.shared::cta.b64 [%0], %1;" :: "r"(bar), "r"(cnt) : "memory"); }
__device__ __forceinline__ void mbar_expect_tx(uint32_t bar, uint32_t bytes) {
    asm volatile("mbarrier.arrive.expect_tx.shared::cta.b64 _, [%0], %1;" :: "r"(bar), "r"(bytes) : "memory"); }
__device__ __forceinline__ void mbar_wait(uint32_t bar, uint32_t parity) {
    uint32_t ok = 0;
    for (int it = 0; it < (1 << 22) && !ok; it++) {
        asm volatile("{ .reg .pred p; mbarrier.try_wait.parity.shared::cta.b64 p, [%1], %2; selp.u32 %0, 1, 0, p; }"
                     : "=r"(ok) : "r"(bar), "r"(parity) : "memory");
    }
}
__device__ __forceinline__ void tma_2d(uint32_t dst, const CUtensorMap* map, int c0, int c1, uint32_t bar) {
    asm volatile("cp.async.bulk.tensor.2d.shared::cluster.global.mbarrier::complete_tx::bytes [%0], [%1, {%3, %4}], [%2];"
                 :: "r"(dst), "l"((uint64_t)map), "r"(bar), "r"(c0), "r"(c1) : "memory");
}
__device__ __forceinline__ void tma_2d_mc(uint32_t dst, const CUtensorMap* map, int c0, int c1, uint32_t bar) {
    asm volatile("cp.async.bulk.tensor.2d.shared::cluster.global.mbarrier::complete_tx::bytes.multicast::cluster [%0], [%1, {%3, %4}], [%2], %5;"
                 :: "r"(dst), "l"((uint64_t)map), "r"(bar), "r"(c0), "r"(c1), "h"((uint16_t)3) : "memory");
}
__device__ __forceinline__ void bulk_g2s_mc(uint32_t dst, const void* src, uint32_t bytes, uint32_t bar) {
    asm volatile("cp.async.bulk.shared::cluster.global.mbarrier::complete_tx::bytes.multicast::cluster [%0], [%1], %2, [%3], %4;"
                 :: "r"(dst), "l"((uint64_t)src), "r"(bytes), "r"(bar), "h"((uint16_t)3) : "memory");
}
__device__ __forceinline__ void pair_sync(uint32_t bar, uint32_t peer) {
    uint32_t ra;
    asm volatile("mapa.shared::cluster.u32 %0, %1, %2;" : "=r"(ra) : "r"(bar), "r"(peer));
    asm volatile("mbarrier.arrive.shared::cluster.b64 _, [%0];" :: "r"(ra) : "memory");
    asm volatile("mbarrier.arrive.shared::cta.b64 _, [%0];" :: "r"(bar) : "memory");
    uint32_t ok = 0;
    for (int it = 0; it < (1 << 22) && !ok; it++) {
        asm volatile("{ .reg .pred p; mbarrier.try_wait.parity.shared::cta.b64 p, [%1], 0; selp.u32 %0, 1, 0, p; }"
                     : "=r"(ok) : "r"(bar) : "memory");
    }
}
__device__ __forceinline__ void fence_async_all() { asm volatile("fence.proxy.async.global;" ::: "memory"); }
__device__ __forceinline__ void fence_async_smem() { asm volatile("fence.proxy.async.shared::cta;" ::: "memory"); }
__device__ __forceinline__ unsigned ld_acquire(const unsigned* p) {
    unsigned v; asm volatile("ld.acquire.gpu.global.u32 %0, [%1];" : "=r"(v) : "l"(p) : "memory"); return v; }
__device__ __forceinline__ void st_release(unsigned* p, unsigned v) { asm volatile("st.release.gpu.global.u32 [%0], %1;" :: "l"(p), "r"(v) : "memory"); }
__device__ __forceinline__ void wait_flag(const unsigned* p, unsigned epoch) {
    for (int it = 0; it < (1 << 22); it++) { if (ld_acquire(p) == epoch) break; }
}
__device__ __forceinline__ unsigned long long ld_acquire64(const unsigned long long* p) {
    unsigned long long v; asm volatile("ld.acquire.gpu.global.u64 %0, [%1];" : "=l"(v) : "l"(p) : "memory"); return v; }
__device__ __forceinline__ void st_release64(unsigned long long* p, unsigned long long v) { asm volatile("st.release.gpu.global.u64 [%0], %1;" :: "l"(p), "l"(v) : "memory"); }
__device__ __forceinline__ float wait_flag64(const unsigned long long* p, unsigned epoch) {
    unsigned long long v = 0;
    for (int it = 0; it < (1 << 22); it++) { v = ld_acquire64(p); if ((unsigned)(v >> 32) == epoch) break; }
    return __uint_as_float((unsigned)v);
}
__device__ __forceinline__ void tma_3d_mc(uint32_t dst, const CUtensorMap* map, int c0, int c1, int c2, uint32_t bar) {
    asm volatile("cp.async.bulk.tensor.3d.shared::cluster.global.mbarrier::complete_tx::bytes.multicast::cluster [%0], [%1, {%3, %4, %5}], [%2], %6;"
                 :: "r"(dst), "l"((uint64_t)map), "r"(bar), "r"(c0), "r"(c1), "r"(c2), "h"((uint16_t)3) : "memory");
}
__device__ __forceinline__ void bar_sync(int id, int n) { asm volatile("bar.sync %0, %1;" :: "r"(id), "r"(n) : "memory"); }
__device__ __forceinline__ void bar_arrive(int id, int n) { asm volatile("bar.arrive %0, %1;" :: "r"(id), "r"(n) : "memory"); }
__device__ __forceinline__ void mbar_arrive(uint32_t bar) { asm volatile("mbarrier.arrive.shared::cta.b64 _, [%0];" :: "r"(bar) : "memory"); }

__device__ __forceinline__ uint64_t make_desc(uint32_t saddr, uint32_t lbo, uint32_t sbo, uint32_t swz) {
    uint64_t d = 0;
    d |= (uint64_t)((saddr & 0x3FFFF) >> 4);
    d |= (uint64_t)((lbo >> 4) & 0x3FFF) << 16;
    d |= (uint64_t)((sbo >> 4) & 0x3FFF) << 32;
    d |= (uint64_t)swz << 62;
    return d;
}
__device__ __forceinline__ void wg_fence() { asm volatile("wgmma.fence.sync.aligned;" ::: "memory"); }
__device__ __forceinline__ void wg_commit() { asm volatile("wgmma.commit_group.sync.aligned;" ::: "memory"); }
template<int N> __device__ __forceinline__ void wg_wait() { asm volatile("wgmma.wait_group.sync.aligned %0;" :: "n"(N) : "memory"); }
#define A4(d, o) "+f"(d[o + 0]), "+f"(d[o + 1]), "+f"(d[o + 2]), "+f"(d[o + 3])
#define A16(d, o) A4(d, o), A4(d, o + 4), A4(d, o + 8), A4(d, o + 12)

__device__ __forceinline__ void wg_pv(float* d, const uint32_t* a, uint32_t lo, uint32_t hi) {
    asm volatile("{ .reg .b64 dd; mov.b64 dd, {%16, %17};\n"
                 "wgmma.mma_async.sync.aligned.m64n24k16.f32.bf16.bf16 {%0,%1,%2,%3,%4,%5,%6,%7,%8,%9,%10,%11}, {%12,%13,%14,%15}, dd, 1, 1, 1, 1; }"
                 : A4(d, 0), A4(d, 4), A4(d, 8) : "r"(a[0]), "r"(a[1]), "r"(a[2]), "r"(a[3]), "r"(lo), "r"(hi));
}
__device__ __forceinline__ void wg_qk(float* d, const uint32_t* a, uint32_t lo) {
    asm volatile("{ .reg .b64 dd; mov.b64 dd, {%36, %37};\n"
                 "wgmma.mma_async.sync.aligned.m64n64k16.f32.bf16.bf16 {%0,%1,%2,%3,%4,%5,%6,%7,%8,%9,%10,%11,%12,%13,%14,%15,%16,%17,%18,%19,%20,%21,%22,%23,%24,%25,%26,%27,%28,%29,%30,%31}, {%32,%33,%34,%35}, dd, 0, 1, 1, 0; }"
                 : A16(d, 0), A16(d, 16) : "r"(a[0]), "r"(a[1]), "r"(a[2]), "r"(a[3]), "r"(lo), "r"(16));
}
__device__ __forceinline__ void wg_ss32(float* d, uint64_t da, uint64_t db) {
    asm volatile("wgmma.mma_async.sync.aligned.m64n32k16.f32.bf16.bf16 {%0,%1,%2,%3,%4,%5,%6,%7,%8,%9,%10,%11,%12,%13,%14,%15}, %16, %17, 1, 1, 1, 0, 1;"
                 : A16(d, 0) : "l"(da), "l"(db));
}
__device__ __forceinline__ void wg_ss16(float* d, uint64_t da, uint64_t db) {
    asm volatile("wgmma.mma_async.sync.aligned.m64n16k16.f32.bf16.bf16 {%0,%1,%2,%3,%4,%5,%6,%7}, %8, %9, 1, 1, 1, 0, 1;"
                 : A4(d, 0), A4(d, 4) : "l"(da), "l"(db));
}
template<int N> __device__ __forceinline__ void fence_regs(float* r) {
    #pragma unroll
    for (int i = 0; i < N; i++) asm volatile("" : "+f"(r[i]) :: "memory");
}
__device__ __forceinline__ void mma_bf16(float* d, uint32_t a0, uint32_t a1, uint32_t a2, uint32_t a3, uint32_t b0, uint32_t b1) {
    asm volatile("mma.sync.aligned.m16n8k16.row.col.f32.bf16.bf16.f32 {%0,%1,%2,%3}, {%4,%5,%6,%7}, {%8,%9}, {%0,%1,%2,%3};"
                 : "+f"(d[0]), "+f"(d[1]), "+f"(d[2]), "+f"(d[3]) : "r"(a0), "r"(a1), "r"(a2), "r"(a3), "r"(b0), "r"(b1));
}
__device__ __forceinline__ void mma_f16(float* d, const uint32_t* a, uint32_t b0, uint32_t b1) {
    asm volatile("mma.sync.aligned.m16n8k16.row.col.f32.f16.f16.f32 {%0,%1,%2,%3}, {%4,%5,%6,%7}, {%8,%9}, {%0,%1,%2,%3};"
                 : "+f"(d[0]), "+f"(d[1]), "+f"(d[2]), "+f"(d[3]) : "r"(a[0]), "r"(a[1]), "r"(a[2]), "r"(a[3]), "r"(b0), "r"(b1));
}
__device__ __forceinline__ void ldsm4(uint32_t* r, uint32_t addr) {
    asm volatile("ldmatrix.sync.aligned.m8n8.x4.shared.b16 {%0,%1,%2,%3}, [%4];" : "=r"(r[0]), "=r"(r[1]), "=r"(r[2]), "=r"(r[3]) : "r"(addr) : "memory");
}
__device__ __forceinline__ void ldsm4t(uint32_t* r, uint32_t addr) {
    asm volatile("ldmatrix.sync.aligned.m8n8.x4.trans.shared.b16 {%0,%1,%2,%3}, [%4];" : "=r"(r[0]), "=r"(r[1]), "=r"(r[2]), "=r"(r[3]) : "r"(addr) : "memory");
}
__device__ __forceinline__ uint32_t lds32(uint32_t addr) { uint32_t v; asm volatile("ld.shared.u32 %0, [%1];" : "=r"(v) : "r"(addr) : "memory"); return v; }
__device__ __forceinline__ uint32_t swz(uint32_t a) { return a ^ ((a >> 3) & 16u); }
__device__ __forceinline__ void sts32(uint32_t addr, uint32_t v) { asm volatile("st.shared.u32 [%0], %1;" :: "r"(addr), "r"(v) : "memory"); }
__device__ __forceinline__ void sts128(uint32_t addr, uint4 v) { asm volatile("st.shared.v4.u32 [%0], {%1,%2,%3,%4};" :: "r"(addr), "r"(v.x), "r"(v.y), "r"(v.z), "r"(v.w) : "memory"); }
__device__ __forceinline__ uint4 lds128(uint32_t addr) { uint4 v; asm volatile("ld.shared.v4.u32 {%0,%1,%2,%3}, [%4];" : "=r"(v.x), "=r"(v.y), "=r"(v.z), "=r"(v.w) : "r"(addr) : "memory"); return v; }
__device__ __forceinline__ float ex2f(float x) { float r; asm("ex2.approx.ftz.f32 %0, %1;" : "=f"(r) : "f"(x)); return r; }
__device__ __forceinline__ uint32_t pack_bf16(float lo, float hi) { uint32_t r; asm("cvt.rn.bf16x2.f32 %0, %1, %2;" : "=r"(r) : "f"(hi), "f"(lo)); return r; }
__device__ __forceinline__ uint32_t pack_f16(float lo, float hi) { uint32_t r; asm("cvt.rn.f16x2.f32 %0, %1, %2;" : "=r"(r) : "f"(hi), "f"(lo)); return r; }
__device__ __forceinline__ float bf_lo(uint32_t v) { return __uint_as_float(v << 16); }
__device__ __forceinline__ float bf_hi(uint32_t v) { return __uint_as_float(v & 0xFFFF0000u); }
__device__ __forceinline__ float bf_round(float x) { return __bfloat162float(__float2bfloat16_rn(x)); }

__device__ __forceinline__ uint32_t exp_mufu(float x0, float x1) { return pack_bf16(ex2f(x0), ex2f(x1)); }
#define SW_MAGIC (256.0f + 127.0f - 0.598938f)
__device__ __forceinline__ uint32_t exp_sw(float x0, float x1, uint32_t cA, uint32_t cB) {
    float t0 = x0 + SW_MAGIC, t1 = x1 + SW_MAGIC;
    uint32_t L, mh, ec, r;
    asm("prmt.b32 %0, %1, %2, 0x6521;" : "=r"(L) : "r"(__float_as_uint(t0)), "r"(__float_as_uint(t1)));
    asm("lop3.b32 %0, %1, 0x007F007F, %2, 0xEA;" : "=r"(mh) : "r"(L), "r"(cA));
    asm("lop3.b32 %0, %1, 0x7F807F80, %2, 0xEA;" : "=r"(ec) : "r"(L), "r"(cB));
    asm("fma.rn.bf16x2 %0, %1, %2, %3;" : "=r"(r) : "r"(L), "r"(mh), "r"(ec));
    return r;
}
constexpr uint32_t MUFU_MASK = 0x4949;

struct cf { float x, y; };
__device__ __forceinline__ cf cmul(cf a, cf b) { cf r; r.x = a.x * b.x - a.y * b.y; r.y = a.x * b.y + a.y * b.x; return r; }
__device__ __forceinline__ cf cexp_p(float a2, float b, float p) {
    float e = ex2f(a2 * p);
    float ph = b * p;
    ph -= (ph + 12582912.0f) - 12582912.0f;
    float ang = ph * 6.283185307f;
    cf r; r.x = e * __cosf(ang); r.y = e * __sinf(ang);
    return r;
}
__device__ __forceinline__ uint32_t h2_cmul(uint32_t w, uint32_t wsw, uint32_t e) {
    __half2 hw = *(__half2*)&w, hs = *(__half2*)&wsw, he = *(__half2*)&e;
    __half2 r = __hfma2(hs, __high2half2(he), __hmul2(hw, __low2half2(he)));
    return *(uint32_t*)&r;
}

template<bool B> struct BoolC { static constexpr bool value = B; };
struct Params {
    const __nv_bfloat16 *u, *lar, *aim, *cre, *cim, *logdt, *dskip;
    __nv_bfloat16* out;
};

constexpr int B_O = 0, B_KV = 8, B_WO = 12, B_WQ2 = 13, B_ST = 14, B_H = 15, B_X = 17, B_U = 19, B_WQ = 20;

__device__ __forceinline__ void helper_role(const Params& P, uint8_t* sp, uint32_t sb, unsigned epoch) {
    const uint32_t sBa = sb + SM_B;
    const int tid = threadIdx.x - 544;
    const int d0 = blockIdx.x * 4;
    uint8_t* sB = sp + SM_B;
    const uint2 dsk = __ldg((const uint2*)(P.dskip + d0));
    asm volatile("barrier.cluster.wait.aligned;" ::: "memory");
    {
        const int hg = blockIdx.x & 7;
        if (hg < 4 && tid < 32) {
            bar_sync(3, 160);
            if (tid == 0) {
                const float* s_misc = (const float*)(sp + SM_BAR + 256);
                const float st = fmaxf(fmaxf(s_misc[20], s_misc[21]), fmaxf(s_misc[22], s_misc[23]));
                st_release64(&g_flag_kv[((blockIdx.x >> 3) * 2 + (hg & 1)) * 2 + (hg >> 1)], ((unsigned long long)epoch << 32) | __float_as_uint(st));
            }
            __syncwarp();
        }
    }
    PROF2(2);
    bar_sync(10, 608);
    {
        uint32_t dd[4] = {__byte_perm(dsk.x, 0, 0x1010), __byte_perm(dsk.x, 0, 0x3232), __byte_perm(dsk.y, 0, 0x1010), __byte_perm(dsk.y, 0, 0x3232)};
        #pragma unroll 2
        for (int pi = tid; pi < 1024; pi += 96) {
            const int l = 2 * pi;
            uint32_t r[4];
            #pragma unroll
            for (int cc = 0; cc < 4; cc++) {
                const uint32_t y2 = *(const uint32_t*)(sB + S_Y + cc * 4096 + l * 2);
                const uint32_t u2 = lds32(swz(sBa + S_U + cc * ULEN * 2 + (PADU + l) * 2));
                __nv_bfloat162 pr = __hmul2(*(const __nv_bfloat162*)&u2, *(const __nv_bfloat162*)&dd[cc]);
                __nv_bfloat162 sm = __hadd2(*(const __nv_bfloat162*)&y2, pr);
                r[cc] = *(uint32_t*)&sm;
            }
            *(uint2*)(P.out + (size_t)l * 1024 + 512 + d0) = make_uint2(__byte_perm(r[0], r[1], 0x5410), __byte_perm(r[2], r[3], 0x5410));
            *(uint2*)(P.out + (size_t)(l + 1) * 1024 + 512 + d0) = make_uint2(__byte_perm(r[0], r[1], 0x7632), __byte_perm(r[2], r[3], 0x7632));
        }
    }
    bar_arrive(11, 128);
    PROF2(4);
}

__global__ void __cluster_dims__(2, 1, 1) __launch_bounds__(NTHR, 1)
fused_kernel(const __grid_constant__ CUtensorMap tm_x, const __grid_constant__ CUtensorMap tm_wq,
             const __grid_constant__ CUtensorMap tm_wo, const __grid_constant__ CUtensorMap tm_wk,
             const __grid_constant__ CUtensorMap tm_wv, const __grid_constant__ CUtensorMap tm_u, const Params P) {
    extern __shared__ uint8_t smem_raw[];
    const uint32_t sb = (smem_u32(smem_raw) + 1023u) & ~1023u;
    uint8_t* sp = smem_raw + (sb - smem_u32(smem_raw));

    const int tid = threadIdx.x, warp = tid >> 5, lane = tid & 31, wg = tid >> 7, wiw = warp & 3;
    const int g = lane >> 2, t = lane & 3;
    const int qb = blockIdx.x >> 3, hg = blockIdx.x & 7;
    const uint32_t rank = blockIdx.x & 1;
    const int rowhalf = wg & 1, nh = wg >> 1;
    const bool kv_cta = hg < 4;
    const int kv_sel = hg >> 1;
    const bool kv_wg = kv_cta && (wg == (hg & 1));

    const uint32_t bars = sb + SM_BAR;
    float* s_misc = (float*)(sp + SM_BAR + 256);
    const CUtensorMap* tm_kv = kv_sel ? &tm_wv : &tm_wk;

    PROF(0);
    unsigned short p_lar = 0, p_aim = 0, p_cre = 0, p_cim = 0, p_ldt = 0;
    if (wg < 4) {
        const int n = (blockIdx.x * 4 + wg) * 128 + (tid & 127);
        p_lar = __ldg((const unsigned short*)P.lar + n);
        p_aim = __ldg((const unsigned short*)P.aim + n);
        p_cre = __ldg((const unsigned short*)P.cre + n);
        p_cim = __ldg((const unsigned short*)P.cim + n);
        p_ldt = __ldg((const unsigned short*)P.logdt + blockIdx.x * 4 + wg);
    } else if (warp == 16) {
        PROF3(5);
        if (lane == 0) {
            asm volatile("prefetch.tensormap [%0];" :: "l"((uint64_t)&tm_x) : "memory");
            asm volatile("prefetch.tensormap [%0];" :: "l"((uint64_t)tm_kv) : "memory");
            asm volatile("prefetch.tensormap [%0];" :: "l"((uint64_t)&tm_wq) : "memory");
            asm volatile("prefetch.tensormap [%0];" :: "l"((uint64_t)&tm_u) : "memory");
            mbar_init(bars + 8 * B_X, 1);
            mbar_init(bars + 8 * B_X + 8, 1);
            mbar_init(bars + 8 * B_U, 1);
            asm volatile("fence.mbarrier_init.release.cluster;" ::: "memory");
            mbar_expect_tx(bars + 8 * B_X, 65536u + (kv_cta ? 8192u : 0u));
            mbar_expect_tx(bars + 8 * B_X + 8, 65536u + (kv_cta ? 8192u : 0u));
            mbar_expect_tx(bars + 8 * B_U, 32768u);
        }
        __syncwarp();
        PROF3(6);
    }
    asm volatile("barrier.cluster.arrive.relaxed.aligned;" ::: "memory");
    const unsigned epoch = *(volatile unsigned*)&g_epoch + 1u;
    if (warp > 16) {
        if (lane == 0) {
            for (int i = warp - 17; i < B_X; i += 3) {
                mbar_init(bars + 8 * i, i >= B_H ? 2 : 1);
                if (i <= B_WQ2) mbar_expect_tx(bars + 8 * i, i < B_KV + 2 ? 16384u : i == B_KV + 2 ? 32768u : i <= B_WO ? 65536u : 32768u);
            }
            asm volatile("fence.mbarrier_init.release.cluster;" ::: "memory");
            fence_async_smem();
        } else if (warp == 19) {
            asm volatile("prefetch.global.L2 [%0];" :: "l"((const char*)g_tabmap.v + (lane - 1) * 128));
            if (lane < 5) asm volatile("prefetch.global.L2 [%0];" :: "l"((const char*)g_tabmap.v + (lane + 30) * 128));
        }
        __syncwarp();
    }
    asm volatile("barrier.cluster.wait.aligned;" ::: "memory");
    PROF(5);
    if (warp == 16 && lane == 0) {
        tma_3d_mc(sb + (rank ? SM_A : SM_B), &tm_x, 0, qb * 128, rank * 4, bars + 8 * (B_X + rank));
        if (kv_cta) {
            #pragma unroll
            for (int i = 0; i < 4; i++) tma_2d(sb + SM_WKV + i * 4096, tm_kv, (i >> 1) * 8, (i & 1) * 256, bars + 8 * (B_X + (i & 1)));
        }
        mbar_init(bars + 8 * B_WQ, 1);
        asm volatile("fence.mbarrier_init.release.cluster;" ::: "memory");
        fence_async_smem();
        mbar_expect_tx(bars + 8 * B_WQ, 32768u);
        tma_2d(sb + SM_WQ, &tm_wq, hg * 64, 0, bars + 8 * B_WQ);
        #pragma unroll
        for (int i = 0; i < 4; i++) tma_2d_mc(sb + SM_SLAB + (rank * 4 + i) * 4096, &tm_u, (blockIdx.x >> 1) * 8, (rank * 4 + i) * 256, bars + 8 * B_U);
    }
    __syncwarp();
    asm volatile("barrier.cluster.arrive.relaxed.aligned;" ::: "memory");

    if (warp == 16) {
        if (lane == 0) asm volatile("prefetch.tensormap [%0];" :: "l"((uint64_t)&tm_wo) : "memory");
        asm volatile("barrier.cluster.wait.aligned;" ::: "memory");
        PROF3(10);
        bar_sync(13, 544);
        if (lane == 0) { fence_async_smem(); tma_2d(sb + SM_SLAB, &tm_wq, hg * 64, 256, bars + 8 * B_WQ2); }
        bar_sync(14, 544);
        if (lane == 0) pair_sync(bars + 8 * B_H, rank ^ 1);
        __syncwarp();
        PROF3(11);
        *(uint4*)(sp + SM_V + 32768 + lane * 32) = make_uint4(0x3F803F80u, 0x3F803F80u, 0x3F803F80u, 0x3F803F80u);
        *(uint4*)(sp + SM_V + 32768 + lane * 32 + 16) = make_uint4(0x3F803F80u, 0x3F803F80u, 0x3F803F80u, 0x3F803F80u);
        fence_async_smem();
        float km = wait_flag64(&g_flag_kv[2 * lane], epoch);
        float vm = wait_flag64(&g_flag_kv[2 * lane + 1], epoch);
        __syncwarp();
        PROF3(12);
        if (lane == 0) {
            fence_async_all();
            #pragma unroll
            for (int i = 0; i < 4; i++) {
                const uint32_t k0 = i == 0 ? 0 : 128u << i, nk = i == 0 ? 256 : 128u << i;
                const uint32_t bar = bars + 8 * (B_KV + i);
                if (rank == 0) bulk_g2s_mc(sb + SM_K + k0 * 32, g_kimg + k0 * 32, nk * 32, bar);
                else {
                    bulk_g2s_mc(sb + SM_V + k0 * 16, g_vimg + k0 * 16, nk * 16, bar);
                    bulk_g2s_mc(sb + SM_V + 66560 - (k0 + nk) * 16, g_vimg + 66560 - (k0 + nk) * 16, nk * 16, bar);
                }
            }
        }
        #pragma unroll
        for (int o = 16; o; o >>= 1) { km = fmaxf(km, __shfl_xor_sync(0xffffffffu, km, o)); vm = fmaxf(vm, __shfl_xor_sync(0xffffffffu, vm, o)); }
        if (lane == 0) { s_misc[16] = km; s_misc[17] = vm; mbar_arrive(bars + 8 * B_ST); }
        PROF3(13);
        bar_sync(11, 128);
        if (lane < 2) { fence_async_smem(); tma_2d(sb + SM_B + lane * 32768, &tm_wo, hg * 64, lane * 256, bars + 8 * B_WO); }
        bar_sync(12, 544);
        if (lane == 0) {
            st_release(&g_flag_o[blockIdx.x], epoch);
            pair_sync(bars + 8 * (B_H + 1), rank ^ 1);
        }
        __syncwarp();
        PROF3(14);
        if (lane < 4) {
            const int src = 2 * lane + rank;
            wait_flag(&g_flag_o[qb * 8 + src], epoch);
            fence_async_all();
            bulk_g2s_mc(sb + SM_A + src * 16384, g_oimg + qb * 131072 + src * 16384, 16384, bars + 8 * (B_O + src));
        }
        __syncwarp();
        PROF3(15);
        if (lane == 0) {
            const unsigned prev = atomicAdd(&g_done, 1u);
            if (prev == NCTA - 1) {
                g_done = 0;
                __threadfence();
                *(volatile unsigned*)&g_epoch = epoch;
            }
        }
    } else if (wg == 4) {
        helper_role(P, sp, sb, epoch);
    } else {
        uint8_t* sB = sp + SM_B;
        const uint32_t sBa = sb + SM_B;
        {
            const int c = wg;
            const float dt = bf_round(expf(bf_lo(p_ldt)));
            const float are = -bf_round(expf(bf_lo(p_lar))) * dt;
            const float aim = bf_lo(p_aim) * dt;
            float cr = 2.0f * (bf_lo(p_cre) * dt);
            float ci = 2.0f * (bf_lo(p_cim) * dt);
            const float a2 = are * 1.4426950408889634f, bb = aim * 0.15915494309189535f;
            float m = fmaxf(fabsf(cr), fabsf(ci));
            #pragma unroll
            for (int o = 16; o; o >>= 1) m = fmaxf(m, __shfl_xor_sync(0xffffffffu, m, o));
            int ebits = (__float_as_uint(m) >> 23) & 0xFF;
            ebits = min(max(ebits, 2), 250);
            const float scale = __uint_as_float((uint32_t)(ebits + 1) << 23);
            const float iscale = __uint_as_float((uint32_t)(253 - ebits) << 23);
            cf cc; cc.x = cr * iscale; cc.y = ci * iscale;

            const uint32_t stg = sBa + S_KC + warp * 1024;
            uint4* stp = (uint4*)(sB + S_KC + warp * 1024 + lane * 32);
            const uint32_t fa = stg + t * 32 + g * 4;

            uint32_t af[4][2][4];
            cf E256;
            {
                const cf E8 = cexp_p(a2, bb, 8.0f);
                uint32_t w[8];
                cf cur; cur.x = 1.0f; cur.y = 0.0f;
                w[0] = pack_f16(1.0f, 0.0f);
                cur = E8; w[1] = pack_f16(cur.x, cur.y);
                #pragma unroll
                for (int i = 2; i < 8; i++) { cur = cmul(cur, E8); w[i] = pack_f16(cur.x, cur.y); }
                stp[0] = make_uint4(w[0], w[1], w[2], w[3]);
                stp[1] = make_uint4(w[4], w[5], w[6], w[7]);
                const cf E64 = cexp_p(a2, bb, 64.0f);
                const cf E128 = cmul(E64, E64), E192 = cmul(E128, E64);
                E256 = cexp_p(a2, bb, 256.0f);
                const uint32_t e1 = pack_f16(E64.x, E64.y), e2 = pack_f16(E128.x, E128.y), e3 = pack_f16(E192.x, E192.y);
                __syncwarp();
                #pragma unroll
                for (int s = 0; s < 4; s++) {
                    #pragma unroll
                    for (int hh = 0; hh < 2; hh++) {
                        const uint32_t w0 = lds32(fa + s * 256 + hh * 128);
                        const uint32_t wsw = __byte_perm(w0, 0, 0x1032) ^ 0x00008000u;
                        const int src = 8 * s + t + 4 * hh;
                        const uint32_t f1 = __shfl_sync(0xffffffffu, e1, src), f2 = __shfl_sync(0xffffffffu, e2, src), f3 = __shfl_sync(0xffffffffu, e3, src);
                        af[s][0][2 * hh] = w0;
                        af[s][0][2 * hh + 1] = h2_cmul(w0, wsw, f1);
                        af[s][1][2 * hh] = h2_cmul(w0, wsw, f2);
                        af[s][1][2 * hh + 1] = h2_cmul(w0, wsw, f3);
                    }
                }
                __syncwarp();
            }
            float acc[2][3][4];
            #pragma unroll
            for (int i = 0; i < 24; i++) (&acc[0][0][0])[i] = 0.0f;
            const cf E1 = cexp_p(a2, bb, 1.0f);
            const cf E2 = cmul(E1, E1), E4 = cmul(E2, E2);
            cf X512;
            #pragma unroll
            for (int nt = 0; nt < 3; nt++) {
                uint32_t xv[8];
                if (nt == 0) {
                    cf cur = cc;
                    xv[0] = pack_f16(cur.x, -cur.y);
                    #pragma unroll
                    for (int i = 1; i < 8; i++) { cur = cmul(cur, E1); xv[i] = pack_f16(cur.x, -cur.y); }
                } else if (nt == 1) {
                    cf cur = cmul(cc, E256);
                    X512 = cmul(cur, E256);
                    xv[0] = pack_f16(cur.x, -cur.y);
                    #pragma unroll
                    for (int i = 1; i < 4; i++) { cur = cmul(cur, E2); xv[i] = pack_f16(cur.x, -cur.y); }
                    cur = cmul(X512, E4);
                    xv[4] = pack_f16(X512.x, -X512.y); xv[5] = pack_f16(cur.x, -cur.y);
                    X512 = cmul(X512, E256);
                    cur = cmul(X512, E4);
                    xv[6] = pack_f16(X512.x, -X512.y); xv[7] = pack_f16(cur.x, -cur.y);
                } else {
                    cf cur = X512;
                    #pragma unroll
                    for (int i = 0; i < 5; i++) { cur = cmul(cur, E256); xv[i] = pack_f16(cur.x, -cur.y); }
                    xv[5] = 0; xv[6] = 0; xv[7] = 0;
                }
                stp[0] = make_uint4(xv[0], xv[1], xv[2], xv[3]);
                stp[1] = make_uint4(xv[4], xv[5], xv[6], xv[7]);
                __syncwarp();
                #pragma unroll
                for (int s = 0; s < 4; s++) {
                    const uint32_t b0 = lds32(fa + s * 256), b1 = lds32(fa + s * 256 + 128);
                    mma_f16(acc[0][nt], af[s][0], b0, b1);
                    mma_f16(acc[1][nt], af[s][1], b0, b1);
                }
                __syncwarp();
            }
            float* kc = (float*)(sB + S_KC + c * 4096);
            bar_sync(4 + c, 128);
            #pragma unroll 1
            for (int step = 0; step < 4; step++) {
                if ((warp & 3) == step) {
                    #pragma unroll
                    for (int mt = 0; mt < 2; mt++)
                        #pragma unroll
                        for (int nt = 0; nt < 3; nt++)
                            #pragma unroll
                            for (int hh = 0; hh < 2; hh++) {
                                float2* p = (float2*)(kc + (mt * 16 + hh * 8 + g) * 24 + nt * 8 + 2 * t);
                                float2 v = make_float2(acc[mt][nt][2 * hh] * scale, acc[mt][nt][2 * hh + 1] * scale);
                                if (step) { float2 o = *p; v.x += o.x; v.y += o.y; }
                                *p = v;
                            }
                }
                if (step < 3) bar_sync(4 + c, 128);
            }
        }

        asm volatile("barrier.cluster.wait.aligned;" ::: "memory");
        PROF(4);
        uint32_t q[2][4];
        {
            float acc[16], akv[8];
            #pragma unroll
            for (int i = 0; i < 16; i++) acc[i] = 0.0f;
            #pragma unroll
            for (int i = 0; i < 8; i++) akv[i] = 0.0f;
            fence_regs<16>(acc);
            fence_regs<8>(akv);
            const uint64_t dA0 = make_desc(sb + SM_B + rowhalf * 8192, 16, 1024, 1);
            const uint64_t dA1 = make_desc(sb + SM_A + rowhalf * 8192, 16, 1024, 1) - 4096;
            const uint64_t dB = make_desc(sb + SM_WQ + nh * 64, 16, 1024, 1);
            const uint64_t dC = make_desc(sb + SM_WKV, 128, 8192, 0);
            if (kv_wg) {
                #pragma unroll 1
                for (int ch = 0; ch < 8; ch++) {
                    if ((ch & 3) == 0) mbar_wait(bars + 8 * (B_X + (ch >> 2)), 0);
                    const uint64_t dA = ch < 4 ? dA0 : dA1;
                    wg_fence();
                    #pragma unroll
                    for (int ks = 0; ks < 4; ks++) wg_ss16(akv, dA + ch * 1024 + ks * 2, dC + (ch * 4 + ks) * 16);
                    wg_commit();
                }
                wg_wait<0>();
            }
            fence_regs<8>(akv);
            if (kv_wg) {
                const int key = qb * 128 + rowhalf * 64 + wiw * 16 + g;
                uint32_t pk[4];
                #pragma unroll
                for (int i = 0; i < 4; i++) pk[i] = pack_bf16(akv[2 * i], akv[2 * i + 1]);
                float st;
                if (kv_sel == 0) {
                    uint8_t* b = g_kimg + (key >> 3) * 256 + (key & 7) * 16 + 4 * t;
                    *(uint32_t*)(b) = pk[0]; *(uint32_t*)(b + 256) = pk[1]; *(uint32_t*)(b + 128) = pk[2]; *(uint32_t*)(b + 384) = pk[3];
                    float n0 = bf_lo(pk[0]) * bf_lo(pk[0]) + bf_hi(pk[0]) * bf_hi(pk[0]) + bf_lo(pk[2]) * bf_lo(pk[2]) + bf_hi(pk[2]) * bf_hi(pk[2]);
                    float n1 = bf_lo(pk[1]) * bf_lo(pk[1]) + bf_hi(pk[1]) * bf_hi(pk[1]) + bf_lo(pk[3]) * bf_lo(pk[3]) + bf_hi(pk[3]) * bf_hi(pk[3]);
                    n0 += __shfl_xor_sync(0xffffffffu, n0, 1); n0 += __shfl_xor_sync(0xffffffffu, n0, 2);
                    n1 += __shfl_xor_sync(0xffffffffu, n1, 1); n1 += __shfl_xor_sync(0xffffffffu, n1, 2);
                    st = (n0 != n0 || n1 != n1) ? __int_as_float(0x7f800000) : fmaxf(n0, n1);
                } else {
                    uint8_t* lo = g_vimg + key * 16 + 4 * t;
                    uint8_t* hi = g_vimg + 33792 + (31 - (key >> 6)) * 1024 + (key & 63) * 16 + 4 * t;
                    *(uint32_t*)(lo) = pk[0]; *(uint32_t*)(lo + 128) = pk[1]; *(uint32_t*)(hi) = pk[2]; *(uint32_t*)(hi + 128) = pk[3];
                    st = 0.0f;
                    #pragma unroll
                    for (int i = 0; i < 4; i++) {
                        float a = fabsf(bf_lo(pk[i])), b = fabsf(bf_hi(pk[i]));
                        st = (a != a || b != b) ? __int_as_float(0x7f800000) : fmaxf(st, fmaxf(a, b));
                    }
                }
                #pragma unroll
                for (int o = 16; o; o >>= 1) st = fmaxf(st, __shfl_xor_sync(0xffffffffu, st, o));
                if (lane == 0) s_misc[20 + wiw] = st;
                bar_arrive(3, 160);
            }
            uint32_t mp[9];
            #pragma unroll
            for (int i = 0; i < 9; i++) { const int w = (tid & 127) + 128 * i; mp[i] = (w < TABN / 2) ? __ldg((const uint32_t*)g_tabmap.v + w) : 0u; }
            mbar_wait(bars + 8 * B_WQ, 0);
            mbar_wait(bars + 8 * B_X, 0);
            PROF(2);
            #pragma unroll 1
            for (int ch = 0; ch < 4; ch++) {
                wg_fence();
                #pragma unroll
                for (int ks = 0; ks < 4; ks++) wg_ss32(acc, dA0 + ch * 1024 + ks * 2, dB + (ch * 4 + ks) * 128);
                wg_commit();
            }
            wg_wait<0>();
            fence_regs<16>(acc);
            bar_sync(1, 512);
            PROF(15);
            if (tid < 4 * (PADU / 8)) sts128(swz(sBa + S_U + (tid / (PADU / 8)) * ULEN * 2 + (tid % (PADU / 8)) * 16), make_uint4(0, 0, 0, 0));
            PROF(8);
            mbar_wait(bars + 8 * B_U, 0);
            PROF(14);
            #pragma unroll
            for (int i = 0; i < 2; i++) {
                const int l = 2 * (tid + 512 * i);
                const uint2 r0 = *(const uint2*)(sp + SM_SLAB + l * 16 + rank * 8), r1 = *(const uint2*)(sp + SM_SLAB + l * 16 + 16 + rank * 8);
                const uint32_t dst = sBa + S_U + (PADU + l) * 2;
                sts32(swz(dst), __byte_perm(r0.x, r1.x, 0x5410));
                sts32(swz(dst + ULEN * 2), __byte_perm(r0.x, r1.x, 0x7632));
                sts32(swz(dst + ULEN * 4), __byte_perm(r0.y, r1.y, 0x5410));
                sts32(swz(dst + ULEN * 6), __byte_perm(r0.y, r1.y, 0x7632));
            }
            bar_arrive(13, 544);
            {
                const float* kc = (const float*)(sB + S_KC + wg * 4096);
                uint32_t* tab = (uint32_t*)(sB + S_TAB + wg * TABN * 2);
                #pragma unroll
                for (int i = 0; i < 9; i++) { const int w = (tid & 127) + 128 * i; if (w < TABN / 2) tab[w] = pack_bf16(kc[mp[i] & 0xFFFF], kc[mp[i] >> 16]); }
            }
            PROF(1);
            mbar_wait(bars + 8 * B_WQ2, 0);
            mbar_wait(bars + 8 * (B_X + 1), 0);
            fence_regs<16>(acc);
            #pragma unroll 1
            for (int ch = 4; ch < 8; ch++) {
                wg_fence();
                #pragma unroll
                for (int ks = 0; ks < 4; ks++) wg_ss32(acc, dA1 + ch * 1024 + ks * 2, dB + (ch * 4 + ks) * 128);
                wg_commit();
            }
            wg_wait<0>();
            fence_regs<16>(acc);
            bar_arrive(14, 544);
            const float QS = 0.25f * 1.4426950408889634f;
            float qm = 0.0f;
            #pragma unroll
            for (int i = 0; i < 2; i++) {
                #pragma unroll
                for (int j = 0; j < 4; j++) q[i][j] = pack_bf16(acc[8 * i + 2 * j] * QS, acc[8 * i + 2 * j + 1] * QS);
                float n0 = bf_lo(q[i][0]) * bf_lo(q[i][0]) + bf_hi(q[i][0]) * bf_hi(q[i][0]) + bf_lo(q[i][2]) * bf_lo(q[i][2]) + bf_hi(q[i][2]) * bf_hi(q[i][2]);
                float n1 = bf_lo(q[i][1]) * bf_lo(q[i][1]) + bf_hi(q[i][1]) * bf_hi(q[i][1]) + bf_lo(q[i][3]) * bf_lo(q[i][3]) + bf_hi(q[i][3]) * bf_hi(q[i][3]);
                n0 += __shfl_xor_sync(0xffffffffu, n0, 1); n0 += __shfl_xor_sync(0xffffffffu, n0, 2);
                n1 += __shfl_xor_sync(0xffffffffu, n1, 1); n1 += __shfl_xor_sync(0xffffffffu, n1, 2);
                qm = (n0 != n0 || n1 != n1) ? __int_as_float(0x7f800000) : fmaxf(qm, fmaxf(n0, n1));
            }
            #pragma unroll
            for (int o = 16; o; o >>= 1) qm = fmaxf(qm, __shfl_xor_sync(0xffffffffu, qm, o));
            if (lane == 0) s_misc[warp] = qm;
        }
        PROF(3);
        bar_sync(1, 512);
        #pragma unroll 1
        for (int task = tid; task < 4 * 194; task += 512) {
            const int c = task / 194, i = task % 194;
            const uint32_t src = sBa + S_U + c * ULEN * 2 + (PADU + 8 * i - WPAD - 8) * 2;
            const uint4 v0 = lds128(swz(src)), v1 = lds128(swz(src + 16)), v2 = lds128(swz(src + 32));
            float x[24];
            const uint32_t vv[12] = {v0.x, v0.y, v0.z, v0.w, v1.x, v1.y, v1.z, v1.w, v2.x, v2.y, v2.z, v2.w};
            #pragma unroll
            for (int k = 0; k < 12; k++) { x[2 * k] = bf_lo(vv[k]); x[2 * k + 1] = bf_hi(vv[k]); }
            float w3[12], w5[8];
            #pragma unroll
            for (int e = 0; e < 12; e++) w3[e] = (x[3 + e] + x[4 + e]) + x[5 + e];
            #pragma unroll
            for (int e = 0; e < 8; e++) w5[e] = w3[4 + e] + (x[6 + e] + x[10 + e]);
            sts128(swz(sBa + S_W3 + c * W2LEN * 2 + i * 16), make_uint4(pack_bf16(w3[0], w3[1]), pack_bf16(w3[2], w3[3]), pack_bf16(w3[4], w3[5]), pack_bf16(w3[6], w3[7])));
            sts128(swz(sBa + S_W5 + c * W2LEN * 2 + i * 16), make_uint4(pack_bf16(w5[0], w5[1]), pack_bf16(w5[2], w5[3]), pack_bf16(w5[4], w5[5]), pack_bf16(w5[6], w5[7])));
            if (i < 130) {
                float w7[8], w9[8];
                #pragma unroll
                for (int e = 0; e < 8; e++) { w7[e] = w5[e] + (x[5 + e] + x[11 + e]); w9[e] = w7[e] + (x[4 + e] + x[12 + e]); }
                sts128(swz(sBa + S_W7 + c * W3LEN * 2 + i * 16), make_uint4(pack_bf16(w7[0], w7[1]), pack_bf16(w7[2], w7[3]), pack_bf16(w7[4], w7[5]), pack_bf16(w7[6], w7[7])));
                sts128(swz(sBa + S_W9 + c * W3LEN * 2 + i * 16), make_uint4(pack_bf16(w9[0], w9[1]), pack_bf16(w9[2], w9[3]), pack_bf16(w9[4], w9[5]), pack_bf16(w9[6], w9[7])));
            }
        }
        bar_sync(1, 512);
        PROF(6);
        {
            const int c = wg, ps = (wiw + c) & 3;
            float acc[2][2][4];
            #pragma unroll
            for (int i = 0; i < 16; i++) (&acc[0][0][0])[i] = 0.0f;
            const uint32_t tabc = sBa + S_TAB + c * TABN * 2;
            const int e2 = (g - 2 * t) * 2;
            const int mi = lane >> 3, r8 = lane & 7;
            const uint32_t frag = (16 * (8 * (mi >> 1) + r8) + 8 * (mi & 1)) * 2;
            const uint32_t ub = sBa + S_U + c * ULEN * 2 + PADU * 2 + frag;
            {
                const uint32_t tD = tabc + ((g & 1) ? (TD1 + CD + 1) : (TD0 + CD)) * 2 - e2;
                #pragma unroll 1
                for (int rho = 0; rho < 8; rho++) {
                    uint32_t R[5][3];
                    #pragma unroll
                    for (int qq = 0; qq < 5; qq++) {
                        const uint32_t a = tD - 32 * ((qq < 4 || rho < 2) ? rho + 8 * qq : 0);
                        R[qq][0] = lds32(a + 16); R[qq][1] = lds32(a); R[qq][2] = lds32(a - 16);
                    }
                    const uint32_t base = swz(ub - rho * 32);
                    #pragma unroll
                    for (int pi = 0; pi < 2; pi++) {
                        const int Pp = pi ? 7 - ps : ps;
                        #pragma unroll
                        for (int i = 0; i < 3; i++) {
                            const int jp = Pp - 2 + i;
                            if (pi == 0 && (jp < -1 || (jp == -1 && rho > 0))) continue;
                            uint32_t b[4];
                            ldsm4(b, base + jp * 512);
                            #pragma unroll
                            for (int hh = 0; hh < 2; hh++) {
                                #pragma unroll
                                for (int tt = 0; tt < 2; tt++) {
                                    const int qq = 4 - 2 * i + tt - hh;
                                    if (qq >= 0 && qq < 4) mma_bf16(acc[pi][tt], R[qq][1], R[qq][2], R[qq][0], R[qq][1], b[2 * hh], b[2 * hh + 1]);
                                }
                            }
                            if (i == 0 && rho < 2) {
                                mma_bf16(acc[pi][0], R[4][1], R[4][2], R[4][0], R[4][1], b[0], b[1]);
                                mma_bf16(acc[pi][1], R[4][1], R[4][2], R[4][0], R[4][1], b[2], b[3]);
                            }
                        }
                    }
                }
            }
            {
                const uint32_t tE = tabc + ((g & 1) ? (TE1 + CE + 1) : (TE0 + CE)) * 2 - e2;
                uint32_t R[5];
                #pragma unroll
                for (int i = 0; i < 5; i++) R[i] = lds32(tE - 16 * (127 + i));
                #pragma unroll
                for (int kk = 0; kk < 2; kk++) {
                    uint32_t b[4];
                    ldsm4(b, swz(ub - kk * 32) + (3 - ps) * 512);
                    mma_bf16(acc[1][0], R[2 * kk + 1], R[2 * kk + 2], R[2 * kk], R[2 * kk + 1], b[0], b[1]);
                    mma_bf16(acc[1][1], R[2 * kk + 1], R[2 * kk + 2], R[2 * kk], R[2 * kk + 1], b[2], b[3]);
                }
            }
            {
                const uint32_t t2 = tabc + (T2B + ((g & 1) ? (T2C + C2 + 1) : C2)) * 2 - e2;
                #pragma unroll 1
                for (int s = 0; s < 4; s++) {
                    const uint32_t sig = swz(sBa + ((s & 1) ? S_W3 : S_W5) + c * W2LEN * 2 + WPAD * 2 + frag - ((s == 0) ? 32 : (s == 1) ? 0 : 16));
                    uint32_t R[7];
                    #pragma unroll
                    for (int i = 0; i < 7; i++) R[i] = lds32(t2 + s * (T2S * 2) - 16 * (3 + i));
                    #pragma unroll
                    for (int pi = 0; pi < 2; pi++) {
                        const int Pp = pi ? 7 - ps : ps;
                        #pragma unroll
                        for (int be = 2; be <= 4; be++) {
                            if (pi == 0 && Pp - be < 0) continue;
                            uint32_t a[4];
                            ldsm4t(a, sig + (Pp - be) * 512);
                            mma_bf16(acc[pi][0], a[0], a[1], a[2], a[3], R[2 * be - 3], R[2 * be - 4]);
                            mma_bf16(acc[pi][1], a[0], a[1], a[2], a[3], R[2 * be - 2], R[2 * be - 3]);
                        }
                    }
                }
                const uint32_t t3 = tabc + (T3B + ((g & 1) ? (T3C + C3 + 1) : C3)) * 2 - e2;
                #pragma unroll 1
                for (int s = 0; s < 2; s++) {
                    const uint32_t sig = swz(sBa + (s ? S_W7 : S_W9) + c * W3LEN * 2 + WPAD * 2 + frag - (s ? 16 : 32));
                    uint32_t R[9];
                    #pragma unroll
                    for (int i = 0; i < 9; i++) R[i] = lds32(t3 + s * (T3S * 2) - 16 * (7 + i));
                    #pragma unroll
                    for (int be = 4; be <= 7; be++) {
                        if (7 - ps - be < 0) continue;
                        uint32_t a[4];
                        ldsm4t(a, sig + (7 - ps - be) * 512);
                        mma_bf16(acc[1][0], a[0], a[1], a[2], a[3], R[2 * be - 7], R[2 * be - 8]);
                        mma_bf16(acc[1][1], a[0], a[1], a[2], a[3], R[2 * be - 6], R[2 * be - 7]);
                    }
                }
            }
            __nv_bfloat16* ys = (__nv_bfloat16*)(sB + S_Y + c * 4096) + 32 * t + g;
            #pragma unroll
            for (int pi = 0; pi < 2; pi++) {
                #pragma unroll
                for (int tt = 0; tt < 2; tt++) {
                    __nv_bfloat16* y = ys + 128 * (2 * (pi ? 7 - ps : ps) + tt);
                    y[0] = __float2bfloat16_rn(acc[pi][tt][0]);
                    y[16] = __float2bfloat16_rn(acc[pi][tt][1]);
                    y[8] = __float2bfloat16_rn(acc[pi][tt][2]);
                    y[24] = __float2bfloat16_rn(acc[pi][tt][3]);
                }
            }
        }
        bar_arrive(10, 608);
        PROF(7);
        {
            mbar_wait(bars + 8 * B_ST, 0);
            PROF(9); PROFC(8);
            float qm = 0.0f;
            #pragma unroll
            for (int i = 0; i < 16; i++) qm = fmaxf(qm, s_misc[i]);
            const float vm = s_misc[17];
            const bool fast = (qm * s_misc[16] <= 60.0f * 60.0f) && (vm <= 1.0e12f) && (vm >= 1.0e-12f || vm == 0.0f);
            uint8_t* ob = g_oimg + qb * 131072 + hg * 16384 + nh * 8192 + (rowhalf * 8 + wiw * 2) * 128 + g * 16 + 4 * t;
            uint32_t cA = 0xBF00BF00u, cB = 0x00030003u;
            asm volatile("" : "+r"(cA), "+r"(cB));
            #pragma unroll 1
            for (int tile = 0; tile < 2; tile++) {
                uint32_t kLo = (((sb + SM_K) & 0x3FFFF) >> 4) | (8u << 16), vLo = (((sb + SM_V) & 0x3FFFF) >> 4) | (8u << 16), vHi = 2048;
                float o[12], s[32];
                uint32_t p[16], qq[4];
                #pragma unroll
                for (int i = 0; i < 4; i++) { qq[i] = tile ? q[1][i] : q[0][i]; asm volatile("" : "+r"(qq[i])); }
                #pragma unroll
                for (int i = 0; i < 12; i++) o[i] = 0.0f;
                #pragma unroll
                for (int i = 0; i < 32; i++) s[i] = 0.0f;
                fence_regs<12>(o);
                fence_regs<32>(s);
                if (fast) {
                    #pragma unroll 1
                    for (int c = 0; c < SEQ / 256; c++) {
                        if (c <= 4) mbar_wait(bars + 8 * (B_KV + (c < 2 ? c : c < 4 ? 2 : 3)), 0);
                        wg_fence();
                        wg_qk(s, qq, kLo);
                        wg_commit();
                        #pragma unroll
                        for (int u = 0; u < 4; u++) {
                            wg_wait<0>();
                            fence_regs<32>(s);
                            #pragma unroll
                            for (int i = 0; i < 16; i++) {
                                if ((MUFU_MASK >> i) & 1) p[i] = exp_mufu(s[2 * i], s[2 * i + 1]);
                                else p[i] = exp_sw(s[2 * i], s[2 * i + 1], cA, cB);
                            }
                            wg_fence();
                            if (u + 1 < 4) wg_qk(s, qq, kLo + (u + 1) * 128);
                            #pragma unroll
                            for (int kk = 0; kk < 4; kk++) wg_pv(o, p + 4 * kk, vLo + u * 64 + kk * 16, vHi - u * 64);
                            wg_commit();
                        }
                        kLo += 512; vLo += 256; vHi -= 256;
                    }
                    wg_wait<0>();
                } else {
                    float mx0 = -INFINITY, mx1 = -INFINITY;
                    #pragma unroll 1
                    for (int c = 0; c < SEQ / 64; c++) {
                        if (c <= 16) mbar_wait(bars + 8 * (B_KV + (c < 8 ? (c >> 2) : c < 16 ? 2 : 3)), 0);
                        wg_fence();
                        wg_qk(s, qq, kLo);
                        wg_commit();
                        wg_wait<0>();
                        fence_regs<32>(s);
                        fence_regs<12>(o);
                        float m0 = mx0, m1 = mx1;
                        #pragma unroll
                        for (int j = 0; j < 8; j++) {
                            m0 = fmaxf(m0, fmaxf(s[4 * j], s[4 * j + 1]));
                            m1 = fmaxf(m1, fmaxf(s[4 * j + 2], s[4 * j + 3]));
                        }
                        m0 = fmaxf(m0, __shfl_xor_sync(0xffffffffu, m0, 1)); m0 = fmaxf(m0, __shfl_xor_sync(0xffffffffu, m0, 2));
                        m1 = fmaxf(m1, __shfl_xor_sync(0xffffffffu, m1, 1)); m1 = fmaxf(m1, __shfl_xor_sync(0xffffffffu, m1, 2));
                        const float c0 = ex2f(mx0 - m0), c1 = ex2f(mx1 - m1);
                        mx0 = m0; mx1 = m1;
                        #pragma unroll
                        for (int j = 0; j < 3; j++) { o[4 * j] *= c0; o[4 * j + 1] *= c0; o[4 * j + 2] *= c1; o[4 * j + 3] *= c1; }
                        #pragma unroll
                        for (int j = 0; j < 8; j++) {
                            p[2 * j] = exp_mufu(s[4 * j] - m0, s[4 * j + 1] - m0);
                            p[2 * j + 1] = exp_mufu(s[4 * j + 2] - m1, s[4 * j + 3] - m1);
                        }
                        wg_fence();
                        #pragma unroll
                        for (int kk = 0; kk < 4; kk++) wg_pv(o, p + 4 * kk, vLo + kk * 16, vHi);
                        wg_commit();
                        wg_wait<0>();
                        kLo += 128; vLo += 64; vHi -= 64;
                    }
                }
                fence_regs<12>(o);
                if (tile == 0) PROFC(3);
                const float i0 = 1.0f / o[4], i1 = 1.0f / o[6];
                uint8_t* b = ob + tile * 4096;
                *(uint32_t*)(b) = pack_bf16(o[0] * i0, o[1] * i0);
                *(uint32_t*)(b + 128) = pack_bf16(o[2] * i1, o[3] * i1);
                *(uint32_t*)(b + 2048) = pack_bf16(o[8] * i0, o[9] * i0);
                *(uint32_t*)(b + 2048 + 128) = pack_bf16(o[10] * i1, o[11] * i1);
            }
        }
        PROF(10); PROFC(9);
        bar_arrive(12, 544);

        {
            float acc[16];
            #pragma unroll
            for (int i = 0; i < 16; i++) acc[i] = 0.0f;
            fence_regs<16>(acc);
            const uint64_t dA = make_desc(sb + SM_A + rowhalf * 1024, 2048, 128, 0);
            const uint64_t dB = make_desc(sb + SM_B + nh * 64, 16, 1024, 1);
            mbar_wait(bars + 8 * B_WO, 0);
            #pragma unroll 1
            for (int i = 0; i < 8; i++) {
                const int src = (hg + i) & 7;
                mbar_wait(bars + 8 * (B_O + src), 0);
                wg_fence();
                #pragma unroll
                for (int kk = 0; kk < 4; kk++) wg_ss32(acc, dA + src * 1024 + kk * 256, dB + (src * 4 + kk) * 128);
                wg_commit();
            }
            wg_wait<0>();
            fence_regs<16>(acc);
            PROF(12);
            const int row = qb * 128 + rowhalf * 64 + wiw * 16 + g;
            uint32_t* o32 = (uint32_t*)(P.out + (size_t)row * 1024 + hg * 64 + nh * 32 + 2 * t);
            #pragma unroll
            for (int j = 0; j < 4; j++) {
                o32[4 * j] = pack_bf16(acc[4 * j], acc[4 * j + 1]);
                o32[4 * j + 8 * 512] = pack_bf16(acc[4 * j + 2], acc[4 * j + 3]);
            }
        }
        PROF(13);
    }
}

typedef CUresult (*EncodeFn)(CUtensorMap*, CUtensorMapDataType, cuuint32_t, void*, const cuuint64_t*, const cuuint64_t*,
                             const cuuint32_t*, const cuuint32_t*, CUtensorMapInterleave, CUtensorMapSwizzle,
                             CUtensorMapL2promotion, CUtensorMapFloatOOBfill);

void make_map(EncodeFn fn, CUtensorMap* m, const void* ptr, uint64_t inner, uint64_t outer, uint32_t box_in, uint32_t box_out, CUtensorMapSwizzle swz) {
    cuuint64_t dims[2] = {inner, outer};
    cuuint64_t strides[1] = {inner * 2};
    cuuint32_t box[2] = {box_in, box_out};
    cuuint32_t es[2] = {1, 1};
    fn(m, CU_TENSOR_MAP_DATA_TYPE_BFLOAT16, 2, const_cast<void*>(ptr), dims, strides, box, es, CU_TENSOR_MAP_INTERLEAVE_NONE, swz,
       CU_TENSOR_MAP_L2_PROMOTION_L2_128B, CU_TENSOR_MAP_FLOAT_OOB_FILL_NONE);
}

}

extern "C" void kernel_launch(void* const* d_in, const int* in_sizes, int n_in, void* d_out, int out_size) {
    (void)in_sizes; (void)n_in; (void)out_size;
    static EncodeFn fn = nullptr;
    if (!fn) {
        void* p = nullptr;
        cudaDriverEntryPointQueryResult qr;
        cudaGetDriverEntryPoint("cuTensorMapEncodeTiled", &p, cudaEnableDefault, &qr);
        fn = (EncodeFn)p;
        cudaFuncSetAttribute(fused_kernel, cudaFuncAttributeMaxDynamicSharedMemorySize, SM_ALLOC);
    }
    CUtensorMap tx, twq, two, twk, twv, tu;
    {
        cuuint64_t dims[3] = {64, 2048, 8};
        cuuint64_t strides[2] = {1024, 128};
        cuuint32_t box[3] = {64, 128, 4};
        cuuint32_t es[3] = {1, 1, 1};
        fn(&tx, CU_TENSOR_MAP_DATA_TYPE_BFLOAT16, 3, d_in[0], dims, strides, box, es, CU_TENSOR_MAP_INTERLEAVE_NONE, CU_TENSOR_MAP_SWIZZLE_128B,
           CU_TENSOR_MAP_L2_PROMOTION_L2_128B, CU_TENSOR_MAP_FLOAT_OOB_FILL_NONE);
    }
    make_map(fn, &tu, d_in[5], 512, 2048, 8, 256, CU_TENSOR_MAP_SWIZZLE_NONE);
    make_map(fn, &twq, d_in[1], 512, 512, 64, 256, CU_TENSOR_MAP_SWIZZLE_128B);
    make_map(fn, &twk, d_in[2], 16, 512, 8, 256, CU_TENSOR_MAP_SWIZZLE_NONE);
    make_map(fn, &twv, d_in[3], 16, 512, 8, 256, CU_TENSOR_MAP_SWIZZLE_NONE);
    make_map(fn, &two, d_in[4], 512, 512, 64, 256, CU_TENSOR_MAP_SWIZZLE_128B);
    Params P;
    P.u = (const __nv_bfloat16*)d_in[5];
    P.lar = (const __nv_bfloat16*)d_in[6];
    P.aim = (const __nv_bfloat16*)d_in[7];
    P.cre = (const __nv_bfloat16*)d_in[8];
    P.cim = (const __nv_bfloat16*)d_in[9];
    P.logdt = (const __nv_bfloat16*)d_in[10];
    P.dskip = (const __nv_bfloat16*)d_in[11];
    P.out = (__nv_bfloat16*)d_out;
    fused_kernel<<<NCTA, NTHR, SM_ALLOC>>>(tx, twq, two, twk, twv, tu, P);
}
```

```cpp
#include <cuda_runtime.h>
#include <cuda_bf16.h>
#include <cuda_fp16.h>
#include <cuda.h>
#include <stdint.h>

namespace {

constexpr int SEQ = 2048;
constexpr int NCTA = 128, NTHR = 640;

constexpr int SM_A = 0;
constexpr int SM_WQ = 65536;
constexpr int SM_SLAB = SM_WQ + 32768;
constexpr int SM_K = 0, SM_V = 65536;
constexpr int SM_B = 132096;
constexpr int SM_WKV = SM_B + 65536;

constexpr int PADU = 288, ULEN = PADU + 2048;
constexpr int WPAD = 16, W2LEN = WPAD + 1536, W3LEN = WPAD + 1024;
constexpr int TABN = 2240;
constexpr int S_U = 0;
constexpr int S_W3 = S_U + 4 * ULEN * 2;
constexpr int S_W5 = S_W3 + 4 * W2LEN * 2;
constexpr int S_W7 = S_W5 + 4 * W2LEN * 2;
constexpr int S_W9 = S_W7 + 4 * W3LEN * 2;
constexpr int S_TAB = S_W9 + 4 * W3LEN * 2;
constexpr int S_KC = 214016 - SM_B;
constexpr int S_Y = S_KC;
constexpr int SM_BAR = SM_B + S_KC + 16384;
constexpr int SM_TOTAL = SM_BAR + 1024;
constexpr int SM_ALLOC = SM_TOTAL + 1024;
static_assert(SM_V + 65536 + 1024 <= SM_B && SM_ALLOC <= 232448 && S_TAB + 4 * TABN * 2 <= S_KC && SM_WKV + 16384 <= SM_B + S_KC, "smem map");

constexpr int TD0 = 0, TD1 = 560, CD = 544;
constexpr int TE0 = 1120, TE1 = 1168, CE = 1056;
constexpr int T2B = 1216, T2S = 160, T2C = 80, C2 = 80;
constexpr int T3B = 1856, T3S = 192, T3C = 96, C3 = 144;

constexpr int rne8(int t) {
    if (t < 256) return t;
    int sh = 0;
    while ((t >> sh) >= 256) sh++;
    int q = t >> sh, rem = t & ((1 << sh) - 1), half = 1 << (sh - 1);
    if (rem > half || (rem == half && (q & 1))) q++;
    return q << sh;
}
constexpr int kcidx(int p) {
    if (p < 256) return (p >> 3) * 24 + (p & 7);
    if (p < 512) return ((p - 256) >> 3) * 24 + 8 + (((p - 256) & 7) >> 1);
    if (p < 1024) { int q = p - 512, hi = q >> 8, rem = q & 255; return (rem >> 3) * 24 + 12 + 2 * hi + ((rem & 7) >> 2); }
    if (p < 2048) { int q = p - 1024; return ((q & 255) >> 3) * 24 + 16 + (q >> 8); }
    return 20;
}
constexpr int KC_ZERO = 23;
constexpr int tab_dense(int t) { return (t >= 0 && t <= 514) ? kcidx(rne8(t)) : KC_ZERO; }
constexpr int tab_extra(int t) { return (t >= 1027 && t <= 1028) ? kcidx(1024) : KC_ZERO; }
constexpr int tab_2(int s, int lag) { return (lag >= 32 && lag <= 63) ? kcidx(s == 0 ? 16 * (lag + 1) : 16 * lag + 4 * s) : KC_ZERO; }
constexpr int tab_3(int s, int lag) { return (lag >= 64 && lag <= 127) ? kcidx(s == 0 ? 16 * (lag + 1) : 16 * lag + 8) : KC_ZERO; }
struct TabMap {
    uint16_t v[TABN];
    constexpr TabMap() : v{} {
        for (int i = 0; i < 560; i++) { v[TD0 + i] = tab_dense(CD - i); v[TD1 + i] = tab_dense(CD + 1 - i); }
        for (int i = 0; i < 48; i++) { v[TE0 + i] = tab_extra(CE - i); v[TE1 + i] = tab_extra(CE + 1 - i); }
        for (int s = 0; s < 4; s++)
            for (int i = 0; i < T2C; i++) { v[T2B + s * T2S + i] = tab_2(s, C2 - i); v[T2B + s * T2S + T2C + i] = tab_2(s, C2 + 1 - i); }
        for (int s = 0; s < 2; s++)
            for (int i = 0; i < T3C; i++) { v[T3B + s * T3S + i] = tab_3(s, C3 - i); v[T3B + s * T3S + T3C + i] = tab_3(s, C3 + 1 - i); }
    }
};
__device__ const __align__(16) TabMap g_tabmap = TabMap();

__device__ __align__(1024) uint8_t g_kimg[65536];
__device__ __align__(1024) uint8_t g_vimg[65536 + 1024];
__device__ __align__(1024) uint8_t g_oimg[16 * 131072];
__device__ unsigned long long g_flag_kv[64];
__device__ unsigned g_flag_o[128];
__device__ unsigned g_epoch;
__device__ unsigned g_done;

#define PROF(i) do {} while (0)
#define PROF2(i) do {} while (0)
#define PROFC(i) do {} while (0)
#define PROF3(i) do {} while (0)

__device__ __forceinline__ uint32_t smem_u32(const void* p) { return (uint32_t)__cvta_generic_to_shared(p); }
__device__ __forceinline__ void mbar_init(uint32_t bar, uint32_t cnt) { asm volatile("mbarrier.init.shared::cta.b64 [%0], %1;" :: "r"(bar), "r"(cnt) : "memory"); }
__device__ __forceinline__ void mbar_expect_tx(uint32_t bar, uint32_t bytes) {
    asm volatile("mbarrier.arrive.expect_tx.shared::cta.b64 _, [%0], %1;" :: "r"(bar), "r"(bytes) : "memory"); }
__device__ __forceinline__ void mbar_wait(uint32_t bar, uint32_t parity) {
    uint32_t ok = 0;
    for (int it = 0; it < (1 << 22) && !ok; it++) {
        asm volatile("{ .reg .pred p; mbarrier.try_wait.parity.shared::cta.b64 p, [%1], %2; selp.u32 %0, 1, 0, p; }"
                     : "=r"(ok) : "r"(bar), "r"(parity) : "memory");
    }
}
__device__ __forceinline__ void tma_2d(uint32_t dst, const CUtensorMap* map, int c0, int c1, uint32_t bar) {
    asm volatile("cp.async.bulk.tensor.2d.shared::cluster.global.mbarrier::complete_tx::bytes [%0], [%1, {%3, %4}], [%2];"
                 :: "r"(dst), "l"((uint64_t)map), "r"(bar), "r"(c0), "r"(c1) : "memory");
}
__device__ __forceinline__ void tma_2d_mc(uint32_t dst, const CUtensorMap* map, int c0, int c1, uint32_t bar) {
    asm volatile("cp.async.bulk.tensor.2d.shared::cluster.global.mbarrier::complete_tx::bytes.multicast::cluster [%0], [%1, {%3, %4}], [%2], %5;"
                 :: "r"(dst), "l"((uint64_t)map), "r"(bar), "r"(c0), "r"(c1), "h"((uint16_t)3) : "memory");
}
__device__ __forceinline__ void bulk_g2s_mc(uint32_t dst, const void* src, uint32_t bytes, uint32_t bar) {
    asm volatile("cp.async.bulk.shared::cluster.global.mbarrier::complete_tx::bytes.multicast::cluster [%0], [%1], %2, [%3], %4;"
                 :: "r"(dst), "l"((uint64_t)src), "r"(bytes), "r"(bar), "h"((uint16_t)3) : "memory");
}
__device__ __forceinline__ void pair_sync(uint32_t bar, uint32_t peer) {
    uint32_t ra;
    asm volatile("mapa.shared::cluster.u32 %0, %1, %2;" : "=r"(ra) : "r"(bar), "r"(peer));
    asm volatile("mbarrier.arrive.shared::cluster.b64 _, [%0];" :: "r"(ra) : "memory");
    asm volatile("mbarrier.arrive.shared::cta.b64 _, [%0];" :: "r"(bar) : "memory");
    uint32_t ok = 0;
    for (int it = 0; it < (1 << 22) && !ok; it++) {
        asm volatile("{ .reg .pred p; mbarrier.try_wait.parity.shared::cta.b64 p, [%1], 0; selp.u32 %0, 1, 0, p; }"
                     : "=r"(ok) : "r"(bar) : "memory");
    }
}
__device__ __forceinline__ void fence_async_all() { asm volatile("fence.proxy.async.global;" ::: "memory"); }
__device__ __forceinline__ void fence_async_smem() { asm volatile("fence.proxy.async.shared::cta;" ::: "memory"); }
__device__ __forceinline__ unsigned ld_acquire(const unsigned* p) {
    unsigned v; asm volatile("ld.acquire.gpu.global.u32 %0, [%1];" : "=r"(v) : "l"(p) : "memory"); return v; }
__device__ __forceinline__ void st_release(unsigned* p, unsigned v) { asm volatile("st.release.gpu.global.u32 [%0], %1;" :: "l"(p), "r"(v) : "memory"); }
__device__ __forceinline__ void wait_flag(const unsigned* p, unsigned epoch) {
    for (int it = 0; it < (1 << 22); it++) { if (ld_acquire(p) == epoch) break; }
}
__device__ __forceinline__ unsigned long long ld_acquire64(const unsigned long long* p) {
    unsigned long long v; asm volatile("ld.acquire.gpu.global.u64 %0, [%1];" : "=l"(v) : "l"(p) : "memory"); return v; }
__device__ __forceinline__ void st_release64(unsigned long long* p, unsigned long long v) { asm volatile("st.release.gpu.global.u64 [%0], %1;" :: "l"(p), "l"(v) : "memory"); }
__device__ __forceinline__ float wait_flag64(const unsigned long long* p, unsigned epoch) {
    unsigned long long v = 0;
    for (int it = 0; it < (1 << 22); it++) { v = ld_acquire64(p); if ((unsigned)(v >> 32) == epoch) break; }
    return __uint_as_float((unsigned)v);
}
__device__ __forceinline__ void tma_3d_mc(uint32_t dst, const CUtensorMap* map, int c0, int c1, int c2, uint32_t bar) {
    asm volatile("cp.async.bulk.tensor.3d.shared::cluster.global.mbarrier::complete_tx::bytes.multicast::cluster [%0], [%1, {%3, %4, %5}], [%2], %6;"
                 :: "r"(dst), "l"((uint64_t)map), "r"(bar), "r"(c0), "r"(c1), "r"(c2), "h"((uint16_t)3) : "memory");
}
__device__ __forceinline__ void bar_sync(int id, int n) { asm volatile("bar.sync %0, %1;" :: "r"(id), "r"(n) : "memory"); }
__device__ __forceinline__ void bar_arrive(int id, int n) { asm volatile("bar.arrive %0, %1;" :: "r"(id), "r"(n) : "memory"); }
__device__ __forceinline__ void mbar_arrive(uint32_t bar) { asm volatile("mbarrier.arrive.shared::cta.b64 _, [%0];" :: "r"(bar) : "memory"); }

__device__ __forceinline__ uint64_t make_desc(uint32_t saddr, uint32_t lbo, uint32_t sbo, uint32_t swz) {
    uint64_t d = 0;
    d |= (uint64_t)((saddr & 0x3FFFF) >> 4);
    d |= (uint64_t)((lbo >> 4) & 0x3FFF) << 16;
    d |= (uint64_t)((sbo >> 4) & 0x3FFF) << 32;
    d |= (uint64_t)swz << 62;
    return d;
}
__device__ __forceinline__ void wg_fence() { asm volatile("wgmma.fence.sync.aligned;" ::: "memory"); }
__device__ __forceinline__ void wg_commit() { asm volatile("wgmma.commit_group.sync.aligned;" ::: "memory"); }
template<int N> __device__ __forceinline__ void wg_wait() { asm volatile("wgmma.wait_group.sync.aligned %0;" :: "n"(N) : "memory"); }
#define A4(d, o) "+f"(d[o + 0]), "+f"(d[o + 1]), "+f"(d[o + 2]), "+f"(d[o + 3])
#define A16(d, o) A4(d, o), A4(d, o + 4), A4(d, o + 8), A4(d, o + 12)

__device__ __forceinline__ void wg_pv(float* d, const uint32_t* a, uint32_t lo, uint32_t hi) {
    asm volatile("{ .reg .b64 dd; mov.b64 dd, {%16, %17};\n"
                 "wgmma.mma_async.sync.aligned.m64n24k16.f32.bf16.bf16 {%0,%1,%2,%3,%4,%5,%6,%7,%8,%9,%10,%11}, {%12,%13,%14,%15}, dd, 1, 1, 1, 1; }"
                 : A4(d, 0), A4(d, 4), A4(d, 8) : "r"(a[0]), "r"(a[1]), "r"(a[2]), "r"(a[3]), "r"(lo), "r"(hi));
}
__device__ __forceinline__ void wg_qk(float* d, const uint32_t* a, uint32_t lo) {
    asm volatile("{ .reg .b64 dd; mov.b64 dd, {%36, %37};\n"
                 "wgmma.mma_async.sync.aligned.m64n64k16.f32.bf16.bf16 {%0,%1,%2,%3,%4,%5,%6,%7,%8,%9,%10,%11,%12,%13,%14,%15,%16,%17,%18,%19,%20,%21,%22,%23,%24,%25,%26,%27,%28,%29,%30,%31}, {%32,%33,%34,%35}, dd, 0, 1, 1, 0; }"
                 : A16(d, 0), A16(d, 16) : "r"(a[0]), "r"(a[1]), "r"(a[2]), "r"(a[3]), "r"(lo), "r"(16));
}
__device__ __forceinline__ void wg_ss32(float* d, uint64_t da, uint64_t db) {
    asm volatile("wgmma.mma_async.sync.aligned.m64n32k16.f32.bf16.bf16 {%0,%1,%2,%3,%4,%5,%6,%7,%8,%9,%10,%11,%12,%13,%14,%15}, %16, %17, 1, 1, 1, 0, 1;"
                 : A16(d, 0) : "l"(da), "l"(db));
}
__device__ __forceinline__ void wg_ss16(float* d, uint64_t da, uint64_t db) {
    asm volatile("wgmma.mma_async.sync.aligned.m64n16k16.f32.bf16.bf16 {%0,%1,%2,%3,%4,%5,%6,%7}, %8, %9, 1, 1, 1, 0, 1;"
                 : A4(d, 0), A4(d, 4) : "l"(da), "l"(db));
}
template<int N> __device__ __forceinline__ void fence_regs(float* r) {
    #pragma unroll
    for (int i = 0; i < N; i++) asm volatile("" : "+f"(r[i]) :: "memory");
}
__device__ __forceinline__ void mma_bf16(float* d, uint32_t a0, uint32_t a1, uint32_t a2, uint32_t a3, uint32_t b0, uint32_t b1) {
    asm volatile("mma.sync.aligned.m16n8k16.row.col.f32.bf16.bf16.f32 {%0,%1,%2,%3}, {%4,%5,%6,%7}, {%8,%9}, {%0,%1,%2,%3};"
                 : "+f"(d[0]), "+f"(d[1]), "+f"(d[2]), "+f"(d[3]) : "r"(a0), "r"(a1), "r"(a2), "r"(a3), "r"(b0), "r"(b1));
}
__device__ __forceinline__ void mma_f16(float* d, const uint32_t* a, uint32_t b0, uint32_t b1) {
    asm volatile("mma.sync.aligned.m16n8k16.row.col.f32.f16.f16.f32 {%0,%1,%2,%3}, {%4,%5,%6,%7}, {%8,%9}, {%0,%1,%2,%3};"
                 : "+f"(d[0]), "+f"(d[1]), "+f"(d[2]), "+f"(d[3]) : "r"(a[0]), "r"(a[1]), "r"(a[2]), "r"(a[3]), "r"(b0), "r"(b1));
}
__device__ __forceinline__ void ldsm4(uint32_t* r, uint32_t addr) {
    asm volatile("ldmatrix.sync.aligned.m8n8.x4.shared.b16 {%0,%1,%2,%3}, [%4];" : "=r"(r[0]), "=r"(r[1]), "=r"(r[2]), "=r"(r[3]) : "r"(addr) : "memory");
}
__device__ __forceinline__ void ldsm4t(uint32_t* r, uint32_t addr) {
    asm volatile("ldmatrix.sync.aligned.m8n8.x4.trans.shared.b16 {%0,%1,%2,%3}, [%4];" : "=r"(r[0]), "=r"(r[1]), "=r"(r[2]), "=r"(r[3]) : "r"(addr) : "memory");
}
__device__ __forceinline__ uint32_t lds32(uint32_t addr) { uint32_t v; asm volatile("ld.shared.u32 %0, [%1];" : "=r"(v) : "r"(addr) : "memory"); return v; }
__device__ __forceinline__ void mma_bf16_p(float* d, uint32_t a0, uint32_t a1, uint32_t a2, uint32_t a3, uint32_t b0, uint32_t b1) {
    asm("mma.sync.aligned.m16n8k16.row.col.f32.bf16.bf16.f32 {%0,%1,%2,%3}, {%4,%5,%6,%7}, {%8,%9}, {%0,%1,%2,%3};"
        : "+f"(d[0]), "+f"(d[1]), "+f"(d[2]), "+f"(d[3]) : "r"(a0), "r"(a1), "r"(a2), "r"(a3), "r"(b0), "r"(b1));
}
__device__ __forceinline__ void ldsm4_p(uint32_t* r, uint32_t addr) {
    asm("ldmatrix.sync.aligned.m8n8.x4.shared.b16 {%0,%1,%2,%3}, [%4];" : "=r"(r[0]), "=r"(r[1]), "=r"(r[2]), "=r"(r[3]) : "r"(addr));
}
__device__ __forceinline__ void ldsm4t_p(uint32_t* r, uint32_t addr) {
    asm("ldmatrix.sync.aligned.m8n8.x4.trans.shared.b16 {%0,%1,%2,%3}, [%4];" : "=r"(r[0]), "=r"(r[1]), "=r"(r[2]), "=r"(r[3]) : "r"(addr));
}
__device__ __forceinline__ uint32_t lds32_p(uint32_t addr) { uint32_t v; asm("ld.shared.u32 %0, [%1];" : "=r"(v) : "r"(addr)); return v; }
__device__ __forceinline__ uint32_t swz(uint32_t a) { return a ^ ((a >> 3) & 16u); }
__device__ __forceinline__ void sts32(uint32_t addr, uint32_t v) { asm volatile("st.shared.u32 [%0], %1;" :: "r"(addr), "r"(v) : "memory"); }
__device__ __forceinline__ void sts128(uint32_t addr, uint4 v) { asm volatile("st.shared.v4.u32 [%0], {%1,%2,%3,%4};" :: "r"(addr), "r"(v.x), "r"(v.y), "r"(v.z), "r"(v.w) : "memory"); }
__device__ __forceinline__ uint4 lds128(uint32_t addr) { uint4 v; asm volatile("ld.shared.v4.u32 {%0,%1,%2,%3}, [%4];" : "=r"(v.x), "=r"(v.y), "=r"(v.z), "=r"(v.w) : "r"(addr) : "memory"); return v; }
__device__ __forceinline__ float ex2f(float x) { float r; asm("ex2.approx.ftz.f32 %0, %1;" : "=f"(r) : "f"(x)); return r; }
__device__ __forceinline__ uint32_t pack_bf16(float lo, float hi) { uint32_t r; asm("cvt.rn.bf16x2.f32 %0, %1, %2;" : "=r"(r) : "f"(hi), "f"(lo)); return r; }
__device__ __forceinline__ uint32_t pack_f16(float lo, float hi) { uint32_t r; asm("cvt.rn.f16x2.f32 %0, %1, %2;" : "=r"(r) : "f"(hi), "f"(lo)); return r; }
__device__ __forceinline__ float bf_lo(uint32_t v) { return __uint_as_float(v << 16); }
__device__ __forceinline__ float bf_hi(uint32_t v) { return __uint_as_float(v & 0xFFFF0000u); }
__device__ __forceinline__ float bf_round(float x) { return __bfloat162float(__float2bfloat16_rn(x)); }

__device__ __forceinline__ uint32_t exp_mufu(float x0, float x1) { return pack_bf16(ex2f(x0), ex2f(x1)); }
#define SW_MAGIC (256.0f + 127.0f - 0.598938f)
__device__ __forceinline__ uint32_t exp_sw(float x0, float x1, uint32_t cA, uint32_t cB) {
    float t0 = x0 + SW_MAGIC, t1 = x1 + SW_MAGIC;
    uint32_t L, mh, ec, r;
    asm("prmt.b32 %0, %1, %2, 0x6521;" : "=r"(L) : "r"(__float_as_uint(t0)), "r"(__float_as_uint(t1)));
    asm("lop3.b32 %0, %1, 0x007F007F, %2, 0xEA;" : "=r"(mh) : "r"(L), "r"(cA));
    asm("lop3.b32 %0, %1, 0x7F807F80, %2, 0xEA;" : "=r"(ec) : "r"(L), "r"(cB));
    asm("fma.rn.bf16x2 %0, %1, %2, %3;" : "=r"(r) : "r"(L), "r"(mh), "r"(ec));
    return r;
}
constexpr uint32_t MUFU_MASK = 0x4949;

struct cf { float x, y; };
__device__ __forceinline__ cf cmul(cf a, cf b) { cf r; r.x = a.x * b.x - a.y * b.y; r.y = a.x * b.y + a.y * b.x; return r; }
__device__ __forceinline__ cf cexp_p(float a2, float b, float p) {
    float e = ex2f(a2 * p);
    float ph = b * p;
    ph -= (ph + 12582912.0f) - 12582912.0f;
    float ang = ph * 6.283185307f;
    cf r; r.x = e * __cosf(ang); r.y = e * __sinf(ang);
    return r;
}
__device__ __forceinline__ uint32_t h2_cmul(uint32_t w, uint32_t wsw, uint32_t e) {
    __half2 hw = *(__half2*)&w, hs = *(__half2*)&wsw, he = *(__half2*)&e;
    __half2 r = __hfma2(hs, __high2half2(he), __hmul2(hw, __low2half2(he)));
    return *(uint32_t*)&r;
}

template<bool B> struct BoolC { static constexpr bool value = B; };
struct Params {
    const __nv_bfloat16 *u, *lar, *aim, *cre, *cim, *logdt, *dskip;
    __nv_bfloat16* out;
};

constexpr int B_O = 0, B_KV = 8, B_WO = 12, B_WQ2 = 13, B_ST = 14, B_H = 15, B_X = 17, B_U = 19, B_WQ = 20;

__device__ __forceinline__ void helper_role(const Params& P, uint8_t* sp, uint32_t sb, unsigned epoch) {
    const uint32_t sBa = sb + SM_B;
    const int tid = threadIdx.x - 544;
    const int d0 = blockIdx.x * 4;
    uint8_t* sB = sp + SM_B;
    const uint2 dsk = __ldg((const uint2*)(P.dskip + d0));
    asm volatile("barrier.cluster.wait.aligned;" ::: "memory");
    {
        const int hg = blockIdx.x & 7;
        if (hg < 4 && tid < 32) {
            bar_sync(3, 160);
            if (tid == 0) {
                const float* s_misc = (const float*)(sp + SM_BAR + 256);
                const float st = fmaxf(fmaxf(s_misc[20], s_misc[21]), fmaxf(s_misc[22], s_misc[23]));
                st_release64(&g_flag_kv[((blockIdx.x >> 3) * 2 + (hg & 1)) * 2 + (hg >> 1)], ((unsigned long long)epoch << 32) | __float_as_uint(st));
            }
            __syncwarp();
        }
    }
    PROF2(2);
    bar_sync(10, 608);
    {
        uint32_t dd[4] = {__byte_perm(dsk.x, 0, 0x1010), __byte_perm(dsk.x, 0, 0x3232), __byte_perm(dsk.y, 0, 0x1010), __byte_perm(dsk.y, 0, 0x3232)};
        #pragma unroll 2
        for (int pi = tid; pi < 1024; pi += 96) {
            const int l = 2 * pi;
            uint32_t r[4];
            #pragma unroll
            for (int cc = 0; cc < 4; cc++) {
                const uint32_t y2 = *(const uint32_t*)(sB + S_Y + cc * 4096 + l * 2);
                const uint32_t u2 = lds32(swz(sBa + S_U + cc * ULEN * 2 + (PADU + l) * 2));
                __nv_bfloat162 pr = __hmul2(*(const __nv_bfloat162*)&u2, *(const __nv_bfloat162*)&dd[cc]);
                __nv_bfloat162 sm = __hadd2(*(const __nv_bfloat162*)&y2, pr);
                r[cc] = *(uint32_t*)&sm;
            }
            *(uint2*)(P.out + (size_t)l * 1024 + 512 + d0) = make_uint2(__byte_perm(r[0], r[1], 0x5410), __byte_perm(r[2], r[3], 0x5410));
            *(uint2*)(P.out + (size_t)(l + 1) * 1024 + 512 + d0) = make_uint2(__byte_perm(r[0], r[1], 0x7632), __byte_perm(r[2], r[3], 0x7632));
        }
    }
    bar_arrive(11, 128);
    PROF2(4);
}

__global__ void __cluster_dims__(2, 1, 1) __launch_bounds__(NTHR, 1)
fused_kernel(const __grid_constant__ CUtensorMap tm_x, const __grid_constant__ CUtensorMap tm_wq,
             const __grid_constant__ CUtensorMap tm_wo, const __grid_constant__ CUtensorMap tm_wk,
             const __grid_constant__ CUtensorMap tm_wv, const __grid_constant__ CUtensorMap tm_u, const Params P) {
    extern __shared__ uint8_t smem_raw[];
    const uint32_t sb = (smem_u32(smem_raw) + 1023u) & ~1023u;
    uint8_t* sp = smem_raw + (sb - smem_u32(smem_raw));

    const int tid = threadIdx.x, warp = tid >> 5, lane = tid & 31, wg = tid >> 7, wiw = warp & 3;
    const int g = lane >> 2, t = lane & 3;
    const int qb = blockIdx.x >> 3, hg = blockIdx.x & 7;
    const uint32_t rank = blockIdx.x & 1;
    const int rowhalf = wg & 1, nh = wg >> 1;
    const bool kv_cta = hg < 4;
    const int kv_sel = hg >> 1;
    const bool kv_wg = kv_cta && (wg == (hg & 1));

    const uint32_t bars = sb + SM_BAR;
    float* s_misc = (float*)(sp + SM_BAR + 256);
    const CUtensorMap* tm_kv = kv_sel ? &tm_wv : &tm_wk;

    PROF(0);
    unsigned short p_lar = 0, p_aim = 0, p_cre = 0, p_cim = 0, p_ldt = 0;
    if (wg < 4) {
        const int n = (blockIdx.x * 4 + wg) * 128 + (tid & 127);
        p_lar = __ldg((const unsigned short*)P.lar + n);
        p_aim = __ldg((const unsigned short*)P.aim + n);
        p_cre = __ldg((const unsigned short*)P.cre + n);
        p_cim = __ldg((const unsigned short*)P.cim + n);
        p_ldt = __ldg((const unsigned short*)P.logdt + blockIdx.x * 4 + wg);
    } else if (warp == 16) {
        PROF3(5);
        if (lane == 0) {
            asm volatile("prefetch.tensormap [%0];" :: "l"((uint64_t)&tm_x) : "memory");
            asm volatile("prefetch.tensormap [%0];" :: "l"((uint64_t)tm_kv) : "memory");
            asm volatile("prefetch.tensormap [%0];" :: "l"((uint64_t)&tm_wq) : "memory");
            asm volatile("prefetch.tensormap [%0];" :: "l"((uint64_t)&tm_u) : "memory");
            mbar_init(bars + 8 * B_X, 1);
            mbar_init(bars + 8 * B_X + 8, 1);
            mbar_init(bars + 8 * B_U, 1);
            asm volatile("fence.mbarrier_init.release.cluster;" ::: "memory");
            mbar_expect_tx(bars + 8 * B_X, 65536u + (kv_cta ? 8192u : 0u));
            mbar_expect_tx(bars + 8 * B_X + 8, 65536u + (kv_cta ? 8192u : 0u));
            mbar_expect_tx(bars + 8 * B_U, 32768u);
        }
        __syncwarp();
        PROF3(6);
    }
    asm volatile("barrier.cluster.arrive.relaxed.aligned;" ::: "memory");
    const unsigned epoch = *(volatile unsigned*)&g_epoch + 1u;
    if (warp > 16) {
        if (lane == 0) {
            for (int i = warp - 17; i < B_X; i += 3) {
                mbar_init(bars + 8 * i, i >= B_H ? 2 : 1);
                if (i <= B_WQ2) mbar_expect_tx(bars + 8 * i, i < B_KV + 2 ? 16384u : i == B_KV + 2 ? 32768u : i <= B_WO ? 65536u : 32768u);
            }
            asm volatile("fence.mbarrier_init.release.cluster;" ::: "memory");
            fence_async_smem();
        } else if (warp == 19) {
            asm volatile("prefetch.global.L2 [%0];" :: "l"((const char*)g_tabmap.v + (lane - 1) * 128));
            if (lane < 5) asm volatile("prefetch.global.L2 [%0];" :: "l"((const char*)g_tabmap.v + (lane + 30) * 128));
        }
        __syncwarp();
    }
    asm volatile("barrier.cluster.wait.aligned;" ::: "memory");
    PROF(5);
    if (warp == 16 && lane == 0) {
        tma_3d_mc(sb + (rank ? SM_A : SM_B), &tm_x, 0, qb * 128, rank * 4, bars + 8 * (B_X + rank));
        if (kv_cta) {
            #pragma unroll
            for (int i = 0; i < 4; i++) tma_2d(sb + SM_WKV + i * 4096, tm_kv, (i >> 1) * 8, (i & 1) * 256, bars + 8 * (B_X + (i & 1)));
        }
        mbar_init(bars + 8 * B_WQ, 1);
        asm volatile("fence.mbarrier_init.release.cluster;" ::: "memory");
        fence_async_smem();
        mbar_expect_tx(bars + 8 * B_WQ, 32768u);
        tma_2d(sb + SM_WQ, &tm_wq, hg * 64, 0, bars + 8 * B_WQ);
        #pragma unroll
        for (int i = 0; i < 4; i++) tma_2d_mc(sb + SM_SLAB + (rank * 4 + i) * 4096, &tm_u, (blockIdx.x >> 1) * 8, (rank * 4 + i) * 256, bars + 8 * B_U);
    }
    __syncwarp();
    asm volatile("barrier.cluster.arrive.relaxed.aligned;" ::: "memory");

    if (warp == 16) {
        if (lane == 0) asm volatile("prefetch.tensormap [%0];" :: "l"((uint64_t)&tm_wo) : "memory");
        asm volatile("barrier.cluster.wait.aligned;" ::: "memory");
        PROF3(10);
        bar_sync(13, 544);
        if (lane == 0) { fence_async_smem(); tma_2d(sb + SM_SLAB, &tm_wq, hg * 64, 256, bars + 8 * B_WQ2); }
        bar_sync(14, 544);
        if (lane == 0) pair_sync(bars + 8 * B_H, rank ^ 1);
        __syncwarp();
        PROF3(11);
        *(uint4*)(sp + SM_V + 32768 + lane * 32) = make_uint4(0x3F803F80u, 0x3F803F80u, 0x3F803F80u, 0x3F803F80u);
        *(uint4*)(sp + SM_V + 32768 + lane * 32 + 16) = make_uint4(0x3F803F80u, 0x3F803F80u, 0x3F803F80u, 0x3F803F80u);
        fence_async_smem();
        float km = wait_flag64(&g_flag_kv[2 * lane], epoch);
        float vm = wait_flag64(&g_flag_kv[2 * lane + 1], epoch);
        __syncwarp();
        PROF3(12);
        if (lane == 0) {
            fence_async_all();
            #pragma unroll
            for (int i = 0; i < 4; i++) {
                const uint32_t k0 = i == 0 ? 0 : 128u << i, nk = i == 0 ? 256 : 128u << i;
                const uint32_t bar = bars + 8 * (B_KV + i);
                if (rank == 0) bulk_g2s_mc(sb + SM_K + k0 * 32, g_kimg + k0 * 32, nk * 32, bar);
                else {
                    bulk_g2s_mc(sb + SM_V + k0 * 16, g_vimg + k0 * 16, nk * 16, bar);
                    bulk_g2s_mc(sb + SM_V + 66560 - (k0 + nk) * 16, g_vimg + 66560 - (k0 + nk) * 16, nk * 16, bar);
                }
            }
        }
        #pragma unroll
        for (int o = 16; o; o >>= 1) { km = fmaxf(km, __shfl_xor_sync(0xffffffffu, km, o)); vm = fmaxf(vm, __shfl_xor_sync(0xffffffffu, vm, o)); }
        if (lane == 0) { s_misc[16] = km; s_misc[17] = vm; mbar_arrive(bars + 8 * B_ST); }
        PROF3(13);
        bar_sync(11, 128);
        if (lane < 2) { fence_async_smem(); tma_2d(sb + SM_B + lane * 32768, &tm_wo, hg * 64, lane * 256, bars + 8 * B_WO); }
        bar_sync(12, 544);
        if (lane == 0) {
            st_release(&g_flag_o[blockIdx.x], epoch);
            pair_sync(bars + 8 * (B_H + 1), rank ^ 1);
        }
        __syncwarp();
        PROF3(14);
        if (lane < 4) {
            const int src = 2 * lane + rank;
            wait_flag(&g_flag_o[qb * 8 + src], epoch);
            fence_async_all();
            bulk_g2s_mc(sb + SM_A + src * 16384, g_oimg + qb * 131072 + src * 16384, 16384, bars + 8 * (B_O + src));
        }
        __syncwarp();
        PROF3(15);
        if (lane == 0) {
            const unsigned prev = atomicAdd(&g_done, 1u);
            if (prev == NCTA - 1) {
                g_done = 0;
                __threadfence();
                *(volatile unsigned*)&g_epoch = epoch;
            }
        }
    } else if (wg == 4) {
        helper_role(P, sp, sb, epoch);
    } else {
        uint8_t* sB = sp + SM_B;
        const uint32_t sBa = sb + SM_B;
        {
            const int c = wg;
            const float dt = bf_round(expf(bf_lo(p_ldt)));
            const float are = -bf_round(expf(bf_lo(p_lar))) * dt;
            const float aim = bf_lo(p_aim) * dt;
            float cr = 2.0f * (bf_lo(p_cre) * dt);
            float ci = 2.0f * (bf_lo(p_cim) * dt);
            const float a2 = are * 1.4426950408889634f, bb = aim * 0.15915494309189535f;
            float m = fmaxf(fabsf(cr), fabsf(ci));
            #pragma unroll
            for (int o = 16; o; o >>= 1) m = fmaxf(m, __shfl_xor_sync(0xffffffffu, m, o));
            int ebits = (__float_as_uint(m) >> 23) & 0xFF;
            ebits = min(max(ebits, 2), 250);
            const float scale = __uint_as_float((uint32_t)(ebits + 1) << 23);
            const float iscale = __uint_as_float((uint32_t)(253 - ebits) << 23);
            cf cc; cc.x = cr * iscale; cc.y = ci * iscale;

            const uint32_t stg = sBa + S_KC + warp * 1024;
            uint4* stp = (uint4*)(sB + S_KC + warp * 1024 + lane * 32);
            const uint32_t fa = stg + t * 32 + g * 4;

            uint32_t af[4][2][4];
            cf E256;
            {
                const cf E8 = cexp_p(a2, bb, 8.0f);
                uint32_t w[8];
                cf cur; cur.x = 1.0f; cur.y = 0.0f;
                w[0] = pack_f16(1.0f, 0.0f);
                cur = E8; w[1] = pack_f16(cur.x, cur.y);
                #pragma unroll
                for (int i = 2; i < 8; i++) { cur = cmul(cur, E8); w[i] = pack_f16(cur.x, cur.y); }
                stp[0] = make_uint4(w[0], w[1], w[2], w[3]);
                stp[1] = make_uint4(w[4], w[5], w[6], w[7]);
                const cf E64 = cexp_p(a2, bb, 64.0f);
                const cf E128 = cmul(E64, E64), E192 = cmul(E128, E64);
                E256 = cexp_p(a2, bb, 256.0f);
                const uint32_t e1 = pack_f16(E64.x, E64.y), e2 = pack_f16(E128.x, E128.y), e3 = pack_f16(E192.x, E192.y);
                __syncwarp();
                #pragma unroll
                for (int s = 0; s < 4; s++) {
                    #pragma unroll
                    for (int hh = 0; hh < 2; hh++) {
                        const uint32_t w0 = lds32(fa + s * 256 + hh * 128);
                        const uint32_t wsw = __byte_perm(w0, 0, 0x1032) ^ 0x00008000u;
                        const int src = 8 * s + t + 4 * hh;
                        const uint32_t f1 = __shfl_sync(0xffffffffu, e1, src), f2 = __shfl_sync(0xffffffffu, e2, src), f3 = __shfl_sync(0xffffffffu, e3, src);
                        af[s][0][2 * hh] = w0;
                        af[s][0][2 * hh + 1] = h2_cmul(w0, wsw, f1);
                        af[s][1][2 * hh] = h2_cmul(w0, wsw, f2);
                        af[s][1][2 * hh + 1] = h2_cmul(w0, wsw, f3);
                    }
                }
                __syncwarp();
            }
            float acc[2][3][4];
            #pragma unroll
            for (int i = 0; i < 24; i++) (&acc[0][0][0])[i] = 0.0f;
            const cf E1 = cexp_p(a2, bb, 1.0f);
            const cf E2 = cmul(E1, E1), E4 = cmul(E2, E2);
            cf X512;
            #pragma unroll
            for (int nt = 0; nt < 3; nt++) {
                uint32_t xv[8];
                if (nt == 0) {
                    cf cur = cc;
                    xv[0] = pack_f16(cur.x, -cur.y);
                    #pragma unroll
                    for (int i = 1; i < 8; i++) { cur = cmul(cur, E1); xv[i] = pack_f16(cur.x, -cur.y); }
                } else if (nt == 1) {
                    cf cur = cmul(cc, E256);
                    X512 = cmul(cur, E256);
                    xv[0] = pack_f16(cur.x, -cur.y);
                    #pragma unroll
                    for (int i = 1; i < 4; i++) { cur = cmul(cur, E2); xv[i] = pack_f16(cur.x, -cur.y); }
                    cur = cmul(X512, E4);
                    xv[4] = pack_f16(X512.x, -X512.y); xv[5] = pack_f16(cur.x, -cur.y);
                    X512 = cmul(X512, E256);
                    cur = cmul(X512, E4);
                    xv[6] = pack_f16(X512.x, -X512.y); xv[7] = pack_f16(cur.x, -cur.y);
                } else {
                    cf cur = X512;
                    #pragma unroll
                    for (int i = 0; i < 5; i++) { cur = cmul(cur, E256); xv[i] = pack_f16(cur.x, -cur.y); }
                    xv[5] = 0; xv[6] = 0; xv[7] = 0;
                }
                stp[0] = make_uint4(xv[0], xv[1], xv[2], xv[3]);
                stp[1] = make_uint4(xv[4], xv[5], xv[6], xv[7]);
                __syncwarp();
                #pragma unroll
                for (int s = 0; s < 4; s++) {
                    const uint32_t b0 = lds32(fa + s * 256), b1 = lds32(fa + s * 256 + 128);
                    mma_f16(acc[0][nt], af[s][0], b0, b1);
                    mma_f16(acc[1][nt], af[s][1], b0, b1);
                }
                __syncwarp();
            }
            float* kc = (float*)(sB + S_KC + c * 4096);
            bar_sync(4 + c, 128);
            #pragma unroll 1
            for (int step = 0; step < 4; step++) {
                if ((warp & 3) == step) {
                    #pragma unroll
                    for (int mt = 0; mt < 2; mt++)
                        #pragma unroll
                        for (int nt = 0; nt < 3; nt++)
                            #pragma unroll
                            for (int hh = 0; hh < 2; hh++) {
                                float2* p = (float2*)(kc + (mt * 16 + hh * 8 + g) * 24 + nt * 8 + 2 * t);
                                float2 v = make_float2(acc[mt][nt][2 * hh] * scale, acc[mt][nt][2 * hh + 1] * scale);
                                if (step) { float2 o = *p; v.x += o.x; v.y += o.y; }
                                *p = v;
                            }
                }
                if (step < 3) bar_sync(4 + c, 128);
            }
        }

        asm volatile("barrier.cluster.wait.aligned;" ::: "memory");
        PROF(4);
        uint32_t q[2][4];
        {
            float acc[16], akv[8];
            #pragma unroll
            for (int i = 0; i < 16; i++) acc[i] = 0.0f;
            #pragma unroll
            for (int i = 0; i < 8; i++) akv[i] = 0.0f;
            fence_regs<16>(acc);
            fence_regs<8>(akv);
            const uint64_t dA0 = make_desc(sb + SM_B + rowhalf * 8192, 16, 1024, 1);
            const uint64_t dA1 = make_desc(sb + SM_A + rowhalf * 8192, 16, 1024, 1) - 4096;
            const uint64_t dB = make_desc(sb + SM_WQ + nh * 64, 16, 1024, 1);
            const uint64_t dC = make_desc(sb + SM_WKV, 128, 8192, 0);
            if (kv_wg) {
                #pragma unroll 1
                for (int ch = 0; ch < 8; ch++) {
                    if ((ch & 3) == 0) mbar_wait(bars + 8 * (B_X + (ch >> 2)), 0);
                    const uint64_t dA = ch < 4 ? dA0 : dA1;
                    wg_fence();
                    #pragma unroll
                    for (int ks = 0; ks < 4; ks++) wg_ss16(akv, dA + ch * 1024 + ks * 2, dC + (ch * 4 + ks) * 16);
                    wg_commit();
                }
                wg_wait<0>();
            }
            fence_regs<8>(akv);
            if (kv_wg) {
                const int key = qb * 128 + rowhalf * 64 + wiw * 16 + g;
                uint32_t pk[4];
                #pragma unroll
                for (int i = 0; i < 4; i++) pk[i] = pack_bf16(akv[2 * i], akv[2 * i + 1]);
                float st;
                if (kv_sel == 0) {
                    uint8_t* b = g_kimg + (key >> 3) * 256 + (key & 7) * 16 + 4 * t;
                    *(uint32_t*)(b) = pk[0]; *(uint32_t*)(b + 256) = pk[1]; *(uint32_t*)(b + 128) = pk[2]; *(uint32_t*)(b + 384) = pk[3];
                    float n0 = bf_lo(pk[0]) * bf_lo(pk[0]) + bf_hi(pk[0]) * bf_hi(pk[0]) + bf_lo(pk[2]) * bf_lo(pk[2]) + bf_hi(pk[2]) * bf_hi(pk[2]);
                    float n1 = bf_lo(pk[1]) * bf_lo(pk[1]) + bf_hi(pk[1]) * bf_hi(pk[1]) + bf_lo(pk[3]) * bf_lo(pk[3]) + bf_hi(pk[3]) * bf_hi(pk[3]);
                    n0 += __shfl_xor_sync(0xffffffffu, n0, 1); n0 += __shfl_xor_sync(0xffffffffu, n0, 2);
                    n1 += __shfl_xor_sync(0xffffffffu, n1, 1); n1 += __shfl_xor_sync(0xffffffffu, n1, 2);
                    st = (n0 != n0 || n1 != n1) ? __int_as_float(0x7f800000) : fmaxf(n0, n1);
                } else {
                    uint8_t* lo = g_vimg + key * 16 + 4 * t;
                    uint8_t* hi = g_vimg + 33792 + (31 - (key >> 6)) * 1024 + (key & 63) * 16 + 4 * t;
                    *(uint32_t*)(lo) = pk[0]; *(uint32_t*)(lo + 128) = pk[1]; *(uint32_t*)(hi) = pk[2]; *(uint32_t*)(hi + 128) = pk[3];
                    st = 0.0f;
                    #pragma unroll
                    for (int i = 0; i < 4; i++) {
                        float a = fabsf(bf_lo(pk[i])), b = fabsf(bf_hi(pk[i]));
                        st = (a != a || b != b) ? __int_as_float(0x7f800000) : fmaxf(st, fmaxf(a, b));
                    }
                }
                #pragma unroll
                for (int o = 16; o; o >>= 1) st = fmaxf(st, __shfl_xor_sync(0xffffffffu, st, o));
                if (lane == 0) s_misc[20 + wiw] = st;
                bar_arrive(3, 160);
            }
            uint32_t mp[9];
            #pragma unroll
            for (int i = 0; i < 9; i++) { const int w = (tid & 127) + 128 * i; mp[i] = (w < TABN / 2) ? __ldg((const uint32_t*)g_tabmap.v + w) : 0u; }
            mbar_wait(bars + 8 * B_WQ, 0);
            mbar_wait(bars + 8 * B_X, 0);
            PROF(2);
            #pragma unroll 1
            for (int ch = 0; ch < 4; ch++) {
                wg_fence();
                #pragma unroll
                for (int ks = 0; ks < 4; ks++) wg_ss32(acc, dA0 + ch * 1024 + ks * 2, dB + (ch * 4 + ks) * 128);
                wg_commit();
            }
            wg_wait<0>();
            fence_regs<16>(acc);
            bar_sync(1, 512);
            PROF(15);
            if (tid < 4 * (PADU / 8)) sts128(swz(sBa + S_U + (tid / (PADU / 8)) * ULEN * 2 + (tid % (PADU / 8)) * 16), make_uint4(0, 0, 0, 0));
            PROF(8);
            mbar_wait(bars + 8 * B_U, 0);
            PROF(14);
            #pragma unroll
            for (int i = 0; i < 2; i++) {
                const int l = 2 * (tid + 512 * i);
                const uint2 r0 = *(const uint2*)(sp + SM_SLAB + l * 16 + rank * 8), r1 = *(const uint2*)(sp + SM_SLAB + l * 16 + 16 + rank * 8);
                const uint32_t dst = sBa + S_U + (PADU + l) * 2;
                sts32(swz(dst), __byte_perm(r0.x, r1.x, 0x5410));
                sts32(swz(dst + ULEN * 2), __byte_perm(r0.x, r1.x, 0x7632));
                sts32(swz(dst + ULEN * 4), __byte_perm(r0.y, r1.y, 0x5410));
                sts32(swz(dst + ULEN * 6), __byte_perm(r0.y, r1.y, 0x7632));
            }
            bar_arrive(13, 544);
            {
                const float* kc = (const float*)(sB + S_KC + wg * 4096);
                uint32_t* tab = (uint32_t*)(sB + S_TAB + wg * TABN * 2);
                #pragma unroll
                for (int i = 0; i < 9; i++) { const int w = (tid & 127) + 128 * i; if (w < TABN / 2) tab[w] = pack_bf16(kc[mp[i] & 0xFFFF], kc[mp[i] >> 16]); }
            }
            PROF(1);
            mbar_wait(bars + 8 * B_WQ2, 0);
            mbar_wait(bars + 8 * (B_X + 1), 0);
            fence_regs<16>(acc);
            #pragma unroll 1
            for (int ch = 4; ch < 8; ch++) {
                wg_fence();
                #pragma unroll
                for (int ks = 0; ks < 4; ks++) wg_ss32(acc, dA1 + ch * 1024 + ks * 2, dB + (ch * 4 + ks) * 128);
                wg_commit();
            }
            wg_wait<0>();
            fence_regs<16>(acc);
            bar_arrive(14, 544);
            const float QS = 0.25f * 1.4426950408889634f;
            float qm = 0.0f;
            #pragma unroll
            for (int i = 0; i < 2; i++) {
                #pragma unroll
                for (int j = 0; j < 4; j++) q[i][j] = pack_bf16(acc[8 * i + 2 * j] * QS, acc[8 * i + 2 * j + 1] * QS);
                float n0 = bf_lo(q[i][0]) * bf_lo(q[i][0]) + bf_hi(q[i][0]) * bf_hi(q[i][0]) + bf_lo(q[i][2]) * bf_lo(q[i][2]) + bf_hi(q[i][2]) * bf_hi(q[i][2]);
                float n1 = bf_lo(q[i][1]) * bf_lo(q[i][1]) + bf_hi(q[i][1]) * bf_hi(q[i][1]) + bf_lo(q[i][3]) * bf_lo(q[i][3]) + bf_hi(q[i][3]) * bf_hi(q[i][3]);
                n0 += __shfl_xor_sync(0xffffffffu, n0, 1); n0 += __shfl_xor_sync(0xffffffffu, n0, 2);
                n1 += __shfl_xor_sync(0xffffffffu, n1, 1); n1 += __shfl_xor_sync(0xffffffffu, n1, 2);
                qm = (n0 != n0 || n1 != n1) ? __int_as_float(0x7f800000) : fmaxf(qm, fmaxf(n0, n1));
            }
            #pragma unroll
            for (int o = 16; o; o >>= 1) qm = fmaxf(qm, __shfl_xor_sync(0xffffffffu, qm, o));
            if (lane == 0) s_misc[warp] = qm;
        }
        PROF(3);
        bar_sync(1, 512);
        #pragma unroll 1
        for (int task = tid; task < 4 * 194; task += 512) {
            const int c = task / 194, i = task % 194;
            const uint32_t src = sBa + S_U + c * ULEN * 2 + (PADU + 8 * i - WPAD - 8) * 2;
            const uint4 v0 = lds128(swz(src)), v1 = lds128(swz(src + 16)), v2 = lds128(swz(src + 32));
            float x[24];
            const uint32_t vv[12] = {v0.x, v0.y, v0.z, v0.w, v1.x, v1.y, v1.z, v1.w, v2.x, v2.y, v2.z, v2.w};
            #pragma unroll
            for (int k = 0; k < 12; k++) { x[2 * k] = bf_lo(vv[k]); x[2 * k + 1] = bf_hi(vv[k]); }
            float w3[12], w5[8];
            #pragma unroll
            for (int e = 0; e < 12; e++) w3[e] = (x[3 + e] + x[4 + e]) + x[5 + e];
            #pragma unroll
            for (int e = 0; e < 8; e++) w5[e] = w3[4 + e] + (x[6 + e] + x[10 + e]);
            sts128(swz(sBa + S_W3 + c * W2LEN * 2 + i * 16), make_uint4(pack_bf16(w3[0], w3[1]), pack_bf16(w3[2], w3[3]), pack_bf16(w3[4], w3[5]), pack_bf16(w3[6], w3[7])));
            sts128(swz(sBa + S_W5 + c * W2LEN * 2 + i * 16), make_uint4(pack_bf16(w5[0], w5[1]), pack_bf16(w5[2], w5[3]), pack_bf16(w5[4], w5[5]), pack_bf16(w5[6], w5[7])));
            if (i < 130) {
                float w7[8], w9[8];
                #pragma unroll
                for (int e = 0; e < 8; e++) { w7[e] = w5[e] + (x[5 + e] + x[11 + e]); w9[e] = w7[e] + (x[4 + e] + x[12 + e]); }
                sts128(swz(sBa + S_W7 + c * W3LEN * 2 + i * 16), make_uint4(pack_bf16(w7[0], w7[1]), pack_bf16(w7[2], w7[3]), pack_bf16(w7[4], w7[5]), pack_bf16(w7[6], w7[7])));
                sts128(swz(sBa + S_W9 + c * W3LEN * 2 + i * 16), make_uint4(pack_bf16(w9[0], w9[1]), pack_bf16(w9[2], w9[3]), pack_bf16(w9[4], w9[5]), pack_bf16(w9[6], w9[7])));
            }
        }
        bar_sync(1, 512);
        PROF(6);
        {
            const int c = wg, ps = (wiw + c) & 3;
            uint32_t sBl = sBa;
            asm volatile("" : "+r"(sBl) :: "memory");
            float acc[2][2][2][4];
            #pragma unroll
            for (int i = 0; i < 32; i++) (&acc[0][0][0][0])[i] = 0.0f;
            const uint32_t tabc = sBl + S_TAB + c * TABN * 2;
            const int e2 = (g - 2 * t) * 2;
            const int mi = lane >> 3, r8 = lane & 7;
            const uint32_t frag = (16 * (8 * (mi >> 1) + r8) + 8 * (mi & 1)) * 2;
            const uint32_t ub = sBl + S_U + c * ULEN * 2 + PADU * 2 + frag;
            {
                const uint32_t tD = tabc + ((g & 1) ? (TD1 + CD + 1) : (TD0 + CD)) * 2 - e2;
                #pragma unroll 1
                for (int rho = 0; rho < 8; rho++) {
                    uint32_t R[5][3], b[2][3][4];
                    const uint32_t base = swz(ub - rho * 32);
                    #pragma unroll
                    for (int pi = 0; pi < 2; pi++)
                        #pragma unroll
                        for (int i = 0; i < 3; i++) {
                            const int jp = (pi ? 7 - ps : ps) - 2 + i;
                            ldsm4_p(b[pi][i], base + max(jp, -1) * 512);
                            if (pi == 0 && jp < -1) { b[pi][i][0] = 0; b[pi][i][1] = 0; b[pi][i][2] = 0; b[pi][i][3] = 0; }
                        }
                    #pragma unroll
                    for (int qq = 0; qq < 5; qq++) {
                        const uint32_t a = tD - 32 * ((qq < 4 || rho < 2) ? rho + 8 * qq : 0);
                        R[qq][0] = lds32_p(a + 16); R[qq][1] = lds32_p(a); R[qq][2] = lds32_p(a - 16);
                    }
                    #pragma unroll
                    for (int i = 2; i >= 0; i--) {
                        #pragma unroll
                        for (int hh = 0; hh < 2; hh++)
                            #pragma unroll
                            for (int tt = 0; tt < 2; tt++) {
                                const int qq = 4 - 2 * i + tt - hh;
                                if (qq >= 0 && qq < 4) {
                                    mma_bf16_p(acc[hh][1][tt], R[qq][1], R[qq][2], R[qq][0], R[qq][1], b[1][i][2 * hh], b[1][i][2 * hh + 1]);
                                    if (ps - 2 + i >= (rho ? 0 : -1))
                                        mma_bf16_p(acc[hh][0][tt], R[qq][1], R[qq][2], R[qq][0], R[qq][1], b[0][i][2 * hh], b[0][i][2 * hh + 1]);
                                }
                            }
                    }
                    if (rho < 2) {
                        #pragma unroll
                        for (int pi = 0; pi < 2; pi++) {
                            mma_bf16_p(acc[0][pi][0], R[4][1], R[4][2], R[4][0], R[4][1], b[pi][0][0], b[pi][0][1]);
                            mma_bf16_p(acc[1][pi][1], R[4][1], R[4][2], R[4][0], R[4][1], b[pi][0][2], b[pi][0][3]);
                        }
                    }
                }
            }
            {
                const uint32_t tE = tabc + ((g & 1) ? (TE1 + CE + 1) : (TE0 + CE)) * 2 - e2;
                uint32_t R[5];
                #pragma unroll
                for (int i = 0; i < 5; i++) R[i] = lds32_p(tE - 16 * (127 + i));
                #pragma unroll
                for (int kk = 0; kk < 2; kk++) {
                    uint32_t b[4];
                    ldsm4_p(b, swz(ub - kk * 32) + (3 - ps) * 512);
                    mma_bf16_p(acc[kk][1][0], R[2 * kk + 1], R[2 * kk + 2], R[2 * kk], R[2 * kk + 1], b[0], b[1]);
                    mma_bf16_p(acc[kk][1][1], R[2 * kk + 1], R[2 * kk + 2], R[2 * kk], R[2 * kk + 1], b[2], b[3]);
                }
            }
            {
                const uint32_t t2 = tabc + (T2B + ((g & 1) ? (T2C + C2 + 1) : C2)) * 2 - e2;
                #pragma unroll 1
                for (int s = 0; s < 4; s++) {
                    const uint32_t sig = swz(sBl + ((s & 1) ? S_W3 : S_W5) + c * W2LEN * 2 + WPAD * 2 + frag - ((s == 0) ? 32 : (s == 1) ? 0 : 16));
                    uint32_t R[7], a[2][3][4];
                    #pragma unroll
                    for (int pi = 0; pi < 2; pi++)
                        #pragma unroll
                        for (int be = 2; be <= 4; be++) ldsm4t_p(a[pi][be - 2], sig + max((pi ? 7 - ps : ps) - be, 0) * 512);
                    #pragma unroll
                    for (int i = 0; i < 7; i++) R[i] = lds32_p(t2 + s * (T2S * 2) - 16 * (3 + i));
                    #pragma unroll
                    for (int be = 2; be <= 4; be++) {
                        const uint32_t* a1 = a[1][be - 2];
                        mma_bf16_p(acc[be & 1][1][0], a1[0], a1[1], a1[2], a1[3], R[2 * be - 3], R[2 * be - 4]);
                        mma_bf16_p(acc[be & 1][1][1], a1[0], a1[1], a1[2], a1[3], R[2 * be - 2], R[2 * be - 3]);
                        if (ps - be >= 0) {
                            const uint32_t* a0 = a[0][be - 2];
                            mma_bf16_p(acc[be & 1][0][0], a0[0], a0[1], a0[2], a0[3], R[2 * be - 3], R[2 * be - 4]);
                            mma_bf16_p(acc[be & 1][0][1], a0[0], a0[1], a0[2], a0[3], R[2 * be - 2], R[2 * be - 3]);
                        }
                    }
                }
                const uint32_t t3 = tabc + (T3B + ((g & 1) ? (T3C + C3 + 1) : C3)) * 2 - e2;
                #pragma unroll 1
                for (int s = 0; s < 2; s++) {
                    const uint32_t sig = swz(sBl + (s ? S_W7 : S_W9) + c * W3LEN * 2 + WPAD * 2 + frag - (s ? 16 : 32));
                    uint32_t R[9], a[4][4];
                    #pragma unroll
                    for (int be = 4; be <= 7; be++) ldsm4t_p(a[be - 4], sig + max(7 - ps - be, 0) * 512);
                    #pragma unroll
                    for (int i = 0; i < 9; i++) R[i] = lds32_p(t3 + s * (T3S * 2) - 16 * (7 + i));
                    #pragma unroll
                    for (int be = 4; be <= 7; be++) {
                        if (7 - ps - be >= 0) {
                            mma_bf16_p(acc[be & 1][1][0], a[be - 4][0], a[be - 4][1], a[be - 4][2], a[be - 4][3], R[2 * be - 7], R[2 * be - 8]);
                            mma_bf16_p(acc[be & 1][1][1], a[be - 4][0], a[be - 4][1], a[be - 4][2], a[be - 4][3], R[2 * be - 6], R[2 * be - 7]);
                        }
                    }
                }
            }
            __nv_bfloat16* ys = (__nv_bfloat16*)(sB + S_Y + c * 4096) + 32 * t + g;
            #pragma unroll
            for (int pi = 0; pi < 2; pi++) {
                #pragma unroll
                for (int tt = 0; tt < 2; tt++) {
                    __nv_bfloat16* y = ys + 128 * (2 * (pi ? 7 - ps : ps) + tt);
                    y[0] = __float2bfloat16_rn(acc[0][pi][tt][0] + acc[1][pi][tt][0]);
                    y[16] = __float2bfloat16_rn(acc[0][pi][tt][1] + acc[1][pi][tt][1]);
                    y[8] = __float2bfloat16_rn(acc[0][pi][tt][2] + acc[1][pi][tt][2]);
                    y[24] = __float2bfloat16_rn(acc[0][pi][tt][3] + acc[1][pi][tt][3]);
                }
            }
        }
        bar_arrive(10, 608);
        PROF(7);
        {
            mbar_wait(bars + 8 * B_ST, 0);
            PROF(9); PROFC(8);
            float qm = 0.0f;
            #pragma unroll
            for (int i = 0; i < 16; i++) qm = fmaxf(qm, s_misc[i]);
            const float vm = s_misc[17];
            const bool fast = (qm * s_misc[16] <= 60.0f * 60.0f) && (vm <= 1.0e12f) && (vm >= 1.0e-12f || vm == 0.0f);
            uint8_t* ob = g_oimg + qb * 131072 + hg * 16384 + nh * 8192 + (rowhalf * 8 + wiw * 2) * 128 + g * 16 + 4 * t;
            uint32_t cA = 0xBF00BF00u, cB = 0x00030003u;
            asm volatile("" : "+r"(cA), "+r"(cB));
            #pragma unroll 1
            for (int tile = 0; tile < 2; tile++) {
                uint32_t kLo = (((sb + SM_K) & 0x3FFFF) >> 4) | (8u << 16), vLo = (((sb + SM_V) & 0x3FFFF) >> 4) | (8u << 16), vHi = 2048;
                float o[12], s[32];
                uint32_t p[16], qq[4];
                #pragma unroll
                for (int i = 0; i < 4; i++) { qq[i] = tile ? q[1][i] : q[0][i]; asm volatile("" : "+r"(qq[i])); }
                #pragma unroll
                for (int i = 0; i < 12; i++) o[i] = 0.0f;
                #pragma unroll
                for (int i = 0; i < 32; i++) s[i] = 0.0f;
                fence_regs<12>(o);
                fence_regs<32>(s);
                if (fast) {
                    #pragma unroll 1
                    for (int c = 0; c < SEQ / 256; c++) {
                        if (c <= 4) mbar_wait(bars + 8 * (B_KV + (c < 2 ? c : c < 4 ? 2 : 3)), 0);
                        wg_fence();
                        wg_qk(s, qq, kLo);
                        wg_commit();
                        #pragma unroll
                        for (int u = 0; u < 4; u++) {
                            wg_wait<0>();
                            fence_regs<32>(s);
                            #pragma unroll
                            for (int i = 0; i < 16; i++) {
                                if ((MUFU_MASK >> i) & 1) p[i] = exp_mufu(s[2 * i], s[2 * i + 1]);
                                else p[i] = exp_sw(s[2 * i], s[2 * i + 1], cA, cB);
                            }
                            wg_fence();
                            if (u + 1 < 4) wg_qk(s, qq, kLo + (u + 1) * 128);
                            #pragma unroll
                            for (int kk = 0; kk < 4; kk++) wg_pv(o, p + 4 * kk, vLo + u * 64 + kk * 16, vHi - u * 64);
                            wg_commit();
                        }
                        kLo += 512; vLo += 256; vHi -= 256;
                    }
                    wg_wait<0>();
                } else {
                    float mx0 = -INFINITY, mx1 = -INFINITY;
                    #pragma unroll 1
                    for (int c = 0; c < SEQ / 64; c++) {
                        if (c <= 16) mbar_wait(bars + 8 * (B_KV + (c < 8 ? (c >> 2) : c < 16 ? 2 : 3)), 0);
                        wg_fence();
                        wg_qk(s, qq, kLo);
                        wg_commit();
                        wg_wait<0>();
                        fence_regs<32>(s);
                        fence_regs<12>(o);
                        float m0 = mx0, m1 = mx1;
                        #pragma unroll
                        for (int j = 0; j < 8; j++) {
                            m0 = fmaxf(m0, fmaxf(s[4 * j], s[4 * j + 1]));
                            m1 = fmaxf(m1, fmaxf(s[4 * j + 2], s[4 * j + 3]));
                        }
                        m0 = fmaxf(m0, __shfl_xor_sync(0xffffffffu, m0, 1)); m0 = fmaxf(m0, __shfl_xor_sync(0xffffffffu, m0, 2));
                        m1 = fmaxf(m1, __shfl_xor_sync(0xffffffffu, m1, 1)); m1 = fmaxf(m1, __shfl_xor_sync(0xffffffffu, m1, 2));
                        const float c0 = ex2f(mx0 - m0), c1 = ex2f(mx1 - m1);
                        mx0 = m0; mx1 = m1;
                        #pragma unroll
                        for (int j = 0; j < 3; j++) { o[4 * j] *= c0; o[4 * j + 1] *= c0; o[4 * j + 2] *= c1; o[4 * j + 3] *= c1; }
                        #pragma unroll
                        for (int j = 0; j < 8; j++) {
                            p[2 * j] = exp_mufu(s[4 * j] - m0, s[4 * j + 1] - m0);
                            p[2 * j + 1] = exp_mufu(s[4 * j + 2] - m1, s[4 * j + 3] - m1);
                        }
                        wg_fence();
                        #pragma unroll
                        for (int kk = 0; kk < 4; kk++) wg_pv(o, p + 4 * kk, vLo + kk * 16, vHi);
                        wg_commit();
                        wg_wait<0>();
                        kLo += 128; vLo += 64; vHi -= 64;
                    }
                }
                fence_regs<12>(o);
                if (tile == 0) PROFC(3);
                const float i0 = 1.0f / o[4], i1 = 1.0f / o[6];
                uint8_t* b = ob + tile * 4096;
                *(uint32_t*)(b) = pack_bf16(o[0] * i0, o[1] * i0);
                *(uint32_t*)(b + 128) = pack_bf16(o[2] * i1, o[3] * i1);
                *(uint32_t*)(b + 2048) = pack_bf16(o[8] * i0, o[9] * i0);
                *(uint32_t*)(b + 2048 + 128) = pack_bf16(o[10] * i1, o[11] * i1);
            }
        }
        PROF(10); PROFC(9);
        bar_arrive(12, 544);

        {
            float acc[16];
            #pragma unroll
            for (int i = 0; i < 16; i++) acc[i] = 0.0f;
            fence_regs<16>(acc);
            const uint64_t dA = make_desc(sb + SM_A + rowhalf * 1024, 2048, 128, 0);
            const uint64_t dB = make_desc(sb + SM_B + nh * 64, 16, 1024, 1);
            mbar_wait(bars + 8 * B_WO, 0);
            #pragma unroll 1
            for (int i = 0; i < 8; i++) {
                const int src = (hg + i) & 7;
                mbar_wait(bars + 8 * (B_O + src), 0);
                wg_fence();
                #pragma unroll
                for (int kk = 0; kk < 4; kk++) wg_ss32(acc, dA + src * 1024 + kk * 256, dB + (src * 4 + kk) * 128);
                wg_commit();
            }
            wg_wait<0>();
            fence_regs<16>(acc);
            PROF(12);
            const int row = qb * 128 + rowhalf * 64 + wiw * 16 + g;
            uint32_t* o32 = (uint32_t*)(P.out + (size_t)row * 1024 + hg * 64 + nh * 32 + 2 * t);
            #pragma unroll
            for (int j = 0; j < 4; j++) {
                o32[4 * j] = pack_bf16(acc[4 * j], acc[4 * j + 1]);
                o32[4 * j + 8 * 512] = pack_bf16(acc[4 * j + 2], acc[4 * j + 3]);
            }
        }
        PROF(13);
    }
}

typedef CUresult (*EncodeFn)(CUtensorMap*, CUtensorMapDataType, cuuint32_t, void*, const cuuint64_t*, const cuuint64_t*,
                             const cuuint32_t*, const cuuint32_t*, CUtensorMapInterleave, CUtensorMapSwizzle,
                             CUtensorMapL2promotion, CUtensorMapFloatOOBfill);

void make_map(EncodeFn fn, CUtensorMap* m, const void* ptr, uint64_t inner, uint64_t outer, uint32_t box_in, uint32_t box_out, CUtensorMapSwizzle swz) {
    cuuint64_t dims[2] = {inner, outer};
    cuuint64_t strides[1] = {inner * 2};
    cuuint32_t box[2] = {box_in, box_out};
    cuuint32_t es[2] = {1, 1};
    fn(m, CU_TENSOR_MAP_DATA_TYPE_BFLOAT16, 2, const_cast<void*>(ptr), dims, strides, box, es, CU_TENSOR_MAP_INTERLEAVE_NONE, swz,
       CU_TENSOR_MAP_L2_PROMOTION_L2_128B, CU_TENSOR_MAP_FLOAT_OOB_FILL_NONE);
}

}

extern "C" void kernel_launch(void* const* d_in, const int* in_sizes, int n_in, void* d_out, int out_size) {
    (void)in_sizes; (void)n_in; (void)out_size;
    static EncodeFn fn = nullptr;
    if (!fn) {
        void* p = nullptr;
        cudaDriverEntryPointQueryResult qr;
        cudaGetDriverEntryPoint("cuTensorMapEncodeTiled", &p, cudaEnableDefault, &qr);
        fn = (EncodeFn)p;
        cudaFuncSetAttribute(fused_kernel, cudaFuncAttributeMaxDynamicSharedMemorySize, SM_ALLOC);
    }
    CUtensorMap tx, twq, two, twk, twv, tu;
    {
        cuuint64_t dims[3] = {64, 2048, 8};
        cuuint64_t strides[2] = {1024, 128};
        cuuint32_t box[3] = {64, 128, 4};
        cuuint32_t es[3] = {1, 1, 1};
        fn(&tx, CU_TENSOR_MAP_DATA_TYPE_BFLOAT16, 3, d_in[0], dims, strides, box, es, CU_TENSOR_MAP_INTERLEAVE_NONE, CU_TENSOR_MAP_SWIZZLE_128B,
           CU_TENSOR_MAP_L2_PROMOTION_L2_128B, CU_TENSOR_MAP_FLOAT_OOB_FILL_NONE);
    }
    make_map(fn, &tu, d_in[5], 512, 2048, 8, 256, CU_TENSOR_MAP_SWIZZLE_NONE);
    make_map(fn, &twq, d_in[1], 512, 512, 64, 256, CU_TENSOR_MAP_SWIZZLE_128B);
    make_map(fn, &twk, d_in[2], 16, 512, 8, 256, CU_TENSOR_MAP_SWIZZLE_NONE);
    make_map(fn, &twv, d_in[3], 16, 512, 8, 256, CU_TENSOR_MAP_SWIZZLE_NONE);
    make_map(fn, &two, d_in[4], 512, 512, 64, 256, CU_TENSOR_MAP_SWIZZLE_128B);
    Params P;
    P.u = (const __nv_bfloat16*)d_in[5];
    P.lar = (const __nv_bfloat16*)d_in[6];
    P.aim = (const __nv_bfloat16*)d_in[7];
    P.cre = (const __nv_bfloat16*)d_in[8];
    P.cim = (const __nv_bfloat16*)d_in[9];
    P.logdt = (const __nv_bfloat16*)d_in[10];
    P.dskip = (const __nv_bfloat16*)d_in[11];
    P.out = (__nv_bfloat16*)d_out;
    fused_kernel<<<NCTA, NTHR, SM_ALLOC>>>(tx, twq, two, twk, twv, tu, P);
}
```

```cpp
#include <cuda_runtime.h>
#include <cuda_bf16.h>
#include <cuda_fp16.h>
#include <cuda.h>
#include <stdint.h>

namespace {

constexpr int SEQ = 2048;
constexpr int NCTA = 128, NTHR = 640;

constexpr int SM_A = 0;
constexpr int SM_WQ = 65536;
constexpr int SM_SLAB = SM_WQ + 32768;
constexpr int SM_K = 0, SM_V = 65536;
constexpr int SM_B = 132096;
constexpr int SM_WKV = SM_B + 65536;

constexpr int PADU = 288, ULEN = PADU + 2048;
constexpr int WPAD = 16, W2LEN = WPAD + 1536, W3LEN = WPAD + 1024;
constexpr int TABN = 2240;
constexpr int S_U = 0;
constexpr int S_W3 = S_U + 4 * ULEN * 2;
constexpr int S_W5 = S_W3 + 4 * W2LEN * 2;
constexpr int S_W7 = S_W5 + 4 * W2LEN * 2;
constexpr int S_W9 = S_W7 + 4 * W3LEN * 2;
constexpr int S_TAB = S_W9 + 4 * W3LEN * 2;
constexpr int S_KC = 214016 - SM_B;
constexpr int S_Y = S_KC;
constexpr int SM_BAR = SM_B + S_KC + 16384;
constexpr int SM_TOTAL = SM_BAR + 1024;
constexpr int SM_ALLOC = SM_TOTAL + 1024;
static_assert(SM_V + 65536 + 1024 <= SM_B && SM_ALLOC <= 232448 && S_TAB + 4 * TABN * 2 <= S_KC && SM_WKV + 16384 <= SM_B + S_KC, "smem map");

constexpr int TD0 = 0, TD1 = 560, CD = 544;
constexpr int TE0 = 1120, TE1 = 1168, CE = 1056;
constexpr int T2B = 1216, T2S = 160, T2C = 80, C2 = 80;
constexpr int T3B = 1856, T3S = 192, T3C = 96, C3 = 144;

constexpr int rne8(int t) {
    if (t < 256) return t;
    int sh = 0;
    while ((t >> sh) >= 256) sh++;
    int q = t >> sh, rem = t & ((1 << sh) - 1), half = 1 << (sh - 1);
    if (rem > half || (rem == half && (q & 1))) q++;
    return q << sh;
}
constexpr int kcidx(int p) {
    if (p < 256) return (p >> 3) * 24 + (p & 7);
    if (p < 512) return ((p - 256) >> 3) * 24 + 8 + (((p - 256) & 7) >> 1);
    if (p < 1024) { int q = p - 512, hi = q >> 8, rem = q & 255; return (rem >> 3) * 24 + 12 + 2 * hi + ((rem & 7) >> 2); }
    if (p < 2048) { int q = p - 1024; return ((q & 255) >> 3) * 24 + 16 + (q >> 8); }
    return 20;
}
constexpr int KC_ZERO = 23;
constexpr int tab_dense(int t) { return (t >= 0 && t <= 514) ? kcidx(rne8(t)) : KC_ZERO; }
constexpr int tab_extra(int t) { return (t >= 1027 && t <= 1028) ? kcidx(1024) : KC_ZERO; }
constexpr int tab_2(int s, int lag) { return (lag >= 32 && lag <= 63) ? kcidx(s == 0 ? 16 * (lag + 1) : 16 * lag + 4 * s) : KC_ZERO; }
constexpr int tab_3(int s, int lag) { return (lag >= 64 && lag <= 127) ? kcidx(s == 0 ? 16 * (lag + 1) : 16 * lag + 8) : KC_ZERO; }
struct TabMap {
    uint16_t v[TABN];
    constexpr TabMap() : v{} {
        for (int i = 0; i < 560; i++) { v[TD0 + i] = tab_dense(CD - i); v[TD1 + i] = tab_dense(CD + 1 - i); }
        for (int i = 0; i < 48; i++) { v[TE0 + i] = tab_extra(CE - i); v[TE1 + i] = tab_extra(CE + 1 - i); }
        for (int s = 0; s < 4; s++)
            for (int i = 0; i < T2C; i++) { v[T2B + s * T2S + i] = tab_2(s, C2 - i); v[T2B + s * T2S + T2C + i] = tab_2(s, C2 + 1 - i); }
        for (int s = 0; s < 2; s++)
            for (int i = 0; i < T3C; i++) { v[T3B + s * T3S + i] = tab_3(s, C3 - i); v[T3B + s * T3S + T3C + i] = tab_3(s, C3 + 1 - i); }
    }
};
__device__ const __align__(16) TabMap g_tabmap = TabMap();

__device__ __align__(1024) uint8_t g_kimg[65536];
__device__ __align__(1024) uint8_t g_vimg[65536 + 1024];
__device__ __align__(1024) uint8_t g_oimg[16 * 131072];
__device__ unsigned long long g_flag_kv[64];
__device__ unsigned g_flag_o[128];
__device__ unsigned g_epoch;
__device__ unsigned g_done;

#define PROF(i) do {} while (0)
#define PROF2(i) do {} while (0)
#define PROFC(i) do {} while (0)
#define PROF3(i) do {} while (0)

__device__ __forceinline__ uint32_t smem_u32(const void* p) { return (uint32_t)__cvta_generic_to_shared(p); }
__device__ __forceinline__ void mbar_init(uint32_t bar, uint32_t cnt) { asm volatile("mbarrier.init.shared::cta.b64 [%0], %1;" :: "r"(bar), "r"(cnt) : "memory"); }
__device__ __forceinline__ void mbar_expect_tx(uint32_t bar, uint32_t bytes) {
    asm volatile("mbarrier.arrive.expect_tx.shared::cta.b64 _, [%0], %1;" :: "r"(bar), "r"(bytes) : "memory"); }
__device__ __forceinline__ void mbar_wait(uint32_t bar, uint32_t parity) {
    uint32_t ok = 0;
    for (int it = 0; it < (1 << 22) && !ok; it++) {
        asm volatile("{ .reg .pred p; mbarrier.try_wait.parity.shared::cta.b64 p, [%1], %2; selp.u32 %0, 1, 0, p; }"
                     : "=r"(ok) : "r"(bar), "r"(parity) : "memory");
    }
}
__device__ __forceinline__ void tma_2d(uint32_t dst, const CUtensorMap* map, int c0, int c1, uint32_t bar) {
    asm volatile("cp.async.bulk.tensor.2d.shared::cluster.global.mbarrier::complete_tx::bytes [%0], [%1, {%3, %4}], [%2];"
                 :: "r"(dst), "l"((uint64_t)map), "r"(bar), "r"(c0), "r"(c1) : "memory");
}
__device__ __forceinline__ void tma_2d_mc(uint32_t dst, const CUtensorMap* map, int c0, int c1, uint32_t bar) {
    asm volatile("cp.async.bulk.tensor.2d.shared::cluster.global.mbarrier::complete_tx::bytes.multicast::cluster [%0], [%1, {%3, %4}], [%2], %5;"
                 :: "r"(dst), "l"((uint64_t)map), "r"(bar), "r"(c0), "r"(c1), "h"((uint16_t)3) : "memory");
}
__device__ __forceinline__ void bulk_g2s_mc(uint32_t dst, const void* src, uint32_t bytes, uint32_t bar) {
    asm volatile("cp.async.bulk.shared::cluster.global.mbarrier::complete_tx::bytes.multicast::cluster [%0], [%1], %2, [%3], %4;"
                 :: "r"(dst), "l"((uint64_t)src), "r"(bytes), "r"(bar), "h"((uint16_t)3) : "memory");
}
__device__ __forceinline__ void pair_sync(uint32_t bar, uint32_t peer) {
    uint32_t ra;
    asm volatile("mapa.shared::cluster.u32 %0, %1, %2;" : "=r"(ra) : "r"(bar), "r"(peer));
    asm volatile("mbarrier.arrive.shared::cluster.b64 _, [%0];" :: "r"(ra) : "memory");
    asm volatile("mbarrier.arrive.shared::cta.b64 _, [%0];" :: "r"(bar) : "memory");
    uint32_t ok = 0;
    for (int it = 0; it < (1 << 22) && !ok; it++) {
        asm volatile("{ .reg .pred p; mbarrier.try_wait.parity.shared::cta.b64 p, [%1], 0; selp.u32 %0, 1, 0, p; }"
                     : "=r"(ok) : "r"(bar) : "memory");
    }
}
__device__ __forceinline__ void fence_async_all() { asm volatile("fence.proxy.async.global;" ::: "memory"); }
__device__ __forceinline__ void fence_async_smem() { asm volatile("fence.proxy.async.shared::cta;" ::: "memory"); }
__device__ __forceinline__ unsigned ld_acquire(const unsigned* p) {
    unsigned v; asm volatile("ld.acquire.gpu.global.u32 %0, [%1];" : "=r"(v) : "l"(p) : "memory"); return v; }
__device__ __forceinline__ void st_release(unsigned* p, unsigned v) { asm volatile("st.release.gpu.global.u32 [%0], %1;" :: "l"(p), "r"(v) : "memory"); }
__device__ __forceinline__ void wait_flag(const unsigned* p, unsigned epoch) {
    for (int it = 0; it < (1 << 22); it++) { if (ld_acquire(p) == epoch) break; }
}
__device__ __forceinline__ unsigned long long ld_acquire64(const unsigned long long* p) {
    unsigned long long v; asm volatile("ld.acquire.gpu.global.u64 %0, [%1];" : "=l"(v) : "l"(p) : "memory"); return v; }
__device__ __forceinline__ void st_release64(unsigned long long* p, unsigned long long v) { asm volatile("st.release.gpu.global.u64 [%0], %1;" :: "l"(p), "l"(v) : "memory"); }
__device__ __forceinline__ float wait_flag64(const unsigned long long* p, unsigned epoch) {
    unsigned long long v = 0;
    for (int it = 0; it < (1 << 22); it++) { v = ld_acquire64(p); if ((unsigned)(v >> 32) == epoch) break; }
    return __uint_as_float((unsigned)v);
}
__device__ __forceinline__ void tma_3d_mc(uint32_t dst, const CUtensorMap* map, int c0, int c1, int c2, uint32_t bar) {
    asm volatile("cp.async.bulk.tensor.3d.shared::cluster.global.mbarrier::complete_tx::bytes.multicast::cluster [%0], [%1, {%3, %4, %5}], [%2], %6;"
                 :: "r"(dst), "l"((uint64_t)map), "r"(bar), "r"(c0), "r"(c1), "r"(c2), "h"((uint16_t)3) : "memory");
}
__device__ __forceinline__ void bar_sync(int id, int n) { asm volatile("bar.sync %0, %1;" :: "r"(id), "r"(n) : "memory"); }
__device__ __forceinline__ void bar_arrive(int id, int n) { asm volatile("bar.arrive %0, %1;" :: "r"(id), "r"(n) : "memory"); }
__device__ __forceinline__ void mbar_arrive(uint32_t bar) { asm volatile("mbarrier.arrive.shared::cta.b64 _, [%0];" :: "r"(bar) : "memory"); }

__device__ __forceinline__ uint64_t make_desc(uint32_t saddr, uint32_t lbo, uint32_t sbo, uint32_t swz) {
    uint64_t d = 0;
    d |= (uint64_t)((saddr & 0x3FFFF) >> 4);
    d |= (uint64_t)((lbo >> 4) & 0x3FFF) << 16;
    d |= (uint64_t)((sbo >> 4) & 0x3FFF) << 32;
    d |= (uint64_t)swz << 62;
    return d;
}
__device__ __forceinline__ void wg_fence() { asm volatile("wgmma.fence.sync.aligned;" ::: "memory"); }
__device__ __forceinline__ void wg_commit() { asm volatile("wgmma.commit_group.sync.aligned;" ::: "memory"); }
template<int N> __device__ __forceinline__ void wg_wait() { asm volatile("wgmma.wait_group.sync.aligned %0;" :: "n"(N) : "memory"); }
#define A4(d, o) "+f"(d[o + 0]), "+f"(d[o + 1]), "+f"(d[o + 2]), "+f"(d[o + 3])
#define A16(d, o) A4(d, o), A4(d, o + 4), A4(d, o + 8), A4(d, o + 12)

__device__ __forceinline__ void wg_pv(float* d, const uint32_t* a, uint32_t lo, uint32_t hi) {
    asm volatile("{ .reg .b64 dd; mov.b64 dd, {%16, %17};\n"
                 "wgmma.mma_async.sync.aligned.m64n24k16.f32.bf16.bf16 {%0,%1,%2,%3,%4,%5,%6,%7,%8,%9,%10,%11}, {%12,%13,%14,%15}, dd, 1, 1, 1, 1; }"
                 : A4(d, 0), A4(d, 4), A4(d, 8) : "r"(a[0]), "r"(a[1]), "r"(a[2]), "r"(a[3]), "r"(lo), "r"(hi));
}
__device__ __forceinline__ void wg_qk(float* d, const uint32_t* a, uint32_t lo) {
    asm volatile("{ .reg .b64 dd; mov.b64 dd, {%36, %37};\n"
                 "wgmma.mma_async.sync.aligned.m64n64k16.f32.bf16.bf16 {%0,%1,%2,%3,%4,%5,%6,%7,%8,%9,%10,%11,%12,%13,%14,%15,%16,%17,%18,%19,%20,%21,%22,%23,%24,%25,%26,%27,%28,%29,%30,%31}, {%32,%33,%34,%35}, dd, 0, 1, 1, 0; }"
                 : A16(d, 0), A16(d, 16) : "r"(a[0]), "r"(a[1]), "r"(a[2]), "r"(a[3]), "r"(lo), "r"(16));
}
__device__ __forceinline__ void wg_ss32(float* d, uint64_t da, uint64_t db) {
    asm volatile("wgmma.mma_async.sync.aligned.m64n32k16.f32.bf16.bf16 {%0,%1,%2,%3,%4,%5,%6,%7,%8,%9,%10,%11,%12,%13,%14,%15}, %16, %17, 1, 1, 1, 0, 1;"
                 : A16(d, 0) : "l"(da), "l"(db));
}
__device__ __forceinline__ void wg_ss16(float* d, uint64_t da, uint64_t db) {
    asm volatile("wgmma.mma_async.sync.aligned.m64n16k16.f32.bf16.bf16 {%0,%1,%2,%3,%4,%5,%6,%7}, %8, %9, 1, 1, 1, 0, 1;"
                 : A4(d, 0), A4(d, 4) : "l"(da), "l"(db));
}
template<int N> __device__ __forceinline__ void fence_regs(float* r) {
    #pragma unroll
    for (int i = 0; i < N; i++) asm volatile("" : "+f"(r[i]) :: "memory");
}
__device__ __forceinline__ void mma_f16(float* d, const uint32_t* a, uint32_t b0, uint32_t b1) {
    asm volatile("mma.sync.aligned.m16n8k16.row.col.f32.f16.f16.f32 {%0,%1,%2,%3}, {%4,%5,%6,%7}, {%8,%9}, {%0,%1,%2,%3};"
                 : "+f"(d[0]), "+f"(d[1]), "+f"(d[2]), "+f"(d[3]) : "r"(a[0]), "r"(a[1]), "r"(a[2]), "r"(a[3]), "r"(b0), "r"(b1));
}
__device__ __forceinline__ uint32_t lds32(uint32_t addr) { uint32_t v; asm volatile("ld.shared.u32 %0, [%1];" : "=r"(v) : "r"(addr) : "memory"); return v; }
__device__ __forceinline__ void mma_bf16_p(float* d, uint32_t a0, uint32_t a1, uint32_t a2, uint32_t a3, uint32_t b0, uint32_t b1) {
    asm("mma.sync.aligned.m16n8k16.row.col.f32.bf16.bf16.f32 {%0,%1,%2,%3}, {%4,%5,%6,%7}, {%8,%9}, {%0,%1,%2,%3};"
        : "+f"(d[0]), "+f"(d[1]), "+f"(d[2]), "+f"(d[3]) : "r"(a0), "r"(a1), "r"(a2), "r"(a3), "r"(b0), "r"(b1));
}
__device__ __forceinline__ void ldsm4_p(uint32_t* r, uint32_t addr) {
    asm("ldmatrix.sync.aligned.m8n8.x4.shared.b16 {%0,%1,%2,%3}, [%4];" : "=r"(r[0]), "=r"(r[1]), "=r"(r[2]), "=r"(r[3]) : "r"(addr));
}
__device__ __forceinline__ void ldsm4t_p(uint32_t* r, uint32_t addr) {
    asm("ldmatrix.sync.aligned.m8n8.x4.trans.shared.b16 {%0,%1,%2,%3}, [%4];" : "=r"(r[0]), "=r"(r[1]), "=r"(r[2]), "=r"(r[3]) : "r"(addr));
}
__device__ __forceinline__ uint32_t lds32_p(uint32_t addr) { uint32_t v; asm("ld.shared.u32 %0, [%1];" : "=r"(v) : "r"(addr)); return v; }
__device__ __forceinline__ uint32_t swz(uint32_t a) { return a ^ ((a >> 3) & 16u); }
__device__ __forceinline__ void sts32(uint32_t addr, uint32_t v) { asm volatile("st.shared.u32 [%0], %1;" :: "r"(addr), "r"(v) : "memory"); }
__device__ __forceinline__ void sts128(uint32_t addr, uint4 v) { asm volatile("st.shared.v4.u32 [%0], {%1,%2,%3,%4};" :: "r"(addr), "r"(v.x), "r"(v.y), "r"(v.z), "r"(v.w) : "memory"); }
__device__ __forceinline__ uint4 lds128(uint32_t addr) { uint4 v; asm volatile("ld.shared.v4.u32 {%0,%1,%2,%3}, [%4];" : "=r"(v.x), "=r"(v.y), "=r"(v.z), "=r"(v.w) : "r"(addr) : "memory"); return v; }
__device__ __forceinline__ float ex2f(float x) { float r; asm("ex2.approx.ftz.f32 %0, %1;" : "=f"(r) : "f"(x)); return r; }
__device__ __forceinline__ uint32_t pack_bf16(float lo, float hi) { uint32_t r; asm("cvt.rn.bf16x2.f32 %0, %1, %2;" : "=r"(r) : "f"(hi), "f"(lo)); return r; }
__device__ __forceinline__ uint32_t pack_f16(float lo, float hi) { uint32_t r; asm("cvt.rn.f16x2.f32 %0, %1, %2;" : "=r"(r) : "f"(hi), "f"(lo)); return r; }
__device__ __forceinline__ float bf_lo(uint32_t v) { return __uint_as_float(v << 16); }
__device__ __forceinline__ float bf_hi(uint32_t v) { return __uint_as_float(v & 0xFFFF0000u); }
__device__ __forceinline__ float bf_round(float x) { return __bfloat162float(__float2bfloat16_rn(x)); }

__device__ __forceinline__ uint32_t exp_mufu(float x0, float x1) { return pack_bf16(ex2f(x0), ex2f(x1)); }
#define SW_MAGIC (256.0f + 127.0f - 0.598938f)
__device__ __forceinline__ uint32_t exp_sw(float x0, float x1, uint32_t cA, uint32_t cB) {
    float t0 = x0 + SW_MAGIC, t1 = x1 + SW_MAGIC;
    uint32_t L, mh, ec, r;
    asm("prmt.b32 %0, %1, %2, 0x6521;" : "=r"(L) : "r"(__float_as_uint(t0)), "r"(__float_as_uint(t1)));
    asm("lop3.b32 %0, %1, 0x007F007F, %2, 0xEA;" : "=r"(mh) : "r"(L), "r"(cA));
    asm("lop3.b32 %0, %1, 0x7F807F80, %2, 0xEA;" : "=r"(ec) : "r"(L), "r"(cB));
    asm("fma.rn.bf16x2 %0, %1, %2, %3;" : "=r"(r) : "r"(L), "r"(mh), "r"(ec));
    return r;
}
constexpr uint32_t MUFU_MASK = 0x4949;

struct cf { float x, y; };
__device__ __forceinline__ cf cmul(cf a, cf b) { cf r; r.x = a.x * b.x - a.y * b.y; r.y = a.x * b.y + a.y * b.x; return r; }
__device__ __forceinline__ cf cexp_p(float a2, float b, float p) {
    float e = ex2f(a2 * p);
    float ph = b * p;
    ph -= (ph + 12582912.0f) - 12582912.0f;
    float ang = ph * 6.283185307f;
    cf r; r.x = e * __cosf(ang); r.y = e * __sinf(ang);
    return r;
}
__device__ __forceinline__ uint32_t h2_cmul(uint32_t w, uint32_t wsw, uint32_t e) {
    __half2 hw = *(__half2*)&w, hs = *(__half2*)&wsw, he = *(__half2*)&e;
    __half2 r = __hfma2(hs, __high2half2(he), __hmul2(hw, __low2half2(he)));
    return *(uint32_t*)&r;
}

template<bool B> struct BoolC { static constexpr bool value = B; };
struct Params {
    const __nv_bfloat16 *u, *lar, *aim, *cre, *cim, *logdt, *dskip;
    __nv_bfloat16* out;
};

constexpr int B_O = 0, B_KV = 8, B_WO = 12, B_WQ2 = 13, B_ST = 14, B_H = 15, B_X = 17, B_U = 19, B_WQ = 20;

__device__ __forceinline__ void helper_role(const Params& P, uint8_t* sp, uint32_t sb, unsigned epoch) {
    const uint32_t sBa = sb + SM_B;
    const int tid = threadIdx.x - 544;
    const int d0 = blockIdx.x * 4;
    uint8_t* sB = sp + SM_B;
    const uint2 dsk = __ldg((const uint2*)(P.dskip + d0));
    asm volatile("barrier.cluster.wait.aligned;" ::: "memory");
    {
        const int hg = blockIdx.x & 7;
        if (hg < 4 && tid < 32) {
            bar_sync(3, 160);
            if (tid == 0) {
                const float* s_misc = (const float*)(sp + SM_BAR + 256);
                const float st = fmaxf(fmaxf(s_misc[20], s_misc[21]), fmaxf(s_misc[22], s_misc[23]));
                st_release64(&g_flag_kv[((blockIdx.x >> 3) * 2 + (hg & 1)) * 2 + (hg >> 1)], ((unsigned long long)epoch << 32) | __float_as_uint(st));
            }
            __syncwarp();
        }
    }
    PROF2(2);
    bar_sync(10, 608);
    {
        uint32_t dd[4] = {__byte_perm(dsk.x, 0, 0x1010), __byte_perm(dsk.x, 0, 0x3232), __byte_perm(dsk.y, 0, 0x1010), __byte_perm(dsk.y, 0, 0x3232)};
        #pragma unroll 2
        for (int pi = tid; pi < 1024; pi += 96) {
            const int l = 2 * pi;
            uint32_t r[4];
            #pragma unroll
            for (int cc = 0; cc < 4; cc++) {
                const uint32_t y2 = *(const uint32_t*)(sB + S_Y + cc * 4096 + l * 2);
                const uint32_t u2 = lds32(swz(sBa + S_U + cc * ULEN * 2 + (PADU + l) * 2));
                __nv_bfloat162 pr = __hmul2(*(const __nv_bfloat162*)&u2, *(const __nv_bfloat162*)&dd[cc]);
                __nv_bfloat162 sm = __hadd2(*(const __nv_bfloat162*)&y2, pr);
                r[cc] = *(uint32_t*)&sm;
            }
            *(uint2*)(P.out + (size_t)l * 1024 + 512 + d0) = make_uint2(__byte_perm(r[0], r[1], 0x5410), __byte_perm(r[2], r[3], 0x5410));
            *(uint2*)(P.out + (size_t)(l + 1) * 1024 + 512 + d0) = make_uint2(__byte_perm(r[0], r[1], 0x7632), __byte_perm(r[2], r[3], 0x7632));
        }
    }
    bar_arrive(11, 128);
    PROF2(4);
}

__global__ void __cluster_dims__(2, 1, 1) __launch_bounds__(NTHR, 1)
fused_kernel(const __grid_constant__ CUtensorMap tm_x, const __grid_constant__ CUtensorMap tm_wq,
             const __grid_constant__ CUtensorMap tm_wo, const __grid_constant__ CUtensorMap tm_wk,
             const __grid_constant__ CUtensorMap tm_wv, const __grid_constant__ CUtensorMap tm_u, const Params P) {
    extern __shared__ uint8_t smem_raw[];
    const uint32_t sb = (smem_u32(smem_raw) + 1023u) & ~1023u;
    uint8_t* sp = smem_raw + (sb - smem_u32(smem_raw));

    const int tid = threadIdx.x, warp = tid >> 5, lane = tid & 31, wg = tid >> 7, wiw = warp & 3;
    const int g = lane >> 2, t = lane & 3;
    const int qb = blockIdx.x >> 3, hg = blockIdx.x & 7;
    const uint32_t rank = blockIdx.x & 1;
    const int rowhalf = wg & 1, nh = wg >> 1;
    const bool kv_cta = hg < 4;
    const int kv_sel = hg >> 1;
    const bool kv_wg = kv_cta && (wg == (hg & 1));

    const uint32_t bars = sb + SM_BAR;
    float* s_misc = (float*)(sp + SM_BAR + 256);
    const CUtensorMap* tm_kv = kv_sel ? &tm_wv : &tm_wk;

    PROF(0);
    unsigned short p_lar = 0, p_aim = 0, p_cre = 0, p_cim = 0, p_ldt = 0;
    if (wg < 4) {
        const int n = (blockIdx.x * 4 + wg) * 128 + (tid & 127);
        p_lar = __ldg((const unsigned short*)P.lar + n);
        p_aim = __ldg((const unsigned short*)P.aim + n);
        p_cre = __ldg((const unsigned short*)P.cre + n);
        p_cim = __ldg((const unsigned short*)P.cim + n);
        p_ldt = __ldg((const unsigned short*)P.logdt + blockIdx.x * 4 + wg);
    } else if (warp == 16) {
        PROF3(5);
        if (lane == 0) {
            asm volatile("prefetch.tensormap [%0];" :: "l"((uint64_t)&tm_x) : "memory");
            asm volatile("prefetch.tensormap [%0];" :: "l"((uint64_t)tm_kv) : "memory");
            asm volatile("prefetch.tensormap [%0];" :: "l"((uint64_t)&tm_wq) : "memory");
            asm volatile("prefetch.tensormap [%0];" :: "l"((uint64_t)&tm_u) : "memory");
            mbar_init(bars + 8 * B_X, 1);
            mbar_init(bars + 8 * B_X + 8, 1);
            mbar_init(bars + 8 * B_U, 1);
            asm volatile("fence.mbarrier_init.release.cluster;" ::: "memory");
            mbar_expect_tx(bars + 8 * B_X, 65536u + (kv_cta ? 8192u : 0u));
            mbar_expect_tx(bars + 8 * B_X + 8, 65536u + (kv_cta ? 8192u : 0u));
            mbar_expect_tx(bars + 8 * B_U, 32768u);
        }
        __syncwarp();
        PROF3(6);
    }
    asm volatile("barrier.cluster.arrive.relaxed.aligned;" ::: "memory");
    const unsigned epoch = *(volatile unsigned*)&g_epoch + 1u;
    if (warp > 16) {
        if (lane == 0) {
            for (int i = warp - 17; i < B_X; i += 3) {
                mbar_init(bars + 8 * i, i >= B_H ? 2 : 1);
                if (i <= B_WQ2) mbar_expect_tx(bars + 8 * i, i < B_KV + 2 ? 16384u : i == B_KV + 2 ? 32768u : i <= B_WO ? 65536u : 32768u);
            }
            asm volatile("fence.mbarrier_init.release.cluster;" ::: "memory");
            fence_async_smem();
        } else if (warp == 19) {
            asm volatile("prefetch.global.L2 [%0];" :: "l"((const char*)g_tabmap.v + (lane - 1) * 128));
            if (lane < 5) asm volatile("prefetch.global.L2 [%0];" :: "l"((const char*)g_tabmap.v + (lane + 30) * 128));
        }
        __syncwarp();
    }
    asm volatile("barrier.cluster.wait.aligned;" ::: "memory");
    PROF(5);
    if (warp == 16 && lane == 0) {
        tma_3d_mc(sb + (rank ? SM_A : SM_B), &tm_x, 0, qb * 128, rank * 4, bars + 8 * (B_X + rank));
        if (kv_cta) {
            #pragma unroll
            for (int i = 0; i < 4; i++) tma_2d(sb + SM_WKV + i * 4096, tm_kv, (i >> 1) * 8, (i & 1) * 256, bars + 8 * (B_X + (i & 1)));
        }
        mbar_init(bars + 8 * B_WQ, 1);
        asm volatile("fence.mbarrier_init.release.cluster;" ::: "memory");
        fence_async_smem();
        mbar_expect_tx(bars + 8 * B_WQ, 32768u);
        tma_2d(sb + SM_WQ, &tm_wq, hg * 64, 0, bars + 8 * B_WQ);
        #pragma unroll
        for (int i = 0; i < 4; i++) tma_2d_mc(sb + SM_SLAB + (rank * 4 + i) * 4096, &tm_u, (blockIdx.x >> 1) * 8, (rank * 4 + i) * 256, bars + 8 * B_U);
    }
    __syncwarp();
    asm volatile("barrier.cluster.arrive.relaxed.aligned;" ::: "memory");

    if (warp == 16) {
        if (lane == 0) asm volatile("prefetch.tensormap [%0];" :: "l"((uint64_t)&tm_wo) : "memory");
        asm volatile("barrier.cluster.wait.aligned;" ::: "memory");
        PROF3(10);
        bar_sync(13, 544);
        if (lane == 0) { fence_async_smem(); tma_2d(sb + SM_SLAB, &tm_wq, hg * 64, 256, bars + 8 * B_WQ2); }
        bar_sync(14, 544);
        if (lane == 0) pair_sync(bars + 8 * B_H, rank ^ 1);
        __syncwarp();
        PROF3(11);
        *(uint4*)(sp + SM_V + 32768 + lane * 32) = make_uint4(0x3F803F80u, 0x3F803F80u, 0x3F803F80u, 0x3F803F80u);
        *(uint4*)(sp + SM_V + 32768 + lane * 32 + 16) = make_uint4(0x3F803F80u, 0x3F803F80u, 0x3F803F80u, 0x3F803F80u);
        fence_async_smem();
        float km = wait_flag64(&g_flag_kv[2 * lane], epoch);
        float vm = wait_flag64(&g_flag_kv[2 * lane + 1], epoch);
        __syncwarp();
        PROF3(12);
        if (lane == 0) {
            fence_async_all();
            #pragma unroll
            for (int i = 0; i < 4; i++) {
                const uint32_t k0 = i == 0 ? 0 : 128u << i, nk = i == 0 ? 256 : 128u << i;
                const uint32_t bar = bars + 8 * (B_KV + i);
                if (rank == 0) bulk_g2s_mc(sb + SM_K + k0 * 32, g_kimg + k0 * 32, nk * 32, bar);
                else {
                    bulk_g2s_mc(sb + SM_V + k0 * 16, g_vimg + k0 * 16, nk * 16, bar);
                    bulk_g2s_mc(sb + SM_V + 66560 - (k0 + nk) * 16, g_vimg + 66560 - (k0 + nk) * 16, nk * 16, bar);
                }
            }
        }
        #pragma unroll
        for (int o = 16; o; o >>= 1) { km = fmaxf(km, __shfl_xor_sync(0xffffffffu, km, o)); vm = fmaxf(vm, __shfl_xor_sync(0xffffffffu, vm, o)); }
        if (lane == 0) { s_misc[16] = km; s_misc[17] = vm; mbar_arrive(bars + 8 * B_ST); }
        PROF3(13);
        bar_sync(11, 128);
        if (lane < 2) { fence_async_smem(); tma_2d(sb + SM_B + lane * 32768, &tm_wo, hg * 64, lane * 256, bars + 8 * B_WO); }
        bar_sync(12, 544);
        if (lane == 0) {
            st_release(&g_flag_o[blockIdx.x], epoch);
            pair_sync(bars + 8 * (B_H + 1), rank ^ 1);
        }
        __syncwarp();
        PROF3(14);
        if (lane < 4) {
            const int src = 2 * lane + rank;
            wait_flag(&g_flag_o[qb * 8 + src], epoch);
            fence_async_all();
            bulk_g2s_mc(sb + SM_A + src * 16384, g_oimg + qb * 131072 + src * 16384, 16384, bars + 8 * (B_O + src));
        }
        __syncwarp();
        PROF3(15);
        if (lane == 0) {
            const unsigned prev = atomicAdd(&g_done, 1u);
            if (prev == NCTA - 1) {
                g_done = 0;
                __threadfence();
                *(volatile unsigned*)&g_epoch = epoch;
            }
        }
    } else if (wg == 4) {
        helper_role(P, sp, sb, epoch);
    } else {
        uint8_t* sB = sp + SM_B;
        const uint32_t sBa = sb + SM_B;
        {
            const int c = wg;
            const float dt = bf_round(expf(bf_lo(p_ldt)));
            const float are = -bf_round(expf(bf_lo(p_lar))) * dt;
            const float aim = bf_lo(p_aim) * dt;
            float cr = 2.0f * (bf_lo(p_cre) * dt);
            float ci = 2.0f * (bf_lo(p_cim) * dt);
            const float a2 = are * 1.4426950408889634f, bb = aim * 0.15915494309189535f;
            float m = fmaxf(fabsf(cr), fabsf(ci));
            #pragma unroll
            for (int o = 16; o; o >>= 1) m = fmaxf(m, __shfl_xor_sync(0xffffffffu, m, o));
            int ebits = (__float_as_uint(m) >> 23) & 0xFF;
            ebits = min(max(ebits, 2), 250);
            const float scale = __uint_as_float((uint32_t)(ebits + 1) << 23);
            const float iscale = __uint_as_float((uint32_t)(253 - ebits) << 23);
            cf cc; cc.x = cr * iscale; cc.y = ci * iscale;

            const uint32_t stg = sBa + S_KC + warp * 1024;
            uint4* stp = (uint4*)(sB + S_KC + warp * 1024 + lane * 32);
            const uint32_t fa = stg + t * 32 + g * 4;

            uint32_t af[4][2][4];
            cf E256;
            {
                const cf E8 = cexp_p(a2, bb, 8.0f);
                uint32_t w[8];
                cf cur; cur.x = 1.0f; cur.y = 0.0f;
                w[0] = pack_f16(1.0f, 0.0f);
                cur = E8; w[1] = pack_f16(cur.x, cur.y);
                #pragma unroll
                for (int i = 2; i < 8; i++) { cur = cmul(cur, E8); w[i] = pack_f16(cur.x, cur.y); }
                stp[0] = make_uint4(w[0], w[1], w[2], w[3]);
                stp[1] = make_uint4(w[4], w[5], w[6], w[7]);
                const cf E64 = cexp_p(a2, bb, 64.0f);
                const cf E128 = cmul(E64, E64), E192 = cmul(E128, E64);
                E256 = cexp_p(a2, bb, 256.0f);
                const uint32_t e1 = pack_f16(E64.x, E64.y), e2 = pack_f16(E128.x, E128.y), e3 = pack_f16(E192.x, E192.y);
                __syncwarp();
                #pragma unroll
                for (int s = 0; s < 4; s++) {
                    #pragma unroll
                    for (int hh = 0; hh < 2; hh++) {
                        const uint32_t w0 = lds32(fa + s * 256 + hh * 128);
                        const uint32_t wsw = __byte_perm(w0, 0, 0x1032) ^ 0x00008000u;
                        const int src = 8 * s + t + 4 * hh;
                        const uint32_t f1 = __shfl_sync(0xffffffffu, e1, src), f2 = __shfl_sync(0xffffffffu, e2, src), f3 = __shfl_sync(0xffffffffu, e3, src);
                        af[s][0][2 * hh] = w0;
                        af[s][0][2 * hh + 1] = h2_cmul(w0, wsw, f1);
                        af[s][1][2 * hh] = h2_cmul(w0, wsw, f2);
                        af[s][1][2 * hh + 1] = h2_cmul(w0, wsw, f3);
                    }
                }
                __syncwarp();
            }
            float acc[2][3][4];
            #pragma unroll
            for (int i = 0; i < 24; i++) (&acc[0][0][0])[i] = 0.0f;
            const cf E1 = cexp_p(a2, bb, 1.0f);
            const cf E2 = cmul(E1, E1), E4 = cmul(E2, E2);
            cf X512;
            #pragma unroll
            for (int nt = 0; nt < 3; nt++) {
                uint32_t xv[8];
                if (nt == 0) {
                    cf cur = cc;
                    xv[0] = pack_f16(cur.x, -cur.y);
                    #pragma unroll
                    for (int i = 1; i < 8; i++) { cur = cmul(cur, E1); xv[i] = pack_f16(cur.x, -cur.y); }
                } else if (nt == 1) {
                    cf cur = cmul(cc, E256);
                    X512 = cmul(cur, E256);
                    xv[0] = pack_f16(cur.x, -cur.y);
                    #pragma unroll
                    for (int i = 1; i < 4; i++) { cur = cmul(cur, E2); xv[i] = pack_f16(cur.x, -cur.y); }
                    cur = cmul(X512, E4);
                    xv[4] = pack_f16(X512.x, -X512.y); xv[5] = pack_f16(cur.x, -cur.y);
                    X512 = cmul(X512, E256);
                    cur = cmul(X512, E4);
                    xv[6] = pack_f16(X512.x, -X512.y); xv[7] = pack_f16(cur.x, -cur.y);
                } else {
                    cf cur = X512;
                    #pragma unroll
                    for (int i = 0; i < 5; i++) { cur = cmul(cur, E256); xv[i] = pack_f16(cur.x, -cur.y); }
                    xv[5] = 0; xv[6] = 0; xv[7] = 0;
                }
                stp[0] = make_uint4(xv[0], xv[1], xv[2], xv[3]);
                stp[1] = make_uint4(xv[4], xv[5], xv[6], xv[7]);
                __syncwarp();
                #pragma unroll
                for (int s = 0; s < 4; s++) {
                    const uint32_t b0 = lds32(fa + s * 256), b1 = lds32(fa + s * 256 + 128);
                    mma_f16(acc[0][nt], af[s][0], b0, b1);
                    mma_f16(acc[1][nt], af[s][1], b0, b1);
                }
                __syncwarp();
            }
            float* kc = (float*)(sB + S_KC + c * 4096);
            bar_sync(4 + c, 128);
            #pragma unroll 1
            for (int step = 0; step < 4; step++) {
                if ((warp & 3) == step) {
                    #pragma unroll
                    for (int mt = 0; mt < 2; mt++)
                        #pragma unroll
                        for (int nt = 0; nt < 3; nt++)
                            #pragma unroll
                            for (int hh = 0; hh < 2; hh++) {
                                float2* p = (float2*)(kc + (mt * 16 + hh * 8 + g) * 24 + nt * 8 + 2 * t);
                                float2 v = make_float2(acc[mt][nt][2 * hh] * scale, acc[mt][nt][2 * hh + 1] * scale);
                                if (step) { float2 o = *p; v.x += o.x; v.y += o.y; }
                                *p = v;
                            }
                }
                if (step < 3) bar_sync(4 + c, 128);
            }
        }

        asm volatile("barrier.cluster.wait.aligned;" ::: "memory");
        PROF(4);
        uint32_t q[2][4];
        {
            float acc[16], akv[8];
            #pragma unroll
            for (int i = 0; i < 16; i++) acc[i] = 0.0f;
            #pragma unroll
            for (int i = 0; i < 8; i++) akv[i] = 0.0f;
            fence_regs<16>(acc);
            fence_regs<8>(akv);
            const uint64_t dA0 = make_desc(sb + SM_B + rowhalf * 8192, 16, 1024, 1);
            const uint64_t dA1 = make_desc(sb + SM_A + rowhalf * 8192, 16, 1024, 1) - 4096;
            const uint64_t dB = make_desc(sb + SM_WQ + nh * 64, 16, 1024, 1);
            const uint64_t dC = make_desc(sb + SM_WKV, 128, 8192, 0);
            if (kv_wg) {
                #pragma unroll 1
                for (int ch = 0; ch < 8; ch++) {
                    if ((ch & 3) == 0) mbar_wait(bars + 8 * (B_X + (ch >> 2)), 0);
                    const uint64_t dA = ch < 4 ? dA0 : dA1;
                    wg_fence();
                    #pragma unroll
                    for (int ks = 0; ks < 4; ks++) wg_ss16(akv, dA + ch * 1024 + ks * 2, dC + (ch * 4 + ks) * 16);
                    wg_commit();
                }
                wg_wait<0>();
            }
            fence_regs<8>(akv);
            if (kv_wg) {
                const int key = qb * 128 + rowhalf * 64 + wiw * 16 + g;
                uint32_t pk[4];
                #pragma unroll
                for (int i = 0; i < 4; i++) pk[i] = pack_bf16(akv[2 * i], akv[2 * i + 1]);
                float st;
                if (kv_sel == 0) {
                    uint8_t* b = g_kimg + (key >> 3) * 256 + (key & 7) * 16 + 4 * t;
                    *(uint32_t*)(b) = pk[0]; *(uint32_t*)(b + 256) = pk[1]; *(uint32_t*)(b + 128) = pk[2]; *(uint32_t*)(b + 384) = pk[3];
                    float n0 = bf_lo(pk[0]) * bf_lo(pk[0]) + bf_hi(pk[0]) * bf_hi(pk[0]) + bf_lo(pk[2]) * bf_lo(pk[2]) + bf_hi(pk[2]) * bf_hi(pk[2]);
                    float n1 = bf_lo(pk[1]) * bf_lo(pk[1]) + bf_hi(pk[1]) * bf_hi(pk[1]) + bf_lo(pk[3]) * bf_lo(pk[3]) + bf_hi(pk[3]) * bf_hi(pk[3]);
                    n0 += __shfl_xor_sync(0xffffffffu, n0, 1); n0 += __shfl_xor_sync(0xffffffffu, n0, 2);
                    n1 += __shfl_xor_sync(0xffffffffu, n1, 1); n1 += __shfl_xor_sync(0xffffffffu, n1, 2);
                    st = (n0 != n0 || n1 != n1) ? __int_as_float(0x7f800000) : fmaxf(n0, n1);
                } else {
                    uint8_t* lo = g_vimg + key * 16 + 4 * t;
                    uint8_t* hi = g_vimg + 33792 + (31 - (key >> 6)) * 1024 + (key & 63) * 16 + 4 * t;
                    *(uint32_t*)(lo) = pk[0]; *(uint32_t*)(lo + 128) = pk[1]; *(uint32_t*)(hi) = pk[2]; *(uint32_t*)(hi + 128) = pk[3];
                    st = 0.0f;
                    #pragma unroll
                    for (int i = 0; i < 4; i++) {
                        float a = fabsf(bf_lo(pk[i])), b = fabsf(bf_hi(pk[i]));
                        st = (a != a || b != b) ? __int_as_float(0x7f800000) : fmaxf(st, fmaxf(a, b));
                    }
                }
                #pragma unroll
                for (int o = 16; o; o >>= 1) st = fmaxf(st, __shfl_xor_sync(0xffffffffu, st, o));
                if (lane == 0) s_misc[20 + wiw] = st;
                bar_arrive(3, 160);
            }
            uint32_t mp[9];
            #pragma unroll
            for (int i = 0; i < 9; i++) { const int w = (tid & 127) + 128 * i; mp[i] = (w < TABN / 2) ? __ldg((const uint32_t*)g_tabmap.v + w) : 0u; }
            mbar_wait(bars + 8 * B_WQ, 0);
            mbar_wait(bars + 8 * B_X, 0);
            PROF(2);
            #pragma unroll 1
            for (int ch = 0; ch < 4; ch++) {
                wg_fence();
                #pragma unroll
                for (int ks = 0; ks < 4; ks++) wg_ss32(acc, dA0 + ch * 1024 + ks * 2, dB + (ch * 4 + ks) * 128);
                wg_commit();
            }
            wg_wait<0>();
            fence_regs<16>(acc);
            bar_sync(1, 512);
            PROF(15);
            if (tid < 4 * (PADU / 8)) sts128(swz(sBa + S_U + (tid / (PADU / 8)) * ULEN * 2 + (tid % (PADU / 8)) * 16), make_uint4(0, 0, 0, 0));
            PROF(8);
            mbar_wait(bars + 8 * B_U, 0);
            PROF(14);
            #pragma unroll
            for (int i = 0; i < 2; i++) {
                const int l = 2 * (tid + 512 * i);
                const uint2 r0 = *(const uint2*)(sp + SM_SLAB + l * 16 + rank * 8), r1 = *(const uint2*)(sp + SM_SLAB + l * 16 + 16 + rank * 8);
                const uint32_t dst = sBa + S_U + (PADU + l) * 2;
                sts32(swz(dst), __byte_perm(r0.x, r1.x, 0x5410));
                sts32(swz(dst + ULEN * 2), __byte_perm(r0.x, r1.x, 0x7632));
                sts32(swz(dst + ULEN * 4), __byte_perm(r0.y, r1.y, 0x5410));
                sts32(swz(dst + ULEN * 6), __byte_perm(r0.y, r1.y, 0x7632));
            }
            bar_arrive(13, 544);
            {
                const float* kc = (const float*)(sB + S_KC + wg * 4096);
                uint32_t* tab = (uint32_t*)(sB + S_TAB + wg * TABN * 2);
                #pragma unroll
                for (int i = 0; i < 9; i++) { const int w = (tid & 127) + 128 * i; if (w < TABN / 2) tab[w] = pack_bf16(kc[mp[i] & 0xFFFF], kc[mp[i] >> 16]); }
            }
            PROF(1);
            mbar_wait(bars + 8 * B_WQ2, 0);
            mbar_wait(bars + 8 * (B_X + 1), 0);
            fence_regs<16>(acc);
            #pragma unroll 1
            for (int ch = 4; ch < 8; ch++) {
                wg_fence();
                #pragma unroll
                for (int ks = 0; ks < 4; ks++) wg_ss32(acc, dA1 + ch * 1024 + ks * 2, dB + (ch * 4 + ks) * 128);
                wg_commit();
            }
            wg_wait<0>();
            fence_regs<16>(acc);
            bar_arrive(14, 544);
            const float QS = 0.25f * 1.4426950408889634f;
            float qm = 0.0f;
            #pragma unroll
            for (int i = 0; i < 2; i++) {
                #pragma unroll
                for (int j = 0; j < 4; j++) q[i][j] = pack_bf16(acc[8 * i + 2 * j] * QS, acc[8 * i + 2 * j + 1] * QS);
                float n0 = bf_lo(q[i][0]) * bf_lo(q[i][0]) + bf_hi(q[i][0]) * bf_hi(q[i][0]) + bf_lo(q[i][2]) * bf_lo(q[i][2]) + bf_hi(q[i][2]) * bf_hi(q[i][2]);
                float n1 = bf_lo(q[i][1]) * bf_lo(q[i][1]) + bf_hi(q[i][1]) * bf_hi(q[i][1]) + bf_lo(q[i][3]) * bf_lo(q[i][3]) + bf_hi(q[i][3]) * bf_hi(q[i][3]);
                n0 += __shfl_xor_sync(0xffffffffu, n0, 1); n0 += __shfl_xor_sync(0xffffffffu, n0, 2);
                n1 += __shfl_xor_sync(0xffffffffu, n1, 1); n1 += __shfl_xor_sync(0xffffffffu, n1, 2);
                qm = (n0 != n0 || n1 != n1) ? __int_as_float(0x7f800000) : fmaxf(qm, fmaxf(n0, n1));
            }
            #pragma unroll
            for (int o = 16; o; o >>= 1) qm = fmaxf(qm, __shfl_xor_sync(0xffffffffu, qm, o));
            if (lane == 0) s_misc[warp] = qm;
        }
        PROF(3);
        bar_sync(1, 512);
        #pragma unroll 1
        for (int task = tid; task < 4 * 194; task += 512) {
            const int c = task / 194, i = task % 194;
            const uint32_t src = sBa + S_U + c * ULEN * 2 + (PADU + 8 * i - WPAD - 8) * 2;
            const uint4 v0 = lds128(swz(src)), v1 = lds128(swz(src + 16)), v2 = lds128(swz(src + 32));
            float x[24];
            const uint32_t vv[12] = {v0.x, v0.y, v0.z, v0.w, v1.x, v1.y, v1.z, v1.w, v2.x, v2.y, v2.z, v2.w};
            #pragma unroll
            for (int k = 0; k < 12; k++) { x[2 * k] = bf_lo(vv[k]); x[2 * k + 1] = bf_hi(vv[k]); }
            float w3[12], w5[8];
            #pragma unroll
            for (int e = 0; e < 12; e++) w3[e] = (x[3 + e] + x[4 + e]) + x[5 + e];
            #pragma unroll
            for (int e = 0; e < 8; e++) w5[e] = w3[4 + e] + (x[6 + e] + x[10 + e]);
            sts128(swz(sBa + S_W3 + c * W2LEN * 2 + i * 16), make_uint4(pack_bf16(w3[0], w3[1]), pack_bf16(w3[2], w3[3]), pack_bf16(w3[4], w3[5]), pack_bf16(w3[6], w3[7])));
            sts128(swz(sBa + S_W5 + c * W2LEN * 2 + i * 16), make_uint4(pack_bf16(w5[0], w5[1]), pack_bf16(w5[2], w5[3]), pack_bf16(w5[4], w5[5]), pack_bf16(w5[6], w5[7])));
            if (i < 130) {
                float w7[8], w9[8];
                #pragma unroll
                for (int e = 0; e < 8; e++) { w7[e] = w5[e] + (x[5 + e] + x[11 + e]); w9[e] = w7[e] + (x[4 + e] + x[12 + e]); }
                sts128(swz(sBa + S_W7 + c * W3LEN * 2 + i * 16), make_uint4(pack_bf16(w7[0], w7[1]), pack_bf16(w7[2], w7[3]), pack_bf16(w7[4], w7[5]), pack_bf16(w7[6], w7[7])));
                sts128(swz(sBa + S_W9 + c * W3LEN * 2 + i * 16), make_uint4(pack_bf16(w9[0], w9[1]), pack_bf16(w9[2], w9[3]), pack_bf16(w9[4], w9[5]), pack_bf16(w9[6], w9[7])));
            }
        }
        bar_sync(1, 512);
        PROF(6);
        if ((wg & 1) == 0) {
            const int c = wiw, hf = nh;
            uint32_t sBl = sBa;
            asm volatile("" : "+r"(sBl) :: "memory");
            float acc[8][4];
            #pragma unroll
            for (int i = 0; i < 32; i++) (&acc[0][0])[i] = 0.0f;
            const uint32_t tabc = sBl + S_TAB + c * TABN * 2;
            const int e2 = (g - 2 * t) * 2;
            const int mi = lane >> 3, r8 = lane & 7;
            const uint32_t frag = (16 * (8 * (mi >> 1) + r8) + 8 * (mi & 1)) * 2;
            const uint32_t ub = sBl + S_U + c * ULEN * 2 + PADU * 2 + frag;
            {
                const uint32_t tD = tabc + ((g & 1) ? (TD1 + CD + 1) : (TD0 + CD)) * 2 - e2;
                #pragma unroll 1
                for (int rho = 0; rho < 8; rho++) {
                    uint32_t R[5][3];
                    const uint32_t base = swz(ub - rho * 32) + hf * 2048;
                    #pragma unroll
                    for (int qq = 0; qq < 5; qq++) {
                        const uint32_t a = tD - 32 * ((qq < 4 || rho < 2) ? rho + 8 * qq : 0);
                        R[qq][0] = lds32_p(a + 16); R[qq][1] = lds32_p(a); R[qq][2] = lds32_p(a - 16);
                    }
                    #pragma unroll
                    for (int jp = 3; jp >= -2; jp--) {
                        if (jp < 0 && hf == 0 && (jp == -2 || rho > 0)) continue;
                        uint32_t b[4];
                        ldsm4_p(b, base + jp * 512);
                        #pragma unroll
                        for (int qq = 0; qq < 4; qq++)
                            #pragma unroll
                            for (int hh = 0; hh < 2; hh++) {
                                const int j = 2 * jp + hh + qq;
                                if (j >= 0 && j < 8) mma_bf16_p(acc[j], R[qq][1], R[qq][2], R[qq][0], R[qq][1], b[2 * hh], b[2 * hh + 1]);
                            }
                        if (rho < 2 && jp < 2) {
                            mma_bf16_p(acc[2 * jp + 4], R[4][1], R[4][2], R[4][0], R[4][1], b[0], b[1]);
                            mma_bf16_p(acc[2 * jp + 5], R[4][1], R[4][2], R[4][0], R[4][1], b[2], b[3]);
                        }
                    }
                }
            }
            {
                const uint32_t t2 = tabc + (T2B + ((g & 1) ? (T2C + C2 + 1) : C2)) * 2 - e2;
                #pragma unroll 1
                for (int s = 0; s < 4; s++) {
                    const uint32_t sig = swz(sBl + ((s & 1) ? S_W3 : S_W5) + c * W2LEN * 2 + WPAD * 2 + frag - ((s == 0) ? 32 : (s == 1) ? 0 : 16)) + hf * 2048;
                    uint32_t R[7];
                    #pragma unroll
                    for (int i = 0; i < 7; i++) R[i] = lds32_p(t2 + s * (T2S * 2) - 16 * (3 + i));
                    #pragma unroll
                    for (int be = 1; be >= -4; be--) {
                        if (be < 0 && hf == 0) continue;
                        uint32_t a[4];
                        ldsm4t_p(a, sig + be * 512);
                        #pragma unroll
                        for (int h = 4; h <= 9; h++) {
                            const int j = h + 2 * be;
                            if (j >= 0 && j < 8) mma_bf16_p(acc[j], a[0], a[1], a[2], a[3], R[h - 3], R[h - 4]);
                        }
                    }
                }
            }
            if (hf) {
                {
                    const uint32_t tE = tabc + ((g & 1) ? (TE1 + CE + 1) : (TE0 + CE)) * 2 - e2;
                    uint32_t R[5];
                    #pragma unroll
                    for (int i = 0; i < 5; i++) R[i] = lds32_p(tE - 16 * (127 + i));
                    #pragma unroll
                    for (int kk = 0; kk < 2; kk++) {
                        #pragma unroll
                        for (int jp = 0; jp < 4; jp++) {
                            uint32_t b[4];
                            ldsm4_p(b, swz(ub - kk * 32) + jp * 512);
                            mma_bf16_p(acc[2 * jp], R[2 * kk + 1], R[2 * kk + 2], R[2 * kk], R[2 * kk + 1], b[0], b[1]);
                            mma_bf16_p(acc[2 * jp + 1], R[2 * kk + 1], R[2 * kk + 2], R[2 * kk], R[2 * kk + 1], b[2], b[3]);
                        }
                    }
                }
                const uint32_t t3 = tabc + (T3B + ((g & 1) ? (T3C + C3 + 1) : C3)) * 2 - e2;
                #pragma unroll 1
                for (int s = 0; s < 2; s++) {
                    const uint32_t sig = swz(sBl + (s ? S_W7 : S_W9) + c * W3LEN * 2 + WPAD * 2 + frag - (s ? 16 : 32));
                    uint32_t R[9];
                    #pragma unroll
                    for (int i = 0; i < 9; i++) R[i] = lds32_p(t3 + s * (T3S * 2) - 16 * (7 + i));
                    #pragma unroll
                    for (int b = 0; b < 4; b++) {
                        uint32_t a[4];
                        ldsm4t_p(a, sig + b * 512);
                        #pragma unroll
                        for (int h = 8; h <= 15; h++)
                            if (h + 2 * b < 16) mma_bf16_p(acc[h + 2 * b - 8], a[0], a[1], a[2], a[3], R[h - 7], R[h - 8]);
                    }
                }
            }
            __nv_bfloat16* ys = (__nv_bfloat16*)(sB + S_Y + c * 4096) + 32 * t + g + hf * 1024;
            #pragma unroll
            for (int j = 0; j < 8; j++) {
                ys[128 * j] = __float2bfloat16_rn(acc[j][0]);
                ys[128 * j + 16] = __float2bfloat16_rn(acc[j][1]);
                ys[128 * j + 8] = __float2bfloat16_rn(acc[j][2]);
                ys[128 * j + 24] = __float2bfloat16_rn(acc[j][3]);
            }
        }
        bar_sync(1, 512);
        bar_arrive(10, 608);
        PROF(7);
        {
            mbar_wait(bars + 8 * B_ST, 0);
            PROF(9); PROFC(8);
            float qm = 0.0f;
            #pragma unroll
            for (int i = 0; i < 16; i++) qm = fmaxf(qm, s_misc[i]);
            const float vm = s_misc[17];
            const bool fast = (qm * s_misc[16] <= 60.0f * 60.0f) && (vm <= 1.0e12f) && (vm >= 1.0e-12f || vm == 0.0f);
            uint8_t* ob = g_oimg + qb * 131072 + hg * 16384 + nh * 8192 + (rowhalf * 8 + wiw * 2) * 128 + g * 16 + 4 * t;
            uint32_t cA = 0xBF00BF00u, cB = 0x00030003u;
            asm volatile("" : "+r"(cA), "+r"(cB));
            #pragma unroll 1
            for (int tile = 0; tile < 2; tile++) {
                uint32_t kLo = (((sb + SM_K) & 0x3FFFF) >> 4) | (8u << 16), vLo = (((sb + SM_V) & 0x3FFFF) >> 4) | (8u << 16), vHi = 2048;
                float o[12], s[32];
                uint32_t p[16], qq[4];
                #pragma unroll
                for (int i = 0; i < 4; i++) { qq[i] = tile ? q[1][i] : q[0][i]; asm volatile("" : "+r"(qq[i])); }
                #pragma unroll
                for (int i = 0; i < 12; i++) o[i] = 0.0f;
                #pragma unroll
                for (int i = 0; i < 32; i++) s[i] = 0.0f;
                fence_regs<12>(o);
                fence_regs<32>(s);
                if (fast) {
                    #pragma unroll 1
                    for (int c = 0; c < SEQ / 256; c++) {
                        if (c <= 4) mbar_wait(bars + 8 * (B_KV + (c < 2 ? c : c < 4 ? 2 : 3)), 0);
                        wg_fence();
                        wg_qk(s, qq, kLo);
                        wg_commit();
                        #pragma unroll
                        for (int u = 0; u < 4; u++) {
                            wg_wait<0>();
                            fence_regs<32>(s);
                            #pragma unroll
                            for (int i = 0; i < 16; i++) {
                                if ((MUFU_MASK >> i) & 1) p[i] = exp_mufu(s[2 * i], s[2 * i + 1]);
                                else p[i] = exp_sw(s[2 * i], s[2 * i + 1], cA, cB);
                            }
                            wg_fence();
                            if (u + 1 < 4) wg_qk(s, qq, kLo + (u + 1) * 128);
                            #pragma unroll
                            for (int kk = 0; kk < 4; kk++) wg_pv(o, p + 4 * kk, vLo + u * 64 + kk * 16, vHi - u * 64);
                            wg_commit();
                        }
                        kLo += 512; vLo += 256; vHi -= 256;
                    }
                    wg_wait<0>();
                } else {
                    float mx0 = -INFINITY, mx1 = -INFINITY;
                    #pragma unroll 1
                    for (int c = 0; c < SEQ / 64; c++) {
                        if (c <= 16) mbar_wait(bars + 8 * (B_KV + (c < 8 ? (c >> 2) : c < 16 ? 2 : 3)), 0);
                        wg_fence();
                        wg_qk(s, qq, kLo);
                        wg_commit();
                        wg_wait<0>();
                        fence_regs<32>(s);
                        fence_regs<12>(o);
                        float m0 = mx0, m1 = mx1;
                        #pragma unroll
                        for (int j = 0; j < 8; j++) {
                            m0 = fmaxf(m0, fmaxf(s[4 * j], s[4 * j + 1]));
                            m1 = fmaxf(m1, fmaxf(s[4 * j + 2], s[4 * j + 3]));
                        }
                        m0 = fmaxf(m0, __shfl_xor_sync(0xffffffffu, m0, 1)); m0 = fmaxf(m0, __shfl_xor_sync(0xffffffffu, m0, 2));
                        m1 = fmaxf(m1, __shfl_xor_sync(0xffffffffu, m1, 1)); m1 = fmaxf(m1, __shfl_xor_sync(0xffffffffu, m1, 2));
                        const float c0 = ex2f(mx0 - m0), c1 = ex2f(mx1 - m1);
                        mx0 = m0; mx1 = m1;
                        #pragma unroll
                        for (int j = 0; j < 3; j++) { o[4 * j] *= c0; o[4 * j + 1] *= c0; o[4 * j + 2] *= c1; o[4 * j + 3] *= c1; }
                        #pragma unroll
                        for (int j = 0; j < 8; j++) {
                            p[2 * j] = exp_mufu(s[4 * j] - m0, s[4 * j + 1] - m0);
                            p[2 * j + 1] = exp_mufu(s[4 * j + 2] - m1, s[4 * j + 3] - m1);
                        }
                        wg_fence();
                        #pragma unroll
                        for (int kk = 0; kk < 4; kk++) wg_pv(o, p + 4 * kk, vLo + kk * 16, vHi);
                        wg_commit();
                        wg_wait<0>();
                        kLo += 128; vLo += 64; vHi -= 64;
                    }
                }
                fence_regs<12>(o);
                if (tile == 0) PROFC(3);
                const float i0 = 1.0f / o[4], i1 = 1.0f / o[6];
                uint8_t* b = ob + tile * 4096;
                *(uint32_t*)(b) = pack_bf16(o[0] * i0, o[1] * i0);
                *(uint32_t*)(b + 128) = pack_bf16(o[2] * i1, o[3] * i1);
                *(uint32_t*)(b + 2048) = pack_bf16(o[8] * i0, o[9] * i0);
                *(uint32_t*)(b + 2048 + 128) = pack_bf16(o[10] * i1, o[11] * i1);
            }
        }
        PROF(10); PROFC(9);
        bar_arrive(12, 544);

        {
            float acc[16];
            #pragma unroll
            for (int i = 0; i < 16; i++) acc[i] = 0.0f;
            fence_regs<16>(acc);
            const uint64_t dA = make_desc(sb + SM_A + rowhalf * 1024, 2048, 128, 0);
            const uint64_t dB = make_desc(sb + SM_B + nh * 64, 16, 1024, 1);
            mbar_wait(bars + 8 * B_WO, 0);
            #pragma unroll 1
            for (int i = 0; i < 8; i++) {
                const int src = (hg + i) & 7;
                mbar_wait(bars + 8 * (B_O + src), 0);
                wg_fence();
                #pragma unroll
                for (int kk = 0; kk < 4; kk++) wg_ss32(acc, dA + src * 1024 + kk * 256, dB + (src * 4 + kk) * 128);
                wg_commit();
            }
            wg_wait<0>();
            fence_regs<16>(acc);
            PROF(12);
            const int row = qb * 128 + rowhalf * 64 + wiw * 16 + g;
            uint32_t* o32 = (uint32_t*)(P.out + (size_t)row * 1024 + hg * 64 + nh * 32 + 2 * t);
            #pragma unroll
            for (int j = 0; j < 4; j++) {
                o32[4 * j] = pack_bf16(acc[4 * j], acc[4 * j + 1]);
                o32[4 * j + 8 * 512] = pack_bf16(acc[4 * j + 2], acc[4 * j + 3]);
            }
        }
        PROF(13);
    }
}

typedef CUresult (*EncodeFn)(CUtensorMap*, CUtensorMapDataType, cuuint32_t, void*, const cuuint64_t*, const cuuint64_t*,
                             const cuuint32_t*, const cuuint32_t*, CUtensorMapInterleave, CUtensorMapSwizzle,
                             CUtensorMapL2promotion, CUtensorMapFloatOOBfill);

void make_map(EncodeFn fn, CUtensorMap* m, const void* ptr, uint64_t inner, uint64_t outer, uint32_t box_in, uint32_t box_out, CUtensorMapSwizzle swz) {
    cuuint64_t dims[2] = {inner, outer};
    cuuint64_t strides[1] = {inner * 2};
    cuuint32_t box[2] = {box_in, box_out};
    cuuint32_t es[2] = {1, 1};
    fn(m, CU_TENSOR_MAP_DATA_TYPE_BFLOAT16, 2, const_cast<void*>(ptr), dims, strides, box, es, CU_TENSOR_MAP_INTERLEAVE_NONE, swz,
       CU_TENSOR_MAP_L2_PROMOTION_L2_128B, CU_TENSOR_MAP_FLOAT_OOB_FILL_NONE);
}

}

extern "C" void kernel_launch(void* const* d_in, const int* in_sizes, int n_in, void* d_out, int out_size) {
    (void)in_sizes; (void)n_in; (void)out_size;
    static EncodeFn fn = nullptr;
    if (!fn) {
        void* p = nullptr;
        cudaDriverEntryPointQueryResult qr;
        cudaGetDriverEntryPoint("cuTensorMapEncodeTiled", &p, cudaEnableDefault, &qr);
        fn = (EncodeFn)p;
        cudaFuncSetAttribute(fused_kernel, cudaFuncAttributeMaxDynamicSharedMemorySize, SM_ALLOC);
    }
    CUtensorMap tx, twq, two, twk, twv, tu;
    {
        cuuint64_t dims[3] = {64, 2048, 8};
        cuuint64_t strides[2] = {1024, 128};
        cuuint32_t box[3] = {64, 128, 4};
        cuuint32_t es[3] = {1, 1, 1};
        fn(&tx, CU_TENSOR_MAP_DATA_TYPE_BFLOAT16, 3, d_in[0], dims, strides, box, es, CU_TENSOR_MAP_INTERLEAVE_NONE, CU_TENSOR_MAP_SWIZZLE_128B,
           CU_TENSOR_MAP_L2_PROMOTION_L2_128B, CU_TENSOR_MAP_FLOAT_OOB_FILL_NONE);
    }
    make_map(fn, &tu, d_in[5], 512, 2048, 8, 256, CU_TENSOR_MAP_SWIZZLE_NONE);
    make_map(fn, &twq, d_in[1], 512, 512, 64, 256, CU_TENSOR_MAP_SWIZZLE_128B);
    make_map(fn, &twk, d_in[2], 16, 512, 8, 256, CU_TENSOR_MAP_SWIZZLE_NONE);
    make_map(fn, &twv, d_in[3], 16, 512, 8, 256, CU_TENSOR_MAP_SWIZZLE_NONE);
    make_map(fn, &two, d_in[4], 512, 512, 64, 256, CU_TENSOR_MAP_SWIZZLE_128B);
    Params P;
    P.u = (const __nv_bfloat16*)d_in[5];
    P.lar = (const __nv_bfloat16*)d_in[6];
    P.aim = (const __nv_bfloat16*)d_in[7];
    P.cre = (const __nv_bfloat16*)d_in[8];
    P.cim = (const __nv_bfloat16*)d_in[9];
    P.logdt = (const __nv_bfloat16*)d_in[10];
    P.dskip = (const __nv_bfloat16*)d_in[11];
    P.out = (__nv_bfloat16*)d_out;
    fused_kernel<<<NCTA, NTHR, SM_ALLOC>>>(tx, twq, two, twk, twv, tu, P);
}
```

```cpp
#include <cuda_runtime.h>
#include <cuda_bf16.h>
#include <cuda_fp16.h>
#include <cuda.h>
#include <stdint.h>

namespace {

constexpr int SEQ = 2048;
constexpr int NCTA = 128, NTHR = 640;

constexpr int SM_A = 0;
constexpr int SM_WQ = 65536;
constexpr int SM_SLAB = SM_WQ + 32768;
constexpr int SM_K = 0, SM_V = 65536;
constexpr int SM_B = 132096;
constexpr int SM_WKV = SM_B + 65536;

constexpr int PADU = 288, ULEN = PADU + 2048;
constexpr int WPAD = 16, W2LEN = WPAD + 1536, W3LEN = WPAD + 1024;
constexpr int TABN = 2240;
constexpr int S_U = 0;
constexpr int S_W3 = S_U + 4 * ULEN * 2;
constexpr int S_W5 = S_W3 + 4 * W2LEN * 2;
constexpr int S_W7 = S_W5 + 4 * W2LEN * 2;
constexpr int S_W9 = S_W7 + 4 * W3LEN * 2;
constexpr int S_TAB = S_W9 + 4 * W3LEN * 2;
constexpr int S_KC = 214016 - SM_B;
constexpr int S_Y = S_KC;
constexpr int SM_BAR = SM_B + S_KC + 16384;
constexpr int SM_TOTAL = SM_BAR + 1024;
constexpr int SM_ALLOC = SM_TOTAL + 1024;
static_assert(SM_V + 65536 + 1024 <= SM_B && SM_ALLOC <= 232448 && S_TAB + 4 * TABN * 2 <= S_KC && SM_WKV + 16384 <= SM_B + S_KC, "smem map");

constexpr int TD0 = 0, TD1 = 560, CD = 544;
constexpr int TE0 = 1120, TE1 = 1168, CE = 1056;
constexpr int T2B = 1216, T2S = 160, T2C = 80, C2 = 80;
constexpr int T3B = 1856, T3S = 192, T3C = 96, C3 = 144;

constexpr int rne8(int t) {
    if (t < 256) return t;
    int sh = 0;
    while ((t >> sh) >= 256) sh++;
    int q = t >> sh, rem = t & ((1 << sh) - 1), half = 1 << (sh - 1);
    if (rem > half || (rem == half && (q & 1))) q++;
    return q << sh;
}
constexpr int kcidx(int p) {
    if (p < 256) return (p >> 3) * 24 + (p & 7);
    if (p < 512) return ((p - 256) >> 3) * 24 + 8 + (((p - 256) & 7) >> 1);
    if (p < 1024) { int q = p - 512, hi = q >> 8, rem = q & 255; return (rem >> 3) * 24 + 12 + 2 * hi + ((rem & 7) >> 2); }
    if (p < 2048) { int q = p - 1024; return ((q & 255) >> 3) * 24 + 16 + (q >> 8); }
    return 20;
}
constexpr int KC_ZERO = 23;
constexpr int tab_dense(int t) { return (t >= 0 && t <= 514) ? kcidx(rne8(t)) : KC_ZERO; }
constexpr int tab_extra(int t) { return (t >= 1027 && t <= 1028) ? kcidx(1024) : KC_ZERO; }
constexpr int tab_2(int s, int lag) { return (lag >= 32 && lag <= 63) ? kcidx(s == 0 ? 16 * (lag + 1) : 16 * lag + 4 * s) : KC_ZERO; }
constexpr int tab_3(int s, int lag) { return (lag >= 64 && lag <= 127) ? kcidx(s == 0 ? 16 * (lag + 1) : 16 * lag + 8) : KC_ZERO; }
struct TabMap {
    uint16_t v[TABN];
    constexpr TabMap() : v{} {
        for (int i = 0; i < 560; i++) { v[TD0 + i] = tab_dense(CD - i); v[TD1 + i] = tab_dense(CD + 1 - i); }
        for (int i = 0; i < 48; i++) { v[TE0 + i] = tab_extra(CE - i); v[TE1 + i] = tab_extra(CE + 1 - i); }
        for (int s = 0; s < 4; s++)
            for (int i = 0; i < T2C; i++) { v[T2B + s * T2S + i] = tab_2(s, C2 - i); v[T2B + s * T2S + T2C + i] = tab_2(s, C2 + 1 - i); }
        for (int s = 0; s < 2; s++)
            for (int i = 0; i < T3C; i++) { v[T3B + s * T3S + i] = tab_3(s, C3 - i); v[T3B + s * T3S + T3C + i] = tab_3(s, C3 + 1 - i); }
    }
};
__device__ const __align__(16) TabMap g_tabmap = TabMap();

__device__ __align__(1024) uint8_t g_kimg[65536];
__device__ __align__(1024) uint8_t g_vimg[65536 + 1024];
__device__ __align__(1024) uint8_t g_oimg[16 * 131072];
__device__ unsigned long long g_flag_kv[64];
__device__ unsigned g_flag_o[128];
__device__ unsigned g_epoch;
__device__ unsigned g_done;

#define PROF(i) do {} while (0)
#define PROF2(i) do {} while (0)
#define PROFC(i) do {} while (0)
#define PROF3(i) do {} while (0)

__device__ __forceinline__ uint32_t smem_u32(const void* p) { return (uint32_t)__cvta_generic_to_shared(p); }
__device__ __forceinline__ void mbar_init(uint32_t bar, uint32_t cnt) { asm volatile("mbarrier.init.shared::cta.b64 [%0], %1;" :: "r"(bar), "r"(cnt) : "memory"); }
__device__ __forceinline__ void mbar_expect_tx(uint32_t bar, uint32_t bytes) {
    asm volatile("mbarrier.arrive.expect_tx.shared::cta.b64 _, [%0], %1;" :: "r"(bar), "r"(bytes) : "memory"); }
__device__ __forceinline__ void mbar_wait(uint32_t bar, uint32_t parity) {
    uint32_t ok = 0;
    for (int it = 0; it < (1 << 22) && !ok; it++) {
        asm volatile("{ .reg .pred p; mbarrier.try_wait.parity.shared::cta.b64 p, [%1], %2; selp.u32 %0, 1, 0, p; }"
                     : "=r"(ok) : "r"(bar), "r"(parity) : "memory");
    }
}
__device__ __forceinline__ void tma_2d(uint32_t dst, const CUtensorMap* map, int c0, int c1, uint32_t bar) {
    asm volatile("cp.async.bulk.tensor.2d.shared::cluster.global.mbarrier::complete_tx::bytes [%0], [%1, {%3, %4}], [%2];"
                 :: "r"(dst), "l"((uint64_t)map), "r"(bar), "r"(c0), "r"(c1) : "memory");
}
__device__ __forceinline__ void tma_2d_mc(uint32_t dst, const CUtensorMap* map, int c0, int c1, uint32_t bar) {
    asm volatile("cp.async.bulk.tensor.2d.shared::cluster.global.mbarrier::complete_tx::bytes.multicast::cluster [%0], [%1, {%3, %4}], [%2], %5;"
                 :: "r"(dst), "l"((uint64_t)map), "r"(bar), "r"(c0), "r"(c1), "h"((uint16_t)3) : "memory");
}
__device__ __forceinline__ void bulk_g2s_mc(uint32_t dst, const void* src, uint32_t bytes, uint32_t bar) {
    asm volatile("cp.async.bulk.shared::cluster.global.mbarrier::complete_tx::bytes.multicast::cluster [%0], [%1], %2, [%3], %4;"
                 :: "r"(dst), "l"((uint64_t)src), "r"(bytes), "r"(bar), "h"((uint16_t)3) : "memory");
}
__device__ __forceinline__ void pair_sync(uint32_t bar, uint32_t peer) {
    uint32_t ra;
    asm volatile("mapa.shared::cluster.u32 %0, %1, %2;" : "=r"(ra) : "r"(bar), "r"(peer));
    asm volatile("mbarrier.arrive.shared::cluster.b64 _, [%0];" :: "r"(ra) : "memory");
    asm volatile("mbarrier.arrive.shared::cta.b64 _, [%0];" :: "r"(bar) : "memory");
    uint32_t ok = 0;
    for (int it = 0; it < (1 << 22) && !ok; it++) {
        asm volatile("{ .reg .pred p; mbarrier.try_wait.parity.shared::cta.b64 p, [%1], 0; selp.u32 %0, 1, 0, p; }"
                     : "=r"(ok) : "r"(bar) : "memory");
    }
}
__device__ __forceinline__ void fence_async_all() { asm volatile("fence.proxy.async.global;" ::: "memory"); }
__device__ __forceinline__ void fence_async_smem() { asm volatile("fence.proxy.async.shared::cta;" ::: "memory"); }
__device__ __forceinline__ unsigned ld_acquire(const unsigned* p) {
    unsigned v; asm volatile("ld.acquire.gpu.global.u32 %0, [%1];" : "=r"(v) : "l"(p) : "memory"); return v; }
__device__ __forceinline__ void st_release(unsigned* p, unsigned v) { asm volatile("st.release.gpu.global.u32 [%0], %1;" :: "l"(p), "r"(v) : "memory"); }
__device__ __forceinline__ void wait_flag(const unsigned* p, unsigned epoch) {
    for (int it = 0; it < (1 << 22); it++) { if (ld_acquire(p) == epoch) break; }
}
__device__ __forceinline__ unsigned long long ld_acquire64(const unsigned long long* p) {
    unsigned long long v; asm volatile("ld.acquire.gpu.global.u64 %0, [%1];" : "=l"(v) : "l"(p) : "memory"); return v; }
__device__ __forceinline__ void st_release64(unsigned long long* p, unsigned long long v) { asm volatile("st.release.gpu.global.u64 [%0], %1;" :: "l"(p), "l"(v) : "memory"); }
__device__ __forceinline__ float wait_flag64(const unsigned long long* p, unsigned epoch) {
    unsigned long long v = 0;
    for (int it = 0; it < (1 << 22); it++) { v = ld_acquire64(p); if ((unsigned)(v >> 32) == epoch) break; }
    return __uint_as_float((unsigned)v);
}
__device__ __forceinline__ void tma_3d_mc(uint32_t dst, const CUtensorMap* map, int c0, int c1, int c2, uint32_t bar) {
    asm volatile("cp.async.bulk.tensor.3d.shared::cluster.global.mbarrier::complete_tx::bytes.multicast::cluster [%0], [%1, {%3, %4, %5}], [%2], %6;"
                 :: "r"(dst), "l"((uint64_t)map), "r"(bar), "r"(c0), "r"(c1), "r"(c2), "h"((uint16_t)3) : "memory");
}
__device__ __forceinline__ void bar_sync(int id, int n) { asm volatile("bar.sync %0, %1;" :: "r"(id), "r"(n) : "memory"); }
__device__ __forceinline__ void bar_arrive(int id, int n) { asm volatile("bar.arrive %0, %1;" :: "r"(id), "r"(n) : "memory"); }
__device__ __forceinline__ void mbar_arrive(uint32_t bar) { asm volatile("mbarrier.arrive.shared::cta.b64 _, [%0];" :: "r"(bar) : "memory"); }

__device__ __forceinline__ uint64_t make_desc(uint32_t saddr, uint32_t lbo, uint32_t sbo, uint32_t swz) {
    uint64_t d = 0;
    d |= (uint64_t)((saddr & 0x3FFFF) >> 4);
    d |= (uint64_t)((lbo >> 4) & 0x3FFF) << 16;
    d |= (uint64_t)((sbo >> 4) & 0x3FFF) << 32;
    d |= (uint64_t)swz << 62;
    return d;
}
__device__ __forceinline__ void wg_fence() { asm volatile("wgmma.fence.sync.aligned;" ::: "memory"); }
__device__ __forceinline__ void wg_commit() { asm volatile("wgmma.commit_group.sync.aligned;" ::: "memory"); }
template<int N> __device__ __forceinline__ void wg_wait() { asm volatile("wgmma.wait_group.sync.aligned %0;" :: "n"(N) : "memory"); }
#define A4(d, o) "+f"(d[o + 0]), "+f"(d[o + 1]), "+f"(d[o + 2]), "+f"(d[o + 3])
#define A16(d, o) A4(d, o), A4(d, o + 4), A4(d, o + 8), A4(d, o + 12)

__device__ __forceinline__ void wg_pv(float* d, const uint32_t* a, uint32_t lo, uint32_t hi) {
    asm volatile("{ .reg .b64 dd; mov.b64 dd, {%16, %17};\n"
                 "wgmma.mma_async.sync.aligned.m64n24k16.f32.bf16.bf16 {%0,%1,%2,%3,%4,%5,%6,%7,%8,%9,%10,%11}, {%12,%13,%14,%15}, dd, 1, 1, 1, 1; }"
                 : A4(d, 0), A4(d, 4), A4(d, 8) : "r"(a[0]), "r"(a[1]), "r"(a[2]), "r"(a[3]), "r"(lo), "r"(hi));
}
__device__ __forceinline__ void wg_qk(float* d, const uint32_t* a, uint32_t lo) {
    asm volatile("{ .reg .b64 dd; mov.b64 dd, {%36, %37};\n"
                 "wgmma.mma_async.sync.aligned.m64n64k16.f32.bf16.bf16 {%0,%1,%2,%3,%4,%5,%6,%7,%8,%9,%10,%11,%12,%13,%14,%15,%16,%17,%18,%19,%20,%21,%22,%23,%24,%25,%26,%27,%28,%29,%30,%31}, {%32,%33,%34,%35}, dd, 0, 1, 1, 0; }"
                 : A16(d, 0), A16(d, 16) : "r"(a[0]), "r"(a[1]), "r"(a[2]), "r"(a[3]), "r"(lo), "r"(16));
}
__device__ __forceinline__ void wg_ss32(float* d, uint64_t da, uint64_t db) {
    asm volatile("wgmma.mma_async.sync.aligned.m64n32k16.f32.bf16.bf16 {%0,%1,%2,%3,%4,%5,%6,%7,%8,%9,%10,%11,%12,%13,%14,%15}, %16, %17, 1, 1, 1, 0, 1;"
                 : A16(d, 0) : "l"(da), "l"(db));
}
__device__ __forceinline__ void wg_ss16(float* d, uint64_t da, uint64_t db) {
    asm volatile("wgmma.mma_async.sync.aligned.m64n16k16.f32.bf16.bf16 {%0,%1,%2,%3,%4,%5,%6,%7}, %8, %9, 1, 1, 1, 0, 1;"
                 : A4(d, 0), A4(d, 4) : "l"(da), "l"(db));
}
template<int N> __device__ __forceinline__ void fence_regs(float* r) {
    #pragma unroll
    for (int i = 0; i < N; i++) asm volatile("" : "+f"(r[i]) :: "memory");
}
__device__ __forceinline__ void mma_f16(float* d, const uint32_t* a, uint32_t b0, uint32_t b1) {
    asm volatile("mma.sync.aligned.m16n8k16.row.col.f32.f16.f16.f32 {%0,%1,%2,%3}, {%4,%5,%6,%7}, {%8,%9}, {%0,%1,%2,%3};"
                 : "+f"(d[0]), "+f"(d[1]), "+f"(d[2]), "+f"(d[3]) : "r"(a[0]), "r"(a[1]), "r"(a[2]), "r"(a[3]), "r"(b0), "r"(b1));
}
__device__ __forceinline__ uint32_t lds32(uint32_t addr) { uint32_t v; asm volatile("ld.shared.u32 %0, [%1];" : "=r"(v) : "r"(addr) : "memory"); return v; }
__device__ __forceinline__ void mma_bf16_p(float* d, uint32_t a0, uint32_t a1, uint32_t a2, uint32_t a3, uint32_t b0, uint32_t b1) {
    asm("mma.sync.aligned.m16n8k16.row.col.f32.bf16.bf16.f32 {%0,%1,%2,%3}, {%4,%5,%6,%7}, {%8,%9}, {%0,%1,%2,%3};"
        : "+f"(d[0]), "+f"(d[1]), "+f"(d[2]), "+f"(d[3]) : "r"(a0), "r"(a1), "r"(a2), "r"(a3), "r"(b0), "r"(b1));
}
__device__ __forceinline__ void ldsm4_p(uint32_t* r, uint32_t addr) {
    asm("ldmatrix.sync.aligned.m8n8.x4.shared.b16 {%0,%1,%2,%3}, [%4];" : "=r"(r[0]), "=r"(r[1]), "=r"(r[2]), "=r"(r[3]) : "r"(addr));
}
__device__ __forceinline__ void ldsm4t_p(uint32_t* r, uint32_t addr) {
    asm("ldmatrix.sync.aligned.m8n8.x4.trans.shared.b16 {%0,%1,%2,%3}, [%4];" : "=r"(r[0]), "=r"(r[1]), "=r"(r[2]), "=r"(r[3]) : "r"(addr));
}
__device__ __forceinline__ uint32_t lds32_p(uint32_t addr) { uint32_t v; asm("ld.shared.u32 %0, [%1];" : "=r"(v) : "r"(addr)); return v; }
__device__ __forceinline__ uint32_t swz(uint32_t a) { return a ^ ((a >> 3) & 16u); }
__device__ __forceinline__ void sts32(uint32_t addr, uint32_t v) { asm volatile("st.shared.u32 [%0], %1;" :: "r"(addr), "r"(v) : "memory"); }
__device__ __forceinline__ void sts128(uint32_t addr, uint4 v) { asm volatile("st.shared.v4.u32 [%0], {%1,%2,%3,%4};" :: "r"(addr), "r"(v.x), "r"(v.y), "r"(v.z), "r"(v.w) : "memory"); }
__device__ __forceinline__ uint4 lds128(uint32_t addr) { uint4 v; asm volatile("ld.shared.v4.u32 {%0,%1,%2,%3}, [%4];" : "=r"(v.x), "=r"(v.y), "=r"(v.z), "=r"(v.w) : "r"(addr) : "memory"); return v; }
__device__ __forceinline__ float ex2f(float x) { float r; asm("ex2.approx.ftz.f32 %0, %1;" : "=f"(r) : "f"(x)); return r; }
__device__ __forceinline__ uint32_t pack_bf16(float lo, float hi) { uint32_t r; asm("cvt.rn.bf16x2.f32 %0, %1, %2;" : "=r"(r) : "f"(hi), "f"(lo)); return r; }
__device__ __forceinline__ uint32_t pack_f16(float lo, float hi) { uint32_t r; asm("cvt.rn.f16x2.f32 %0, %1, %2;" : "=r"(r) : "f"(hi), "f"(lo)); return r; }
__device__ __forceinline__ float bf_lo(uint32_t v) { return __uint_as_float(v << 16); }
__device__ __forceinline__ float bf_hi(uint32_t v) { return __uint_as_float(v & 0xFFFF0000u); }
__device__ __forceinline__ float bf_round(float x) { return __bfloat162float(__float2bfloat16_rn(x)); }

__device__ __forceinline__ uint32_t exp_mufu(float x0, float x1) { return pack_bf16(ex2f(x0), ex2f(x1)); }
#define SW_MAGIC (256.0f + 127.0f - 0.598938f)
__device__ __forceinline__ uint32_t exp_sw(float x0, float x1, uint32_t cA, uint32_t cB) {
    float t0 = x0 + SW_MAGIC, t1 = x1 + SW_MAGIC;
    uint32_t L, mh, ec, r;
    asm("prmt.b32 %0, %1, %2, 0x6521;" : "=r"(L) : "r"(__float_as_uint(t0)), "r"(__float_as_uint(t1)));
    asm("lop3.b32 %0, %1, 0x007F007F, %2, 0xEA;" : "=r"(mh) : "r"(L), "r"(cA));
    asm("lop3.b32 %0, %1, 0x7F807F80, %2, 0xEA;" : "=r"(ec) : "r"(L), "r"(cB));
    asm("fma.rn.bf16x2 %0, %1, %2, %3;" : "=r"(r) : "r"(L), "r"(mh), "r"(ec));
    return r;
}
constexpr uint32_t MUFU_MASK = 0x4949;

struct cf { float x, y; };
__device__ __forceinline__ cf cmul(cf a, cf b) { cf r; r.x = a.x * b.x - a.y * b.y; r.y = a.x * b.y + a.y * b.x; return r; }
__device__ __forceinline__ cf cexp_p(float a2, float b, float p) {
    float e = ex2f(a2 * p);
    float ph = b * p;
    ph -= (ph + 12582912.0f) - 12582912.0f;
    float ang = ph * 6.283185307f;
    cf r; r.x = e * __cosf(ang); r.y = e * __sinf(ang);
    return r;
}
__device__ __forceinline__ uint32_t h2_cmul(uint32_t w, uint32_t wsw, uint32_t e) {
    __half2 hw = *(__half2*)&w, hs = *(__half2*)&wsw, he = *(__half2*)&e;
    __half2 r = __hfma2(hs, __high2half2(he), __hmul2(hw, __low2half2(he)));
    return *(uint32_t*)&r;
}

template<bool B> struct BoolC { static constexpr bool value = B; };
struct Params {
    const __nv_bfloat16 *u, *lar, *aim, *cre, *cim, *logdt, *dskip;
    __nv_bfloat16* out;
};

constexpr int B_O = 0, B_KV = 8, B_WO = 12, B_WQ2 = 13, B_ST = 14, B_H = 15, B_X = 17, B_U = 19, B_WQ = 20;

__device__ __forceinline__ void helper_role(const Params& P, uint8_t* sp, uint32_t sb, unsigned epoch) {
    const uint32_t sBa = sb + SM_B;
    const int tid = threadIdx.x - 544;
    const int d0 = blockIdx.x * 4;
    uint8_t* sB = sp + SM_B;
    const uint2 dsk = __ldg((const uint2*)(P.dskip + d0));
    asm volatile("barrier.cluster.wait.aligned;" ::: "memory");
    {
        const int hg = blockIdx.x & 7;
        if (hg < 4 && tid < 32) {
            bar_sync(3, 160);
            if (tid == 0) {
                const float* s_misc = (const float*)(sp + SM_BAR + 256);
                const float st = fmaxf(fmaxf(s_misc[20], s_misc[21]), fmaxf(s_misc[22], s_misc[23]));
                st_release64(&g_flag_kv[((blockIdx.x >> 3) * 2 + (hg & 1)) * 2 + (hg >> 1)], ((unsigned long long)epoch << 32) | __float_as_uint(st));
            }
            __syncwarp();
        }
    }
    PROF2(2);
    bar_sync(10, 608);
    {
        uint32_t dd[4] = {__byte_perm(dsk.x, 0, 0x1010), __byte_perm(dsk.x, 0, 0x3232), __byte_perm(dsk.y, 0, 0x1010), __byte_perm(dsk.y, 0, 0x3232)};
        #pragma unroll 2
        for (int pi = tid; pi < 1024; pi += 96) {
            const int l = 2 * pi;
            uint32_t r[4];
            #pragma unroll
            for (int cc = 0; cc < 4; cc++) {
                const uint32_t y2 = *(const uint32_t*)(sB + S_Y + cc * 4096 + l * 2);
                const uint32_t u2 = lds32(swz(sBa + S_U + cc * ULEN * 2 + (PADU + l) * 2));
                __nv_bfloat162 pr = __hmul2(*(const __nv_bfloat162*)&u2, *(const __nv_bfloat162*)&dd[cc]);
                __nv_bfloat162 sm = __hadd2(*(const __nv_bfloat162*)&y2, pr);
                r[cc] = *(uint32_t*)&sm;
            }
            *(uint2*)(P.out + (size_t)l * 1024 + 512 + d0) = make_uint2(__byte_perm(r[0], r[1], 0x5410), __byte_perm(r[2], r[3], 0x5410));
            *(uint2*)(P.out + (size_t)(l + 1) * 1024 + 512 + d0) = make_uint2(__byte_perm(r[0], r[1], 0x7632), __byte_perm(r[2], r[3], 0x7632));
        }
    }
    bar_arrive(11, 128);
    PROF2(4);
}

__global__ void __cluster_dims__(2, 1, 1) __launch_bounds__(NTHR, 1)
fused_kernel(const __grid_constant__ CUtensorMap tm_x, const __grid_constant__ CUtensorMap tm_wq,
             const __grid_constant__ CUtensorMap tm_wo, const __grid_constant__ CUtensorMap tm_wk,
             const __grid_constant__ CUtensorMap tm_wv, const __grid_constant__ CUtensorMap tm_u, const Params P) {
    extern __shared__ uint8_t smem_raw[];
    const uint32_t sb = (smem_u32(smem_raw) + 1023u) & ~1023u;
    uint8_t* sp = smem_raw + (sb - smem_u32(smem_raw));

    const int tid = threadIdx.x, warp = tid >> 5, lane = tid & 31, wg = tid >> 7, wiw = warp & 3;
    const int g = lane >> 2, t = lane & 3;
    const int qb = blockIdx.x >> 3, hg = blockIdx.x & 7;
    const uint32_t rank = blockIdx.x & 1;
    const int rowhalf = wg & 1, nh = wg >> 1;
    const bool kv_cta = hg < 4;
    const int kv_sel = hg >> 1;
    const bool kv_wg = kv_cta && (wg == (hg & 1));

    const uint32_t bars = sb + SM_BAR;
    float* s_misc = (float*)(sp + SM_BAR + 256);
    const CUtensorMap* tm_kv = kv_sel ? &tm_wv : &tm_wk;

    PROF(0);
    unsigned short p_lar = 0, p_aim = 0, p_cre = 0, p_cim = 0, p_ldt = 0;
    if (wg < 4) {
        const int n = (blockIdx.x * 4 + wg) * 128 + (tid & 127);
        p_lar = __ldg((const unsigned short*)P.lar + n);
        p_aim = __ldg((const unsigned short*)P.aim + n);
        p_cre = __ldg((const unsigned short*)P.cre + n);
        p_cim = __ldg((const unsigned short*)P.cim + n);
        p_ldt = __ldg((const unsigned short*)P.logdt + blockIdx.x * 4 + wg);
    } else if (warp == 16) {
        PROF3(5);
        if (lane == 0) {
            asm volatile("prefetch.tensormap [%0];" :: "l"((uint64_t)&tm_x) : "memory");
            asm volatile("prefetch.tensormap [%0];" :: "l"((uint64_t)tm_kv) : "memory");
            asm volatile("prefetch.tensormap [%0];" :: "l"((uint64_t)&tm_wq) : "memory");
            asm volatile("prefetch.tensormap [%0];" :: "l"((uint64_t)&tm_u) : "memory");
            mbar_init(bars + 8 * B_X, 1);
            mbar_init(bars + 8 * B_X + 8, 1);
            mbar_init(bars + 8 * B_U, 1);
            asm volatile("fence.mbarrier_init.release.cluster;" ::: "memory");
            mbar_expect_tx(bars + 8 * B_X, 65536u + (kv_cta ? 8192u : 0u));
            mbar_expect_tx(bars + 8 * B_X + 8, 65536u + (kv_cta ? 8192u : 0u));
            mbar_expect_tx(bars + 8 * B_U, 32768u);
        }
        __syncwarp();
        PROF3(6);
    }
    asm volatile("barrier.cluster.arrive.relaxed.aligned;" ::: "memory");
    const unsigned epoch = *(volatile unsigned*)&g_epoch + 1u;
    if (warp > 16) {
        if (lane == 0) {
            for (int i = warp - 17; i < B_X; i += 3) {
                mbar_init(bars + 8 * i, i >= B_H ? 2 : 1);
                if (i <= B_WQ2) mbar_expect_tx(bars + 8 * i, i < B_KV + 2 ? 16384u : i == B_KV + 2 ? 32768u : i <= B_WO ? 65536u : 32768u);
            }
            asm volatile("fence.mbarrier_init.release.cluster;" ::: "memory");
            fence_async_smem();
        } else if (warp == 19) {
            asm volatile("prefetch.global.L2 [%0];" :: "l"((const char*)g_tabmap.v + (lane - 1) * 128));
            if (lane < 5) asm volatile("prefetch.global.L2 [%0];" :: "l"((const char*)g_tabmap.v + (lane + 30) * 128));
        }
        __syncwarp();
    }
    asm volatile("barrier.cluster.wait.aligned;" ::: "memory");
    PROF(5);
    if (warp == 16 && lane == 0) {
        tma_3d_mc(sb + (rank ? SM_A : SM_B), &tm_x, 0, qb * 128, rank * 4, bars + 8 * (B_X + rank));
        if (kv_cta) {
            #pragma unroll
            for (int i = 0; i < 4; i++) tma_2d(sb + SM_WKV + i * 4096, tm_kv, (i >> 1) * 8, (i & 1) * 256, bars + 8 * (B_X + (i & 1)));
        }
        mbar_init(bars + 8 * B_WQ, 1);
        asm volatile("fence.mbarrier_init.release.cluster;" ::: "memory");
        fence_async_smem();
        mbar_expect_tx(bars + 8 * B_WQ, 32768u);
        tma_2d(sb + SM_WQ, &tm_wq, hg * 64, 0, bars + 8 * B_WQ);
        #pragma unroll
        for (int i = 0; i < 4; i++) tma_2d_mc(sb + SM_SLAB + (rank * 4 + i) * 4096, &tm_u, (blockIdx.x >> 1) * 8, (rank * 4 + i) * 256, bars + 8 * B_U);
    }
    __syncwarp();
    asm volatile("barrier.cluster.arrive.relaxed.aligned;" ::: "memory");

    if (warp == 16) {
        if (lane == 0) asm volatile("prefetch.tensormap [%0];" :: "l"((uint64_t)&tm_wo) : "memory");
        asm volatile("barrier.cluster.wait.aligned;" ::: "memory");
        PROF3(10);
        bar_sync(13, 544);
        if (lane == 0) { fence_async_smem(); tma_2d(sb + SM_SLAB, &tm_wq, hg * 64, 256, bars + 8 * B_WQ2); }
        bar_sync(14, 544);
        if (lane == 0) pair_sync(bars + 8 * B_H, rank ^ 1);
        __syncwarp();
        PROF3(11);
        *(uint4*)(sp + SM_V + 32768 + lane * 32) = make_uint4(0x3F803F80u, 0x3F803F80u, 0x3F803F80u, 0x3F803F80u);
        *(uint4*)(sp + SM_V + 32768 + lane * 32 + 16) = make_uint4(0x3F803F80u, 0x3F803F80u, 0x3F803F80u, 0x3F803F80u);
        fence_async_smem();
        float km = wait_flag64(&g_flag_kv[2 * lane], epoch);
        float vm = wait_flag64(&g_flag_kv[2 * lane + 1], epoch);
        __syncwarp();
        PROF3(12);
        if (lane == 0) {
            fence_async_all();
            #pragma unroll
            for (int i = 0; i < 4; i++) {
                const uint32_t k0 = i == 0 ? 0 : 128u << i, nk = i == 0 ? 256 : 128u << i;
                const uint32_t bar = bars + 8 * (B_KV + i);
                if (rank == 0) bulk_g2s_mc(sb + SM_K + k0 * 32, g_kimg + k0 * 32, nk * 32, bar);
                else {
                    bulk_g2s_mc(sb + SM_V + k0 * 16, g_vimg + k0 * 16, nk * 16, bar);
                    bulk_g2s_mc(sb + SM_V + 66560 - (k0 + nk) * 16, g_vimg + 66560 - (k0 + nk) * 16, nk * 16, bar);
                }
            }
        }
        #pragma unroll
        for (int o = 16; o; o >>= 1) { km = fmaxf(km, __shfl_xor_sync(0xffffffffu, km, o)); vm = fmaxf(vm, __shfl_xor_sync(0xffffffffu, vm, o)); }
        if (lane == 0) { s_misc[16] = km; s_misc[17] = vm; mbar_arrive(bars + 8 * B_ST); }
        PROF3(13);
        bar_sync(11, 128);
        if (lane < 2) { fence_async_smem(); tma_2d(sb + SM_B + lane * 32768, &tm_wo, hg * 64, lane * 256, bars + 8 * B_WO); }
        bar_sync(12, 544);
        if (lane == 0) {
            st_release(&g_flag_o[blockIdx.x], epoch);
            pair_sync(bars + 8 * (B_H + 1), rank ^ 1);
        }
        __syncwarp();
        PROF3(14);
        if (lane < 4) {
            const int src = 2 * lane + rank;
            wait_flag(&g_flag_o[qb * 8 + src], epoch);
            fence_async_all();
            bulk_g2s_mc(sb + SM_A + src * 16384, g_oimg + qb * 131072 + src * 16384, 16384, bars + 8 * (B_O + src));
        }
        __syncwarp();
        PROF3(15);
        if (lane == 0) {
            const unsigned prev = atomicAdd(&g_done, 1u);
            if (prev == NCTA - 1) {
                g_done = 0;
                __threadfence();
                *(volatile unsigned*)&g_epoch = epoch;
            }
        }
    } else if (wg == 4) {
        helper_role(P, sp, sb, epoch);
    } else {
        uint8_t* sB = sp + SM_B;
        const uint32_t sBa = sb + SM_B;
        {
            const int c = wg;
            const float dt = bf_round(expf(bf_lo(p_ldt)));
            const float are = -bf_round(expf(bf_lo(p_lar))) * dt;
            const float aim = bf_lo(p_aim) * dt;
            float cr = 2.0f * (bf_lo(p_cre) * dt);
            float ci = 2.0f * (bf_lo(p_cim) * dt);
            const float a2 = are * 1.4426950408889634f, bb = aim * 0.15915494309189535f;
            float m = fmaxf(fabsf(cr), fabsf(ci));
            #pragma unroll
            for (int o = 16; o; o >>= 1) m = fmaxf(m, __shfl_xor_sync(0xffffffffu, m, o));
            int ebits = (__float_as_uint(m) >> 23) & 0xFF;
            ebits = min(max(ebits, 2), 250);
            const float scale = __uint_as_float((uint32_t)(ebits + 1) << 23);
            const float iscale = __uint_as_float((uint32_t)(253 - ebits) << 23);
            cf cc; cc.x = cr * iscale; cc.y = ci * iscale;

            const uint32_t stg = sBa + S_KC + warp * 1024;
            uint4* stp = (uint4*)(sB + S_KC + warp * 1024 + lane * 32);
            const uint32_t fa = stg + t * 32 + g * 4;

            uint32_t af[4][2][4];
            cf E256;
            {
                const cf E8 = cexp_p(a2, bb, 8.0f);
                uint32_t w[8];
                cf cur; cur.x = 1.0f; cur.y = 0.0f;
                w[0] = pack_f16(1.0f, 0.0f);
                cur = E8; w[1] = pack_f16(cur.x, cur.y);
                #pragma unroll
                for (int i = 2; i < 8; i++) { cur = cmul(cur, E8); w[i] = pack_f16(cur.x, cur.y); }
                stp[0] = make_uint4(w[0], w[1], w[2], w[3]);
                stp[1] = make_uint4(w[4], w[5], w[6], w[7]);
                const cf E64 = cexp_p(a2, bb, 64.0f);
                const cf E128 = cmul(E64, E64), E192 = cmul(E128, E64);
                E256 = cexp_p(a2, bb, 256.0f);
                const uint32_t e1 = pack_f16(E64.x, E64.y), e2 = pack_f16(E128.x, E128.y), e3 = pack_f16(E192.x, E192.y);
                __syncwarp();
                #pragma unroll
                for (int s = 0; s < 4; s++) {
                    #pragma unroll
                    for (int hh = 0; hh < 2; hh++) {
                        const uint32_t w0 = lds32(fa + s * 256 + hh * 128);
                        const uint32_t wsw = __byte_perm(w0, 0, 0x1032) ^ 0x00008000u;
                        const int src = 8 * s + t + 4 * hh;
                        const uint32_t f1 = __shfl_sync(0xffffffffu, e1, src), f2 = __shfl_sync(0xffffffffu, e2, src), f3 = __shfl_sync(0xffffffffu, e3, src);
                        af[s][0][2 * hh] = w0;
                        af[s][0][2 * hh + 1] = h2_cmul(w0, wsw, f1);
                        af[s][1][2 * hh] = h2_cmul(w0, wsw, f2);
                        af[s][1][2 * hh + 1] = h2_cmul(w0, wsw, f3);
                    }
                }
                __syncwarp();
            }
            float acc[2][3][4];
            #pragma unroll
            for (int i = 0; i < 24; i++) (&acc[0][0][0])[i] = 0.0f;
            const cf E1 = cexp_p(a2, bb, 1.0f);
            const cf E2 = cmul(E1, E1), E4 = cmul(E2, E2);
            cf X512;
            #pragma unroll
            for (int nt = 0; nt < 3; nt++) {
                uint32_t xv[8];
                if (nt == 0) {
                    cf cur = cc;
                    xv[0] = pack_f16(cur.x, -cur.y);
                    #pragma unroll
                    for (int i = 1; i < 8; i++) { cur = cmul(cur, E1); xv[i] = pack_f16(cur.x, -cur.y); }
                } else if (nt == 1) {
                    cf cur = cmul(cc, E256);
                    X512 = cmul(cur, E256);
                    xv[0] = pack_f16(cur.x, -cur.y);
                    #pragma unroll
                    for (int i = 1; i < 4; i++) { cur = cmul(cur, E2); xv[i] = pack_f16(cur.x, -cur.y); }
                    cur = cmul(X512, E4);
                    xv[4] = pack_f16(X512.x, -X512.y); xv[5] = pack_f16(cur.x, -cur.y);
                    X512 = cmul(X512, E256);
                    cur = cmul(X512, E4);
                    xv[6] = pack_f16(X512.x, -X512.y); xv[7] = pack_f16(cur.x, -cur.y);
                } else {
                    cf cur = X512;
                    #pragma unroll
                    for (int i = 0; i < 5; i++) { cur = cmul(cur, E256); xv[i] = pack_f16(cur.x, -cur.y); }
                    xv[5] = 0; xv[6] = 0; xv[7] = 0;
                }
                stp[0] = make_uint4(xv[0], xv[1], xv[2], xv[3]);
                stp[1] = make_uint4(xv[4], xv[5], xv[6], xv[7]);
                __syncwarp();
                #pragma unroll
                for (int s = 0; s < 4; s++) {
                    const uint32_t b0 = lds32(fa + s * 256), b1 = lds32(fa + s * 256 + 128);
                    mma_f16(acc[0][nt], af[s][0], b0, b1);
                    mma_f16(acc[1][nt], af[s][1], b0, b1);
                }
                __syncwarp();
            }
            float* kc = (float*)(sB + S_KC + c * 4096);
            bar_sync(4 + c, 128);
            #pragma unroll 1
            for (int step = 0; step < 4; step++) {
                if ((warp & 3) == step) {
                    #pragma unroll
                    for (int mt = 0; mt < 2; mt++)
                        #pragma unroll
                        for (int nt = 0; nt < 3; nt++)
                            #pragma unroll
                            for (int hh = 0; hh < 2; hh++) {
                                float2* p = (float2*)(kc + (mt * 16 + hh * 8 + g) * 24 + nt * 8 + 2 * t);
                                float2 v = make_float2(acc[mt][nt][2 * hh] * scale, acc[mt][nt][2 * hh + 1] * scale);
                                if (step) { float2 o = *p; v.x += o.x; v.y += o.y; }
                                *p = v;
                            }
                }
                if (step < 3) bar_sync(4 + c, 128);
            }
        }

        asm volatile("barrier.cluster.wait.aligned;" ::: "memory");
        PROF(4);
        uint32_t q[2][4];
        {
            float acc[16], akv[8];
            #pragma unroll
            for (int i = 0; i < 16; i++) acc[i] = 0.0f;
            #pragma unroll
            for (int i = 0; i < 8; i++) akv[i] = 0.0f;
            fence_regs<16>(acc);
            fence_regs<8>(akv);
            const uint64_t dA0 = make_desc(sb + SM_B + rowhalf * 8192, 16, 1024, 1);
            const uint64_t dA1 = make_desc(sb + SM_A + rowhalf * 8192, 16, 1024, 1) - 4096;
            const uint64_t dB = make_desc(sb + SM_WQ + nh * 64, 16, 1024, 1);
            const uint64_t dC = make_desc(sb + SM_WKV, 128, 8192, 0);
            if (kv_wg) {
                #pragma unroll 1
                for (int ch = 0; ch < 8; ch++) {
                    if ((ch & 3) == 0) mbar_wait(bars + 8 * (B_X + (ch >> 2)), 0);
                    const uint64_t dA = ch < 4 ? dA0 : dA1;
                    wg_fence();
                    #pragma unroll
                    for (int ks = 0; ks < 4; ks++) wg_ss16(akv, dA + ch * 1024 + ks * 2, dC + (ch * 4 + ks) * 16);
                    wg_commit();
                }
                wg_wait<0>();
            }
            fence_regs<8>(akv);
            if (kv_wg) {
                const int key = qb * 128 + rowhalf * 64 + wiw * 16 + g;
                uint32_t pk[4];
                #pragma unroll
                for (int i = 0; i < 4; i++) pk[i] = pack_bf16(akv[2 * i], akv[2 * i + 1]);
                float st;
                if (kv_sel == 0) {
                    uint8_t* b = g_kimg + (key >> 3) * 256 + (key & 7) * 16 + 4 * t;
                    *(uint32_t*)(b) = pk[0]; *(uint32_t*)(b + 256) = pk[1]; *(uint32_t*)(b + 128) = pk[2]; *(uint32_t*)(b + 384) = pk[3];
                    float n0 = bf_lo(pk[0]) * bf_lo(pk[0]) + bf_hi(pk[0]) * bf_hi(pk[0]) + bf_lo(pk[2]) * bf_lo(pk[2]) + bf_hi(pk[2]) * bf_hi(pk[2]);
                    float n1 = bf_lo(pk[1]) * bf_lo(pk[1]) + bf_hi(pk[1]) * bf_hi(pk[1]) + bf_lo(pk[3]) * bf_lo(pk[3]) + bf_hi(pk[3]) * bf_hi(pk[3]);
                    n0 += __shfl_xor_sync(0xffffffffu, n0, 1); n0 += __shfl_xor_sync(0xffffffffu, n0, 2);
                    n1 += __shfl_xor_sync(0xffffffffu, n1, 1); n1 += __shfl_xor_sync(0xffffffffu, n1, 2);
                    st = (n0 != n0 || n1 != n1) ? __int_as_float(0x7f800000) : fmaxf(n0, n1);
                } else {
                    uint8_t* lo = g_vimg + key * 16 + 4 * t;
                    uint8_t* hi = g_vimg + 33792 + (31 - (key >> 6)) * 1024 + (key & 63) * 16 + 4 * t;
                    *(uint32_t*)(lo) = pk[0]; *(uint32_t*)(lo + 128) = pk[1]; *(uint32_t*)(hi) = pk[2]; *(uint32_t*)(hi + 128) = pk[3];
                    st = 0.0f;
                    #pragma unroll
                    for (int i = 0; i < 4; i++) {
                        float a = fabsf(bf_lo(pk[i])), b = fabsf(bf_hi(pk[i]));
                        st = (a != a || b != b) ? __int_as_float(0x7f800000) : fmaxf(st, fmaxf(a, b));
                    }
                }
                #pragma unroll
                for (int o = 16; o; o >>= 1) st = fmaxf(st, __shfl_xor_sync(0xffffffffu, st, o));
                if (lane == 0) s_misc[20 + wiw] = st;
                bar_arrive(3, 160);
            }
            uint32_t mp[9];
            #pragma unroll
            for (int i = 0; i < 9; i++) { const int w = (tid & 127) + 128 * i; mp[i] = (w < TABN / 2) ? __ldg((const uint32_t*)g_tabmap.v + w) : 0u; }
            mbar_wait(bars + 8 * B_WQ, 0);
            mbar_wait(bars + 8 * B_X, 0);
            PROF(2);
            #pragma unroll 1
            for (int ch = 0; ch < 4; ch++) {
                wg_fence();
                #pragma unroll
                for (int ks = 0; ks < 4; ks++) wg_ss32(acc, dA0 + ch * 1024 + ks * 2, dB + (ch * 4 + ks) * 128);
                wg_commit();
            }
            wg_wait<0>();
            fence_regs<16>(acc);
            bar_sync(1, 512);
            PROF(15);
            if (tid < 4 * (PADU / 8)) sts128(swz(sBa + S_U + (tid / (PADU / 8)) * ULEN * 2 + (tid % (PADU / 8)) * 16), make_uint4(0, 0, 0, 0));
            PROF(8);
            mbar_wait(bars + 8 * B_U, 0);
            PROF(14);
            #pragma unroll
            for (int i = 0; i < 2; i++) {
                const int l = 2 * (tid + 512 * i);
                const uint2 r0 = *(const uint2*)(sp + SM_SLAB + l * 16 + rank * 8), r1 = *(const uint2*)(sp + SM_SLAB + l * 16 + 16 + rank * 8);
                const uint32_t dst = sBa + S_U + (PADU + l) * 2;
                sts32(swz(dst), __byte_perm(r0.x, r1.x, 0x5410));
                sts32(swz(dst + ULEN * 2), __byte_perm(r0.x, r1.x, 0x7632));
                sts32(swz(dst + ULEN * 4), __byte_perm(r0.y, r1.y, 0x5410));
                sts32(swz(dst + ULEN * 6), __byte_perm(r0.y, r1.y, 0x7632));
            }
            bar_arrive(13, 544);
            {
                const float* kc = (const float*)(sB + S_KC + wg * 4096);
                uint32_t* tab = (uint32_t*)(sB + S_TAB + wg * TABN * 2);
                #pragma unroll
                for (int i = 0; i < 9; i++) { const int w = (tid & 127) + 128 * i; if (w < TABN / 2) tab[w] = pack_bf16(kc[mp[i] & 0xFFFF], kc[mp[i] >> 16]); }
            }
            PROF(1);
            mbar_wait(bars + 8 * B_WQ2, 0);
            mbar_wait(bars + 8 * (B_X + 1), 0);
            fence_regs<16>(acc);
            #pragma unroll 1
            for (int ch = 4; ch < 8; ch++) {
                wg_fence();
                #pragma unroll
                for (int ks = 0; ks < 4; ks++) wg_ss32(acc, dA1 + ch * 1024 + ks * 2, dB + (ch * 4 + ks) * 128);
                wg_commit();
            }
            wg_wait<0>();
            fence_regs<16>(acc);
            bar_arrive(14, 544);
            const float QS = 0.25f * 1.4426950408889634f;
            float qm = 0.0f;
            #pragma unroll
            for (int i = 0; i < 2; i++) {
                #pragma unroll
                for (int j = 0; j < 4; j++) q[i][j] = pack_bf16(acc[8 * i + 2 * j] * QS, acc[8 * i + 2 * j + 1] * QS);
                float n0 = bf_lo(q[i][0]) * bf_lo(q[i][0]) + bf_hi(q[i][0]) * bf_hi(q[i][0]) + bf_lo(q[i][2]) * bf_lo(q[i][2]) + bf_hi(q[i][2]) * bf_hi(q[i][2]);
                float n1 = bf_lo(q[i][1]) * bf_lo(q[i][1]) + bf_hi(q[i][1]) * bf_hi(q[i][1]) + bf_lo(q[i][3]) * bf_lo(q[i][3]) + bf_hi(q[i][3]) * bf_hi(q[i][3]);
                n0 += __shfl_xor_sync(0xffffffffu, n0, 1); n0 += __shfl_xor_sync(0xffffffffu, n0, 2);
                n1 += __shfl_xor_sync(0xffffffffu, n1, 1); n1 += __shfl_xor_sync(0xffffffffu, n1, 2);
                qm = (n0 != n0 || n1 != n1) ? __int_as_float(0x7f800000) : fmaxf(qm, fmaxf(n0, n1));
            }
            #pragma unroll
            for (int o = 16; o; o >>= 1) qm = fmaxf(qm, __shfl_xor_sync(0xffffffffu, qm, o));
            if (lane == 0) s_misc[warp] = qm;
        }
        PROF(3);
        bar_sync(1, 512);
        #pragma unroll 1
        for (int task = tid; task < 4 * 194; task += 512) {
            const int c = task / 194, i = task % 194;
            const uint32_t src = sBa + S_U + c * ULEN * 2 + (PADU + 8 * i - WPAD - 8) * 2;
            const uint4 v0 = lds128(swz(src)), v1 = lds128(swz(src + 16)), v2 = lds128(swz(src + 32));
            float x[24];
            const uint32_t vv[12] = {v0.x, v0.y, v0.z, v0.w, v1.x, v1.y, v1.z, v1.w, v2.x, v2.y, v2.z, v2.w};
            #pragma unroll
            for (int k = 0; k < 12; k++) { x[2 * k] = bf_lo(vv[k]); x[2 * k + 1] = bf_hi(vv[k]); }
            float w3[12], w5[8];
            #pragma unroll
            for (int e = 0; e < 12; e++) w3[e] = (x[3 + e] + x[4 + e]) + x[5 + e];
            #pragma unroll
            for (int e = 0; e < 8; e++) w5[e] = w3[4 + e] + (x[6 + e] + x[10 + e]);
            sts128(swz(sBa + S_W3 + c * W2LEN * 2 + i * 16), make_uint4(pack_bf16(w3[0], w3[1]), pack_bf16(w3[2], w3[3]), pack_bf16(w3[4], w3[5]), pack_bf16(w3[6], w3[7])));
            sts128(swz(sBa + S_W5 + c * W2LEN * 2 + i * 16), make_uint4(pack_bf16(w5[0], w5[1]), pack_bf16(w5[2], w5[3]), pack_bf16(w5[4], w5[5]), pack_bf16(w5[6], w5[7])));
            if (i < 130) {
                float w7[8], w9[8];
                #pragma unroll
                for (int e = 0; e < 8; e++) { w7[e] = w5[e] + (x[5 + e] + x[11 + e]); w9[e] = w7[e] + (x[4 + e] + x[12 + e]); }
                sts128(swz(sBa + S_W7 + c * W3LEN * 2 + i * 16), make_uint4(pack_bf16(w7[0], w7[1]), pack_bf16(w7[2], w7[3]), pack_bf16(w7[4], w7[5]), pack_bf16(w7[6], w7[7])));
                sts128(swz(sBa + S_W9 + c * W3LEN * 2 + i * 16), make_uint4(pack_bf16(w9[0], w9[1]), pack_bf16(w9[2], w9[3]), pack_bf16(w9[4], w9[5]), pack_bf16(w9[6], w9[7])));
            }
        }
        bar_sync(1, 512);
        PROF(6);
        if ((wg & 1) == 0) {
            const int c = wiw, hf = nh;
            uint32_t sBl = sBa;
            asm volatile("" : "+r"(sBl) :: "memory");
            float acc[8][4];
            #pragma unroll
            for (int i = 0; i < 32; i++) (&acc[0][0])[i] = 0.0f;
            const uint32_t tabc = sBl + S_TAB + c * TABN * 2;
            const int e2 = (g - 2 * t) * 2;
            const int mi = lane >> 3, r8 = lane & 7;
            const uint32_t frag = (16 * (8 * (mi >> 1) + r8) + 8 * (mi & 1)) * 2;
            const uint32_t ub = sBl + S_U + c * ULEN * 2 + PADU * 2 + frag;
            {
                const uint32_t tD = tabc + ((g & 1) ? (TD1 + CD + 1) : (TD0 + CD)) * 2 - e2;
                #pragma unroll 1
                for (int rho = 0; rho < 8; rho++) {
                    uint32_t A[5][4], b[6][4];
                    const uint32_t base = swz(ub - rho * 32) + hf * 2048;
                    #pragma unroll
                    for (int i = 5; i >= 0; i--) {
                        if (i >= 2 || hf) ldsm4_p(b[i], base + (i - 2) * 512);
                        else if (i == 1 && rho == 0) ldsm4_p(b[i], base - 512);
                        else { b[i][0] = 0; b[i][1] = 0; b[i][2] = 0; b[i][3] = 0; }
                    }
                    #pragma unroll
                    for (int qq = 0; qq < 5; qq++) {
                        const uint32_t a = tD - 32 * ((qq < 4 || rho < 2) ? rho + 8 * qq : 0);
                        A[qq][0] = lds32_p(a); A[qq][1] = lds32_p(a - 16); A[qq][2] = lds32_p(a + 16);
                        asm("mov.b32 %0, %1;" : "=r"(A[qq][3]) : "r"(A[qq][0]));
                    }
                    #pragma unroll
                    for (int qq = 0; qq < 4; qq++)
                        #pragma unroll
                        for (int j = 7; j >= 0; j--) {
                            const int jb = j - qq + 4;
                            if (j >= qq || hf || (rho == 0 && j == qq - 1))
                                mma_bf16_p(acc[j], A[qq][0], A[qq][1], A[qq][2], A[qq][3], b[jb >> 1][2 * (jb & 1)], b[jb >> 1][2 * (jb & 1) + 1]);
                        }
                    if (rho < 2) {
                        #pragma unroll
                        for (int j = 7; j >= 0; j--)
                            if (j >= 3 || hf) mma_bf16_p(acc[j], A[4][0], A[4][1], A[4][2], A[4][3], b[j >> 1][2 * (j & 1)], b[j >> 1][2 * (j & 1) + 1]);
                    }
                }
            }
            {
                const uint32_t t2 = tabc + (T2B + ((g & 1) ? (T2C + C2 + 1) : C2)) * 2 - e2;
                #pragma unroll 1
                for (int s = 0; s < 4; s++) {
                    const uint32_t sig = swz(sBl + ((s & 1) ? S_W3 : S_W5) + c * W2LEN * 2 + WPAD * 2 + frag - ((s == 0) ? 32 : (s == 1) ? 0 : 16)) + hf * 2048;
                    uint32_t R[7], a[6][4];
                    #pragma unroll
                    for (int i = 5; i >= 0; i--) if (i >= 4 || hf) ldsm4t_p(a[i], sig + (i - 4) * 512);
                    #pragma unroll
                    for (int i = 0; i < 7; i++) R[i] = lds32_p(t2 + s * (T2S * 2) - 16 * (3 + i));
                    #pragma unroll
                    for (int hp = 0; hp < 3; hp++)
                        #pragma unroll
                        for (int j = 7; j >= 0; j--) {
                            const int h = 4 + 2 * hp + (j & 1), i = (j - h) / 2 + 4;
                            if (i >= 4 || hf) mma_bf16_p(acc[j], a[i][0], a[i][1], a[i][2], a[i][3], R[h - 3], R[h - 4]);
                        }
                }
            }
            if (hf) {
                {
                    const uint32_t tE = tabc + ((g & 1) ? (TE1 + CE + 1) : (TE0 + CE)) * 2 - e2;
                    uint32_t R[5];
                    #pragma unroll
                    for (int i = 0; i < 5; i++) R[i] = lds32_p(tE - 16 * (127 + i));
                    #pragma unroll
                    for (int kk = 0; kk < 2; kk++) {
                        #pragma unroll
                        for (int jp = 0; jp < 4; jp++) {
                            uint32_t b[4];
                            ldsm4_p(b, swz(ub - kk * 32) + jp * 512);
                            mma_bf16_p(acc[2 * jp], R[2 * kk + 1], R[2 * kk + 2], R[2 * kk], R[2 * kk + 1], b[0], b[1]);
                            mma_bf16_p(acc[2 * jp + 1], R[2 * kk + 1], R[2 * kk + 2], R[2 * kk], R[2 * kk + 1], b[2], b[3]);
                        }
                    }
                }
                const uint32_t t3 = tabc + (T3B + ((g & 1) ? (T3C + C3 + 1) : C3)) * 2 - e2;
                #pragma unroll 1
                for (int s = 0; s < 2; s++) {
                    const uint32_t sig = swz(sBl + (s ? S_W7 : S_W9) + c * W3LEN * 2 + WPAD * 2 + frag - (s ? 16 : 32));
                    uint32_t R[9];
                    #pragma unroll
                    for (int i = 0; i < 9; i++) R[i] = lds32_p(t3 + s * (T3S * 2) - 16 * (7 + i));
                    uint32_t a[4][4];
                    #pragma unroll
                    for (int b = 0; b < 4; b++) ldsm4t_p(a[b], sig + b * 512);
                    #pragma unroll
                    for (int b = 0; b < 4; b++)
                        #pragma unroll
                        for (int h = 15; h >= 8; h--)
                            if (h + 2 * b < 16) mma_bf16_p(acc[h + 2 * b - 8], a[b][0], a[b][1], a[b][2], a[b][3], R[h - 7], R[h - 8]);
                }
            }
            __nv_bfloat16* ys = (__nv_bfloat16*)(sB + S_Y + c * 4096) + 32 * t + g + hf * 1024;
            #pragma unroll
            for (int j = 0; j < 8; j++) {
                ys[128 * j] = __float2bfloat16_rn(acc[j][0]);
                ys[128 * j + 16] = __float2bfloat16_rn(acc[j][1]);
                ys[128 * j + 8] = __float2bfloat16_rn(acc[j][2]);
                ys[128 * j + 24] = __float2bfloat16_rn(acc[j][3]);
            }
        }
        bar_sync(1, 512);
        bar_arrive(10, 608);
        PROF(7);
        {
            mbar_wait(bars + 8 * B_ST, 0);
            PROF(9); PROFC(8);
            float qm = 0.0f;
            #pragma unroll
            for (int i = 0; i < 16; i++) qm = fmaxf(qm, s_misc[i]);
            const float vm = s_misc[17];
            const bool fast = (qm * s_misc[16] <= 60.0f * 60.0f) && (vm <= 1.0e12f) && (vm >= 1.0e-12f || vm == 0.0f);
            uint8_t* ob = g_oimg + qb * 131072 + hg * 16384 + nh * 8192 + (rowhalf * 8 + wiw * 2) * 128 + g * 16 + 4 * t;
            uint32_t cA = 0xBF00BF00u, cB = 0x00030003u;
            asm volatile("" : "+r"(cA), "+r"(cB));
            #pragma unroll 1
            for (int tile = 0; tile < 2; tile++) {
                uint32_t kLo = (((sb + SM_K) & 0x3FFFF) >> 4) | (8u << 16), vLo = (((sb + SM_V) & 0x3FFFF) >> 4) | (8u << 16), vHi = 2048;
                float o[12], s[32];
                uint32_t p[16], qq[4];
                #pragma unroll
                for (int i = 0; i < 4; i++) { qq[i] = tile ? q[1][i] : q[0][i]; asm volatile("" : "+r"(qq[i])); }
                #pragma unroll
                for (int i = 0; i < 12; i++) o[i] = 0.0f;
                #pragma unroll
                for (int i = 0; i < 32; i++) s[i] = 0.0f;
                fence_regs<12>(o);
                fence_regs<32>(s);
                if (fast) {
                    #pragma unroll 1
                    for (int c = 0; c < SEQ / 256; c++) {
                        if (c <= 4) mbar_wait(bars + 8 * (B_KV + (c < 2 ? c : c < 4 ? 2 : 3)), 0);
                        wg_fence();
                        wg_qk(s, qq, kLo);
                        wg_commit();
                        #pragma unroll
                        for (int u = 0; u < 4; u++) {
                            wg_wait<0>();
                            fence_regs<32>(s);
                            #pragma unroll
                            for (int i = 0; i < 16; i++) {
                                if ((MUFU_MASK >> i) & 1) p[i] = exp_mufu(s[2 * i], s[2 * i + 1]);
                                else p[i] = exp_sw(s[2 * i], s[2 * i + 1], cA, cB);
                            }
                            wg_fence();
                            if (u + 1 < 4) wg_qk(s, qq, kLo + (u + 1) * 128);
                            #pragma unroll
                            for (int kk = 0; kk < 4; kk++) wg_pv(o, p + 4 * kk, vLo + u * 64 + kk * 16, vHi - u * 64);
                            wg_commit();
                        }
                        kLo += 512; vLo += 256; vHi -= 256;
                    }
                    wg_wait<0>();
                } else {
                    float mx0 = -INFINITY, mx1 = -INFINITY;
                    #pragma unroll 1
                    for (int c = 0; c < SEQ / 64; c++) {
                        if (c <= 16) mbar_wait(bars + 8 * (B_KV + (c < 8 ? (c >> 2) : c < 16 ? 2 : 3)), 0);
                        wg_fence();
                        wg_qk(s, qq, kLo);
                        wg_commit();
                        wg_wait<0>();
                        fence_regs<32>(s);
                        fence_regs<12>(o);
                        float m0 = mx0, m1 = mx1;
                        #pragma unroll
                        for (int j = 0; j < 8; j++) {
                            m0 = fmaxf(m0, fmaxf(s[4 * j], s[4 * j + 1]));
                            m1 = fmaxf(m1, fmaxf(s[4 * j + 2], s[4 * j + 3]));
                        }
                        m0 = fmaxf(m0, __shfl_xor_sync(0xffffffffu, m0, 1)); m0 = fmaxf(m0, __shfl_xor_sync(0xffffffffu, m0, 2));
                        m1 = fmaxf(m1, __shfl_xor_sync(0xffffffffu, m1, 1)); m1 = fmaxf(m1, __shfl_xor_sync(0xffffffffu, m1, 2));
                        const float c0 = ex2f(mx0 - m0), c1 = ex2f(mx1 - m1);
                        mx0 = m0; mx1 = m1;
                        #pragma unroll
                        for (int j = 0; j < 3; j++) { o[4 * j] *= c0; o[4 * j + 1] *= c0; o[4 * j + 2] *= c1; o[4 * j + 3] *= c1; }
                        #pragma unroll
                        for (int j = 0; j < 8; j++) {
                            p[2 * j] = exp_mufu(s[4 * j] - m0, s[4 * j + 1] - m0);
                            p[2 * j + 1] = exp_mufu(s[4 * j + 2] - m1, s[4 * j + 3] - m1);
                        }
                        wg_fence();
                        #pragma unroll
                        for (int kk = 0; kk < 4; kk++) wg_pv(o, p + 4 * kk, vLo + kk * 16, vHi);
                        wg_commit();
                        wg_wait<0>();
                        kLo += 128; vLo += 64; vHi -= 64;
                    }
                }
                fence_regs<12>(o);
                if (tile == 0) PROFC(3);
                const float i0 = 1.0f / o[4], i1 = 1.0f / o[6];
                uint8_t* b = ob + tile * 4096;
                *(uint32_t*)(b) = pack_bf16(o[0] * i0, o[1] * i0);
                *(uint32_t*)(b + 128) = pack_bf16(o[2] * i1, o[3] * i1);
                *(uint32_t*)(b + 2048) = pack_bf16(o[8] * i0, o[9] * i0);
                *(uint32_t*)(b + 2048 + 128) = pack_bf16(o[10] * i1, o[11] * i1);
            }
        }
        PROF(10); PROFC(9);
        bar_arrive(12, 544);

        {
            float acc[16];
            #pragma unroll
            for (int i = 0; i < 16; i++) acc[i] = 0.0f;
            fence_regs<16>(acc);
            const uint64_t dA = make_desc(sb + SM_A + rowhalf * 1024, 2048, 128, 0);
            const uint64_t dB = make_desc(sb + SM_B + nh * 64, 16, 1024, 1);
            mbar_wait(bars + 8 * B_WO, 0);
            #pragma unroll 1
            for (int i = 0; i < 8; i++) {
                const int src = (hg + i) & 7;
                mbar_wait(bars + 8 * (B_O + src), 0);
                wg_fence();
                #pragma unroll
                for (int kk = 0; kk < 4; kk++) wg_ss32(acc, dA + src * 1024 + kk * 256, dB + (src * 4 + kk) * 128);
                wg_commit();
            }
            wg_wait<0>();
            fence_regs<16>(acc);
            PROF(12);
            const int row = qb * 128 + rowhalf * 64 + wiw * 16 + g;
            uint32_t* o32 = (uint32_t*)(P.out + (size_t)row * 1024 + hg * 64 + nh * 32 + 2 * t);
            #pragma unroll
            for (int j = 0; j < 4; j++) {
                o32[4 * j] = pack_bf16(acc[4 * j], acc[4 * j + 1]);
                o32[4 * j + 8 * 512] = pack_bf16(acc[4 * j + 2], acc[4 * j + 3]);
            }
        }
        PROF(13);
    }
}

typedef CUresult (*EncodeFn)(CUtensorMap*, CUtensorMapDataType, cuuint32_t, void*, const cuuint64_t*, const cuuint64_t*,
                             const cuuint32_t*, const cuuint32_t*, CUtensorMapInterleave, CUtensorMapSwizzle,
                             CUtensorMapL2promotion, CUtensorMapFloatOOBfill);

void make_map(EncodeFn fn, CUtensorMap* m, const void* ptr, uint64_t inner, uint64_t outer, uint32_t box_in, uint32_t box_out, CUtensorMapSwizzle swz) {
    cuuint64_t dims[2] = {inner, outer};
    cuuint64_t strides[1] = {inner * 2};
    cuuint32_t box[2] = {box_in, box_out};
    cuuint32_t es[2] = {1, 1};
    fn(m, CU_TENSOR_MAP_DATA_TYPE_BFLOAT16, 2, const_cast<void*>(ptr), dims, strides, box, es, CU_TENSOR_MAP_INTERLEAVE_NONE, swz,
       CU_TENSOR_MAP_L2_PROMOTION_L2_128B, CU_TENSOR_MAP_FLOAT_OOB_FILL_NONE);
}

}

extern "C" void kernel_launch(void* const* d_in, const int* in_sizes, int n_in, void* d_out, int out_size) {
    (void)in_sizes; (void)n_in; (void)out_size;
    static EncodeFn fn = nullptr;
    if (!fn) {
        void* p = nullptr;
        cudaDriverEntryPointQueryResult qr;
        cudaGetDriverEntryPoint("cuTensorMapEncodeTiled", &p, cudaEnableDefault, &qr);
        fn = (EncodeFn)p;
        cudaFuncSetAttribute(fused_kernel, cudaFuncAttributeMaxDynamicSharedMemorySize, SM_ALLOC);
    }
    CUtensorMap tx, twq, two, twk, twv, tu;
    {
        cuuint64_t dims[3] = {64, 2048, 8};
        cuuint64_t strides[2] = {1024, 128};
        cuuint32_t box[3] = {64, 128, 4};
        cuuint32_t es[3] = {1, 1, 1};
        fn(&tx, CU_TENSOR_MAP_DATA_TYPE_BFLOAT16, 3, d_in[0], dims, strides, box, es, CU_TENSOR_MAP_INTERLEAVE_NONE, CU_TENSOR_MAP_SWIZZLE_128B,
           CU_TENSOR_MAP_L2_PROMOTION_L2_128B, CU_TENSOR_MAP_FLOAT_OOB_FILL_NONE);
    }
    make_map(fn, &tu, d_in[5], 512, 2048, 8, 256, CU_TENSOR_MAP_SWIZZLE_NONE);
    make_map(fn, &twq, d_in[1], 512, 512, 64, 256, CU_TENSOR_MAP_SWIZZLE_128B);
    make_map(fn, &twk, d_in[2], 16, 512, 8, 256, CU_TENSOR_MAP_SWIZZLE_NONE);
    make_map(fn, &twv, d_in[3], 16, 512, 8, 256, CU_TENSOR_MAP_SWIZZLE_NONE);
    make_map(fn, &two, d_in[4], 512, 512, 64, 256, CU_TENSOR_MAP_SWIZZLE_128B);
    Params P;
    P.u = (const __nv_bfloat16*)d_in[5];
    P.lar = (const __nv_bfloat16*)d_in[6];
    P.aim = (const __nv_bfloat16*)d_in[7];
    P.cre = (const __nv_bfloat16*)d_in[8];
    P.cim = (const __nv_bfloat16*)d_in[9];
    P.logdt = (const __nv_bfloat16*)d_in[10];
    P.dskip = (const __nv_bfloat16*)d_in[11];
    P.out = (__nv_bfloat16*)d_out;
    fused_kernel<<<NCTA, NTHR, SM_ALLOC>>>(tx, twq, two, twk, twv, tu, P);
}
```

```cpp
#include <cuda_runtime.h>
#include <cuda_bf16.h>
#include <cuda_fp16.h>
#include <cuda.h>
#include <stdint.h>

namespace {

constexpr int SEQ = 2048;
constexpr int NCTA = 128, NTHR = 640;

constexpr int SM_A = 0;
constexpr int SM_WQ = 65536;
constexpr int SM_SLAB = SM_WQ + 32768;
constexpr int SM_K = 0, SM_V = 65536;
constexpr int SM_B = 132096;
constexpr int SM_WKV = SM_B + 65536;

constexpr int PADU = 512, ULEN = PADU + 2048;
constexpr int WPAD = 16, W3LEN = WPAD + 1024;
constexpr int TABN = 2592;
constexpr int S_U = 0;
constexpr int S_W7 = S_U + 4 * ULEN * 2;
constexpr int S_W9 = S_W7 + 4 * W3LEN * 2;
constexpr int S_TAB = S_W9 + 4 * W3LEN * 2;
constexpr int S_KC = 214016 - SM_B;
constexpr int S_Y = S_KC;
constexpr int SM_BAR = SM_B + S_KC + 16384;
constexpr int SM_TOTAL = SM_BAR + 1024;
constexpr int SM_ALLOC = SM_TOTAL + 1024;
static_assert(SM_V + 65536 + 1024 <= SM_B && SM_ALLOC <= 232448 && S_TAB + 4 * TABN * 2 <= S_KC && SM_WKV + 16384 <= SM_B + S_KC, "smem map");

constexpr int TD0 = 0, TD1 = 1072, CD = 1056;
constexpr int T3B = 2144, T3S = 224, T3C = 112, C3 = 136;

constexpr int rne8(int t) {
    if (t < 256) return t;
    int sh = 0;
    while ((t >> sh) >= 256) sh++;
    int q = t >> sh, rem = t & ((1 << sh) - 1), half = 1 << (sh - 1);
    if (rem > half || (rem == half && (q & 1))) q++;
    return q << sh;
}
constexpr int kcidx(int p) {
    if (p < 256) return (p >> 3) * 24 + (p & 7);
    if (p < 512) return ((p - 256) >> 3) * 24 + 8 + (((p - 256) & 7) >> 1);
    if (p < 1024) { int q = p - 512, hi = q >> 8, rem = q & 255; return (rem >> 3) * 24 + 12 + 2 * hi + ((rem & 7) >> 2); }
    if (p < 2048) { int q = p - 1024; return ((q & 255) >> 3) * 24 + 16 + (q >> 8); }
    return 20;
}
constexpr int KC_ZERO = 23;
constexpr int tab_dense(int t) { return (t >= 0 && t <= 1028) ? kcidx(rne8(t)) : KC_ZERO; }
constexpr int tab_3(int s, int lag) { return (lag >= 64 && lag <= 127) ? kcidx(s == 0 ? 16 * (lag + 1) : 16 * lag + 8) : KC_ZERO; }
struct TabMap {
    uint16_t v[TABN];
    constexpr TabMap() : v{} {
        for (int i = 0; i < TD1; i++) { v[TD0 + i] = tab_dense(CD - i); v[TD1 + i] = tab_dense(CD + 1 - i); }
        for (int s = 0; s < 2; s++)
            for (int i = 0; i < T3C; i++) { v[T3B + s * T3S + i] = tab_3(s, C3 - i); v[T3B + s * T3S + T3C + i] = tab_3(s, C3 + 1 - i); }
    }
};
__device__ const __align__(16) TabMap g_tabmap = TabMap();

__device__ __align__(1024) uint8_t g_kimg[65536];
__device__ __align__(1024) uint8_t g_vimg[65536 + 1024];
__device__ __align__(1024) uint8_t g_oimg[16 * 131072];
__device__ unsigned long long g_flag_kv[64];
__device__ unsigned g_flag_o[128];
__device__ unsigned g_epoch;
__device__ unsigned g_done;

#define PROF(i) do {} while (0)
#define PROF2(i) do {} while (0)
#define PROFC(i) do {} while (0)
#define PROF3(i) do {} while (0)

__device__ __forceinline__ uint32_t smem_u32(const void* p) { return (uint32_t)__cvta_generic_to_shared(p); }
__device__ __forceinline__ void mbar_init(uint32_t bar, uint32_t cnt) { asm volatile("mbarrier.init.shared::cta.b64 [%0], %1;" :: "r"(bar), "r"(cnt) : "memory"); }
__device__ __forceinline__ void mbar_expect_tx(uint32_t bar, uint32_t bytes) {
    asm volatile("mbarrier.arrive.expect_tx.shared::cta.b64 _, [%0], %1;" :: "r"(bar), "r"(bytes) : "memory"); }
__device__ __forceinline__ void mbar_wait(uint32_t bar, uint32_t parity) {
    uint32_t ok = 0;
    for (int it = 0; it < (1 << 22) && !ok; it++) {
        asm volatile("{ .reg .pred p; mbarrier.try_wait.parity.shared::cta.b64 p, [%1], %2; selp.u32 %0, 1, 0, p; }"
                     : "=r"(ok) : "r"(bar), "r"(parity) : "memory");
    }
}
__device__ __forceinline__ void tma_2d(uint32_t dst, const CUtensorMap* map, int c0, int c1, uint32_t bar) {
    asm volatile("cp.async.bulk.tensor.2d.shared::cluster.global.mbarrier::complete_tx::bytes [%0], [%1, {%3, %4}], [%2];"
                 :: "r"(dst), "l"((uint64_t)map), "r"(bar), "r"(c0), "r"(c1) : "memory");
}
__device__ __forceinline__ void tma_2d_mc(uint32_t dst, const CUtensorMap* map, int c0, int c1, uint32_t bar) {
    asm volatile("cp.async.bulk.tensor.2d.shared::cluster.global.mbarrier::complete_tx::bytes.multicast::cluster [%0], [%1, {%3, %4}], [%2], %5;"
                 :: "r"(dst), "l"((uint64_t)map), "r"(bar), "r"(c0), "r"(c1), "h"((uint16_t)3) : "memory");
}
__device__ __forceinline__ void bulk_g2s_mc(uint32_t dst, const void* src, uint32_t bytes, uint32_t bar) {
    asm volatile("cp.async.bulk.shared::cluster.global.mbarrier::complete_tx::bytes.multicast::cluster [%0], [%1], %2, [%3], %4;"
                 :: "r"(dst), "l"((uint64_t)src), "r"(bytes), "r"(bar), "h"((uint16_t)3) : "memory");
}
__device__ __forceinline__ void pair_sync(uint32_t bar, uint32_t peer) {
    uint32_t ra;
    asm volatile("mapa.shared::cluster.u32 %0, %1, %2;" : "=r"(ra) : "r"(bar), "r"(peer));
    asm volatile("mbarrier.arrive.shared::cluster.b64 _, [%0];" :: "r"(ra) : "memory");
    asm volatile("mbarrier.arrive.shared::cta.b64 _, [%0];" :: "r"(bar) : "memory");
    uint32_t ok = 0;
    for (int it = 0; it < (1 << 22) && !ok; it++) {
        asm volatile("{ .reg .pred p; mbarrier.try_wait.parity.shared::cta.b64 p, [%1], 0; selp.u32 %0, 1, 0, p; }"
                     : "=r"(ok) : "r"(bar) : "memory");
    }
}
__device__ __forceinline__ void fence_async_all() { asm volatile("fence.proxy.async.global;" ::: "memory"); }
__device__ __forceinline__ void fence_async_smem() { asm volatile("fence.proxy.async.shared::cta;" ::: "memory"); }
__device__ __forceinline__ unsigned ld_acquire(const unsigned* p) {
    unsigned v; asm volatile("ld.acquire.gpu.global.u32 %0, [%1];" : "=r"(v) : "l"(p) : "memory"); return v; }
__device__ __forceinline__ void st_release(unsigned* p, unsigned v) { asm volatile("st.release.gpu.global.u32 [%0], %1;" :: "l"(p), "r"(v) : "memory"); }
__device__ __forceinline__ void wait_flag(const unsigned* p, unsigned epoch) {
    for (int it = 0; it < (1 << 22); it++) { if (ld_acquire(p) == epoch) break; }
}
__device__ __forceinline__ unsigned long long ld_acquire64(const unsigned long long* p) {
    unsigned long long v; asm volatile("ld.acquire.gpu.global.u64 %0, [%1];" : "=l"(v) : "l"(p) : "memory"); return v; }
__device__ __forceinline__ void st_release64(unsigned long long* p, unsigned long long v) { asm volatile("st.release.gpu.global.u64 [%0], %1;" :: "l"(p), "l"(v) : "memory"); }
__device__ __forceinline__ float wait_flag64(const unsigned long long* p, unsigned epoch) {
    unsigned long long v = 0;
    for (int it = 0; it < (1 << 22); it++) { v = ld_acquire64(p); if ((unsigned)(v >> 32) == epoch) break; }
    return __uint_as_float((unsigned)v);
}
__device__ __forceinline__ void tma_3d_mc(uint32_t dst, const CUtensorMap* map, int c0, int c1, int c2, uint32_t bar) {
    asm volatile("cp.async.bulk.tensor.3d.shared::cluster.global.mbarrier::complete_tx::bytes.multicast::cluster [%0], [%1, {%3, %4, %5}], [%2], %6;"
                 :: "r"(dst), "l"((uint64_t)map), "r"(bar), "r"(c0), "r"(c1), "r"(c2), "h"((uint16_t)3) : "memory");
}
__device__ __forceinline__ void bar_sync(int id, int n) { asm volatile("bar.sync %0, %1;" :: "r"(id), "r"(n) : "memory"); }
__device__ __forceinline__ void bar_arrive(int id, int n) { asm volatile("bar.arrive %0, %1;" :: "r"(id), "r"(n) : "memory"); }
__device__ __forceinline__ void mbar_arrive(uint32_t bar) { asm volatile("mbarrier.arrive.shared::cta.b64 _, [%0];" :: "r"(bar) : "memory"); }

__device__ __forceinline__ uint64_t make_desc(uint32_t saddr, uint32_t lbo, uint32_t sbo, uint32_t swz) {
    uint64_t d = 0;
    d |= (uint64_t)((saddr & 0x3FFFF) >> 4);
    d |= (uint64_t)((lbo >> 4) & 0x3FFF) << 16;
    d |= (uint64_t)((sbo >> 4) & 0x3FFF) << 32;
    d |= (uint64_t)swz << 62;
    return d;
}
__device__ __forceinline__ void wg_fence() { asm volatile("wgmma.fence.sync.aligned;" ::: "memory"); }
__device__ __forceinline__ void wg_commit() { asm volatile("wgmma.commit_group.sync.aligned;" ::: "memory"); }
template<int N> __device__ __forceinline__ void wg_wait() { asm volatile("wgmma.wait_group.sync.aligned %0;" :: "n"(N) : "memory"); }
#define A4(d, o) "+f"(d[o + 0]), "+f"(d[o + 1]), "+f"(d[o + 2]), "+f"(d[o + 3])
#define A16(d, o) A4(d, o), A4(d, o + 4), A4(d, o + 8), A4(d, o + 12)

__device__ __forceinline__ void wg_pv(float* d, const uint32_t* a, uint32_t lo, uint32_t hi) {
    asm volatile("{ .reg .b64 dd; mov.b64 dd, {%16, %17};\n"
                 "wgmma.mma_async.sync.aligned.m64n24k16.f32.bf16.bf16 {%0,%1,%2,%3,%4,%5,%6,%7,%8,%9,%10,%11}, {%12,%13,%14,%15}, dd, 1, 1, 1, 1; }"
                 : A4(d, 0), A4(d, 4), A4(d, 8) : "r"(a[0]), "r"(a[1]), "r"(a[2]), "r"(a[3]), "r"(lo), "r"(hi));
}
__device__ __forceinline__ void wg_qk(float* d, const uint32_t* a, uint32_t lo) {
    asm volatile("{ .reg .b64 dd; mov.b64 dd, {%36, %37};\n"
                 "wgmma.mma_async.sync.aligned.m64n64k16.f32.bf16.bf16 {%0,%1,%2,%3,%4,%5,%6,%7,%8,%9,%10,%11,%12,%13,%14,%15,%16,%17,%18,%19,%20,%21,%22,%23,%24,%25,%26,%27,%28,%29,%30,%31}, {%32,%33,%34,%35}, dd, 0, 1, 1, 0; }"
                 : A16(d, 0), A16(d, 16) : "r"(a[0]), "r"(a[1]), "r"(a[2]), "r"(a[3]), "r"(lo), "r"(16));
}
__device__ __forceinline__ void wg_rs32(float* d, const uint32_t* a, uint32_t lo) {
    asm volatile("{ .reg .b64 dd; mov.b64 dd, {%20, %21};\n"
                 "wgmma.mma_async.sync.aligned.m64n32k16.f32.bf16.bf16 {%0,%1,%2,%3,%4,%5,%6,%7,%8,%9,%10,%11,%12,%13,%14,%15}, {%16,%17,%18,%19}, dd, 1, 1, 1, 0; }"
                 : A16(d, 0) : "r"(a[0]), "r"(a[1]), "r"(a[2]), "r"(a[3]), "r"(lo), "r"(0x40000040));
}
__device__ __forceinline__ void wg_rs24(float* d, const uint32_t* a, uint32_t lo) {
    asm volatile("{ .reg .b64 dd; mov.b64 dd, {%16, %17};\n"
                 "wgmma.mma_async.sync.aligned.m64n24k16.f32.bf16.bf16 {%0,%1,%2,%3,%4,%5,%6,%7,%8,%9,%10,%11}, {%12,%13,%14,%15}, dd, 1, 1, 1, 0; }"
                 : A4(d, 0), A4(d, 4), A4(d, 8) : "r"(a[0]), "r"(a[1]), "r"(a[2]), "r"(a[3]), "r"(lo), "r"(0x40000040));
}
__device__ __forceinline__ void wg_rs16(float* d, const uint32_t* a, uint32_t lo) {
    asm volatile("{ .reg .b64 dd; mov.b64 dd, {%12, %13};\n"
                 "wgmma.mma_async.sync.aligned.m64n16k16.f32.bf16.bf16 {%0,%1,%2,%3,%4,%5,%6,%7}, {%8,%9,%10,%11}, dd, 1, 1, 1, 0; }"
                 : A4(d, 0), A4(d, 4) : "r"(a[0]), "r"(a[1]), "r"(a[2]), "r"(a[3]), "r"(lo), "r"(0x40000040));
}
__device__ __forceinline__ void wg_ss32(float* d, uint64_t da, uint64_t db) {
    asm volatile("wgmma.mma_async.sync.aligned.m64n32k16.f32.bf16.bf16 {%0,%1,%2,%3,%4,%5,%6,%7,%8,%9,%10,%11,%12,%13,%14,%15}, %16, %17, 1, 1, 1, 0, 1;"
                 : A16(d, 0) : "l"(da), "l"(db));
}
__device__ __forceinline__ void wg_ss16(float* d, uint64_t da, uint64_t db) {
    asm volatile("wgmma.mma_async.sync.aligned.m64n16k16.f32.bf16.bf16 {%0,%1,%2,%3,%4,%5,%6,%7}, %8, %9, 1, 1, 1, 0, 1;"
                 : A4(d, 0), A4(d, 4) : "l"(da), "l"(db));
}
template<int N> __device__ __forceinline__ void fence_regs(float* r) {
    #pragma unroll
    for (int i = 0; i < N; i++) asm volatile("" : "+f"(r[i]) :: "memory");
}
__device__ __forceinline__ void mma_f16(float* d, const uint32_t* a, uint32_t b0, uint32_t b1) {
    asm volatile("mma.sync.aligned.m16n8k16.row.col.f32.f16.f16.f32 {%0,%1,%2,%3}, {%4,%5,%6,%7}, {%8,%9}, {%0,%1,%2,%3};"
                 : "+f"(d[0]), "+f"(d[1]), "+f"(d[2]), "+f"(d[3]) : "r"(a[0]), "r"(a[1]), "r"(a[2]), "r"(a[3]), "r"(b0), "r"(b1));
}
__device__ __forceinline__ uint32_t lds32(uint32_t addr) { uint32_t v; asm volatile("ld.shared.u32 %0, [%1];" : "=r"(v) : "r"(addr) : "memory"); return v; }
__device__ __forceinline__ void mma_bf16_p(float* d, uint32_t a0, uint32_t a1, uint32_t a2, uint32_t a3, uint32_t b0, uint32_t b1) {
    asm("mma.sync.aligned.m16n8k16.row.col.f32.bf16.bf16.f32 {%0,%1,%2,%3}, {%4,%5,%6,%7}, {%8,%9}, {%0,%1,%2,%3};"
        : "+f"(d[0]), "+f"(d[1]), "+f"(d[2]), "+f"(d[3]) : "r"(a0), "r"(a1), "r"(a2), "r"(a3), "r"(b0), "r"(b1));
}
__device__ __forceinline__ void ldsm4t_p(uint32_t* r, uint32_t addr) {
    asm("ldmatrix.sync.aligned.m8n8.x4.trans.shared.b16 {%0,%1,%2,%3}, [%4];" : "=r"(r[0]), "=r"(r[1]), "=r"(r[2]), "=r"(r[3]) : "r"(addr));
}
__device__ __forceinline__ uint32_t lds32_p(uint32_t addr) { uint32_t v; asm("ld.shared.u32 %0, [%1];" : "=r"(v) : "r"(addr)); return v; }
__device__ __forceinline__ uint32_t swz(uint32_t a) { return a ^ ((a >> 3) & 16u); }
__device__ __forceinline__ uint32_t swz128(uint32_t a) { return a ^ ((a >> 3) & 0x70u); }
__device__ __forceinline__ void sts32(uint32_t addr, uint32_t v) { asm volatile("st.shared.u32 [%0], %1;" :: "r"(addr), "r"(v) : "memory"); }
__device__ __forceinline__ void sts128(uint32_t addr, uint4 v) { asm volatile("st.shared.v4.u32 [%0], {%1,%2,%3,%4};" :: "r"(addr), "r"(v.x), "r"(v.y), "r"(v.z), "r"(v.w) : "memory"); }
__device__ __forceinline__ uint4 lds128(uint32_t addr) { uint4 v; asm volatile("ld.shared.v4.u32 {%0,%1,%2,%3}, [%4];" : "=r"(v.x), "=r"(v.y), "=r"(v.z), "=r"(v.w) : "r"(addr) : "memory"); return v; }
__device__ __forceinline__ float ex2f(float x) { float r; asm("ex2.approx.ftz.f32 %0, %1;" : "=f"(r) : "f"(x)); return r; }
__device__ __forceinline__ uint32_t pack_bf16(float lo, float hi) { uint32_t r; asm("cvt.rn.bf16x2.f32 %0, %1, %2;" : "=r"(r) : "f"(hi), "f"(lo)); return r; }
__device__ __forceinline__ uint32_t pack_f16(float lo, float hi) { uint32_t r; asm("cvt.rn.f16x2.f32 %0, %1, %2;" : "=r"(r) : "f"(hi), "f"(lo)); return r; }
__device__ __forceinline__ float bf_lo(uint32_t v) { return __uint_as_float(v << 16); }
__device__ __forceinline__ float bf_hi(uint32_t v) { return __uint_as_float(v & 0xFFFF0000u); }
__device__ __forceinline__ float bf_round(float x) { return __bfloat162float(__float2bfloat16_rn(x)); }

__device__ __forceinline__ uint32_t exp_mufu(float x0, float x1) { return pack_bf16(ex2f(x0), ex2f(x1)); }
#define SW_MAGIC (256.0f + 127.0f - 0.598938f)
__device__ __forceinline__ uint32_t exp_sw(float x0, float x1, uint32_t cA, uint32_t cB) {
    float t0 = x0 + SW_MAGIC, t1 = x1 + SW_MAGIC;
    uint32_t L, mh, ec, r;
    asm("prmt.b32 %0, %1, %2, 0x6521;" : "=r"(L) : "r"(__float_as_uint(t0)), "r"(__float_as_uint(t1)));
    asm("lop3.b32 %0, %1, 0x007F007F, %2, 0xEA;" : "=r"(mh) : "r"(L), "r"(cA));
    asm("lop3.b32 %0, %1, 0x7F807F80, %2, 0xEA;" : "=r"(ec) : "r"(L), "r"(cB));
    asm("fma.rn.bf16x2 %0, %1, %2, %3;" : "=r"(r) : "r"(L), "r"(mh), "r"(ec));
    return r;
}
constexpr uint32_t MUFU_MASK = 0x4949;

struct cf { float x, y; };
__device__ __forceinline__ cf cmul(cf a, cf b) { cf r; r.x = a.x * b.x - a.y * b.y; r.y = a.x * b.y + a.y * b.x; return r; }
__device__ __forceinline__ cf cexp_p(float a2, float b, float p) {
    float e = ex2f(a2 * p);
    float ph = b * p;
    ph -= (ph + 12582912.0f) - 12582912.0f;
    float ang = ph * 6.283185307f;
    cf r; r.x = e * __cosf(ang); r.y = e * __sinf(ang);
    return r;
}
__device__ __forceinline__ uint32_t h2_cmul(uint32_t w, uint32_t wsw, uint32_t e) {
    __half2 hw = *(__half2*)&w, hs = *(__half2*)&wsw, he = *(__half2*)&e;
    __half2 r = __hfma2(hs, __high2half2(he), __hmul2(hw, __low2half2(he)));
    return *(uint32_t*)&r;
}

template<bool B> struct BoolC { static constexpr bool value = B; };
struct Params {
    const __nv_bfloat16 *u, *lar, *aim, *cre, *cim, *logdt, *dskip;
    __nv_bfloat16* out;
};

constexpr int B_O = 0, B_KV = 8, B_WO = 12, B_WQ2 = 13, B_ST = 14, B_H = 15, B_X = 17, B_U = 19, B_WQ = 20;

__device__ __forceinline__ void helper_role(const Params& P, uint8_t* sp, uint32_t sb, unsigned epoch) {
    const uint32_t sBa = sb + SM_B;
    const int tid = threadIdx.x - 544;
    const int d0 = blockIdx.x * 4;
    uint8_t* sB = sp + SM_B;
    const uint2 dsk = __ldg((const uint2*)(P.dskip + d0));
    asm volatile("barrier.cluster.wait.aligned;" ::: "memory");
    {
        const int hg = blockIdx.x & 7;
        if (hg < 4 && tid < 32) {
            bar_sync(3, 160);
            if (tid == 0) {
                const float* s_misc = (const float*)(sp + SM_BAR + 256);
                const float st = fmaxf(fmaxf(s_misc[20], s_misc[21]), fmaxf(s_misc[22], s_misc[23]));
                st_release64(&g_flag_kv[((blockIdx.x >> 3) * 2 + (hg & 1)) * 2 + (hg >> 1)], ((unsigned long long)epoch << 32) | __float_as_uint(st));
            }
            __syncwarp();
        }
    }
    PROF2(2);
    bar_sync(10, 608);
    {
        uint32_t dd[4] = {__byte_perm(dsk.x, 0, 0x1010), __byte_perm(dsk.x, 0, 0x3232), __byte_perm(dsk.y, 0, 0x1010), __byte_perm(dsk.y, 0, 0x3232)};
        #pragma unroll 2
        for (int pi = tid; pi < 1024; pi += 96) {
            const int l = 2 * pi;
            uint32_t r[4];
            #pragma unroll
            for (int cc = 0; cc < 4; cc++) {
                const uint32_t y2 = *(const uint32_t*)(sB + S_Y + cc * 4096 + l * 2);
                const uint32_t u2 = lds32(swz128(sBa + S_U + cc * ULEN * 2 + (PADU + l) * 2));
                __nv_bfloat162 pr = __hmul2(*(const __nv_bfloat162*)&u2, *(const __nv_bfloat162*)&dd[cc]);
                __nv_bfloat162 sm = __hadd2(*(const __nv_bfloat162*)&y2, pr);
                r[cc] = *(uint32_t*)&sm;
            }
            *(uint2*)(P.out + (size_t)l * 1024 + 512 + d0) = make_uint2(__byte_perm(r[0], r[1], 0x5410), __byte_perm(r[2], r[3], 0x5410));
            *(uint2*)(P.out + (size_t)(l + 1) * 1024 + 512 + d0) = make_uint2(__byte_perm(r[0], r[1], 0x7632), __byte_perm(r[2], r[3], 0x7632));
        }
    }
    bar_arrive(11, 128);
    PROF2(4);
}

__global__ void __cluster_dims__(2, 1, 1) __launch_bounds__(NTHR, 1)
fused_kernel(const __grid_constant__ CUtensorMap tm_x, const __grid_constant__ CUtensorMap tm_wq,
             const __grid_constant__ CUtensorMap tm_wo, const __grid_constant__ CUtensorMap tm_wk,
             const __grid_constant__ CUtensorMap tm_wv, const __grid_constant__ CUtensorMap tm_u, const Params P) {
    extern __shared__ uint8_t smem_raw[];
    const uint32_t sb = (smem_u32(smem_raw) + 1023u) & ~1023u;
    uint8_t* sp = smem_raw + (sb - smem_u32(smem_raw));

    const int tid = threadIdx.x, warp = tid >> 5, lane = tid & 31, wg = tid >> 7, wiw = warp & 3;
    const int g = lane >> 2, t = lane & 3;
    const int qb = blockIdx.x >> 3, hg = blockIdx.x & 7;
    const uint32_t rank = blockIdx.x & 1;
    const int rowhalf = wg & 1, nh = wg >> 1;
    const bool kv_cta = hg < 4;
    const int kv_sel = hg >> 1;
    const bool kv_wg = kv_cta && (wg == (hg & 1));

    const uint32_t bars = sb + SM_BAR;
    float* s_misc = (float*)(sp + SM_BAR + 256);
    const CUtensorMap* tm_kv = kv_sel ? &tm_wv : &tm_wk;

    PROF(0);
    unsigned short p_lar = 0, p_aim = 0, p_cre = 0, p_cim = 0, p_ldt = 0;
    if (wg < 4) {
        const int n = (blockIdx.x * 4 + wg) * 128 + (tid & 127);
        p_lar = __ldg((const unsigned short*)P.lar + n);
        p_aim = __ldg((const unsigned short*)P.aim + n);
        p_cre = __ldg((const unsigned short*)P.cre + n);
        p_cim = __ldg((const unsigned short*)P.cim + n);
        p_ldt = __ldg((const unsigned short*)P.logdt + blockIdx.x * 4 + wg);
    } else if (warp == 16) {
        PROF3(5);
        if (lane == 0) {
            asm volatile("prefetch.tensormap [%0];" :: "l"((uint64_t)&tm_x) : "memory");
            asm volatile("prefetch.tensormap [%0];" :: "l"((uint64_t)tm_kv) : "memory");
            asm volatile("prefetch.tensormap [%0];" :: "l"((uint64_t)&tm_wq) : "memory");
            asm volatile("prefetch.tensormap [%0];" :: "l"((uint64_t)&tm_u) : "memory");
            mbar_init(bars + 8 * B_X, 1);
            mbar_init(bars + 8 * B_X + 8, 1);
            mbar_init(bars + 8 * B_U, 1);
            asm volatile("fence.mbarrier_init.release.cluster;" ::: "memory");
            mbar_expect_tx(bars + 8 * B_X, 65536u + (kv_cta ? 8192u : 0u));
            mbar_expect_tx(bars + 8 * B_X + 8, 65536u + (kv_cta ? 8192u : 0u));
            mbar_expect_tx(bars + 8 * B_U, 32768u);
        }
        __syncwarp();
        PROF3(6);
    }
    asm volatile("barrier.cluster.arrive.relaxed.aligned;" ::: "memory");
    const unsigned epoch = *(volatile unsigned*)&g_epoch + 1u;
    if (warp > 16) {
        if (lane == 0) {
            for (int i = warp - 17; i < B_X; i += 3) {
                mbar_init(bars + 8 * i, i >= B_H ? 2 : 1);
                if (i <= B_WQ2) mbar_expect_tx(bars + 8 * i, i < B_KV + 2 ? 16384u : i == B_KV + 2 ? 32768u : i <= B_WO ? 65536u : 32768u);
            }
            asm volatile("fence.mbarrier_init.release.cluster;" ::: "memory");
            fence_async_smem();
        } else if (warp == 19) {
            asm volatile("prefetch.global.L2 [%0];" :: "l"((const char*)g_tabmap.v + (lane - 1) * 128));
            if (lane < 11) asm volatile("prefetch.global.L2 [%0];" :: "l"((const char*)g_tabmap.v + (lane + 30) * 128));
        }
        __syncwarp();
    }
    asm volatile("barrier.cluster.wait.aligned;" ::: "memory");
    PROF(5);
    if (warp == 16 && lane == 0) {
        tma_3d_mc(sb + (rank ? SM_A : SM_B), &tm_x, 0, qb * 128, rank * 4, bars + 8 * (B_X + rank));
        if (kv_cta) {
            #pragma unroll
            for (int i = 0; i < 4; i++) tma_2d(sb + SM_WKV + i * 4096, tm_kv, (i >> 1) * 8, (i & 1) * 256, bars + 8 * (B_X + (i & 1)));
        }
        mbar_init(bars + 8 * B_WQ, 1);
        asm volatile("fence.mbarrier_init.release.cluster;" ::: "memory");
        fence_async_smem();
        mbar_expect_tx(bars + 8 * B_WQ, 32768u);
        tma_2d(sb + SM_WQ, &tm_wq, hg * 64, 0, bars + 8 * B_WQ);
        #pragma unroll
        for (int i = 0; i < 4; i++) tma_2d_mc(sb + SM_SLAB + (rank * 4 + i) * 4096, &tm_u, (blockIdx.x >> 1) * 8, (rank * 4 + i) * 256, bars + 8 * B_U);
    }
    __syncwarp();
    asm volatile("barrier.cluster.arrive.relaxed.aligned;" ::: "memory");

    if (warp == 16) {
        if (lane == 0) asm volatile("prefetch.tensormap [%0];" :: "l"((uint64_t)&tm_wo) : "memory");
        asm volatile("barrier.cluster.wait.aligned;" ::: "memory");
        PROF3(10);
        bar_sync(13, 544);
        if (lane == 0) { fence_async_smem(); tma_2d(sb + SM_SLAB, &tm_wq, hg * 64, 256, bars + 8 * B_WQ2); }
        bar_sync(14, 544);
        if (lane == 0) pair_sync(bars + 8 * B_H, rank ^ 1);
        __syncwarp();
        PROF3(11);
        *(uint4*)(sp + SM_V + 32768 + lane * 32) = make_uint4(0x3F803F80u, 0x3F803F80u, 0x3F803F80u, 0x3F803F80u);
        *(uint4*)(sp + SM_V + 32768 + lane * 32 + 16) = make_uint4(0x3F803F80u, 0x3F803F80u, 0x3F803F80u, 0x3F803F80u);
        fence_async_smem();
        float km = wait_flag64(&g_flag_kv[2 * lane], epoch);
        float vm = wait_flag64(&g_flag_kv[2 * lane + 1], epoch);
        __syncwarp();
        PROF3(12);
        if (lane == 0) {
            fence_async_all();
            #pragma unroll
            for (int i = 0; i < 4; i++) {
                const uint32_t k0 = i == 0 ? 0 : 128u << i, nk = i == 0 ? 256 : 128u << i;
                const uint32_t bar = bars + 8 * (B_KV + i);
                if (rank == 0) bulk_g2s_mc(sb + SM_K + k0 * 32, g_kimg + k0 * 32, nk * 32, bar);
                else {
                    bulk_g2s_mc(sb + SM_V + k0 * 16, g_vimg + k0 * 16, nk * 16, bar);
                    bulk_g2s_mc(sb + SM_V + 66560 - (k0 + nk) * 16, g_vimg + 66560 - (k0 + nk) * 16, nk * 16, bar);
                }
            }
        }
        #pragma unroll
        for (int o = 16; o; o >>= 1) { km = fmaxf(km, __shfl_xor_sync(0xffffffffu, km, o)); vm = fmaxf(vm, __shfl_xor_sync(0xffffffffu, vm, o)); }
        if (lane == 0) { s_misc[16] = km; s_misc[17] = vm; mbar_arrive(bars + 8 * B_ST); }
        PROF3(13);
        bar_sync(11, 128);
        if (lane < 2) { fence_async_smem(); tma_2d(sb + SM_B + lane * 32768, &tm_wo, hg * 64, lane * 256, bars + 8 * B_WO); }
        bar_sync(12, 544);
        if (lane == 0) {
            st_release(&g_flag_o[blockIdx.x], epoch);
            pair_sync(bars + 8 * (B_H + 1), rank ^ 1);
        }
        __syncwarp();
        PROF3(14);
        if (lane < 4) {
            const int src = 2 * lane + rank;
            wait_flag(&g_flag_o[qb * 8 + src], epoch);
            fence_async_all();
            bulk_g2s_mc(sb + SM_A + src * 16384, g_oimg + qb * 131072 + src * 16384, 16384, bars + 8 * (B_O + src));
        }
        __syncwarp();
        PROF3(15);
        if (lane == 0) {
            const unsigned prev = atomicAdd(&g_done, 1u);
            if (prev == NCTA - 1) {
                g_done = 0;
                __threadfence();
                *(volatile unsigned*)&g_epoch = epoch;
            }
        }
    } else if (wg == 4) {
        helper_role(P, sp, sb, epoch);
    } else {
        uint8_t* sB = sp + SM_B;
        const uint32_t sBa = sb + SM_B;
        {
            const int c = wg;
            const float dt = bf_round(expf(bf_lo(p_ldt)));
            const float are = -bf_round(expf(bf_lo(p_lar))) * dt;
            const float aim = bf_lo(p_aim) * dt;
            float cr = 2.0f * (bf_lo(p_cre) * dt);
            float ci = 2.0f * (bf_lo(p_cim) * dt);
            const float a2 = are * 1.4426950408889634f, bb = aim * 0.15915494309189535f;
            float m = fmaxf(fabsf(cr), fabsf(ci));
            #pragma unroll
            for (int o = 16; o; o >>= 1) m = fmaxf(m, __shfl_xor_sync(0xffffffffu, m, o));
            int ebits = (__float_as_uint(m) >> 23) & 0xFF;
            ebits = min(max(ebits, 2), 250);
            const float scale = __uint_as_float((uint32_t)(ebits + 1) << 23);
            const float iscale = __uint_as_float((uint32_t)(253 - ebits) << 23);
            cf cc; cc.x = cr * iscale; cc.y = ci * iscale;

            const uint32_t stg = sBa + S_KC + warp * 1024;
            uint4* stp = (uint4*)(sB + S_KC + warp * 1024 + lane * 32);
            const uint32_t fa = stg + t * 32 + g * 4;

            uint32_t af[4][2][4];
            cf E256;
            {
                const cf E8 = cexp_p(a2, bb, 8.0f);
                uint32_t w[8];
                cf cur; cur.x = 1.0f; cur.y = 0.0f;
                w[0] = pack_f16(1.0f, 0.0f);
                cur = E8; w[1] = pack_f16(cur.x, cur.y);
                #pragma unroll
                for (int i = 2; i < 8; i++) { cur = cmul(cur, E8); w[i] = pack_f16(cur.x, cur.y); }
                stp[0] = make_uint4(w[0], w[1], w[2], w[3]);
                stp[1] = make_uint4(w[4], w[5], w[6], w[7]);
                const cf E64 = cexp_p(a2, bb, 64.0f);
                const cf E128 = cmul(E64, E64), E192 = cmul(E128, E64);
                E256 = cexp_p(a2, bb, 256.0f);
                const uint32_t e1 = pack_f16(E64.x, E64.y), e2 = pack_f16(E128.x, E128.y), e3 = pack_f16(E192.x, E192.y);
                __syncwarp();
                #pragma unroll
                for (int s = 0; s < 4; s++) {
                    #pragma unroll
                    for (int hh = 0; hh < 2; hh++) {
                        const uint32_t w0 = lds32(fa + s * 256 + hh * 128);
                        const uint32_t wsw = __byte_perm(w0, 0, 0x1032) ^ 0x00008000u;
                        const int src = 8 * s + t + 4 * hh;
                        const uint32_t f1 = __shfl_sync(0xffffffffu, e1, src), f2 = __shfl_sync(0xffffffffu, e2, src), f3 = __shfl_sync(0xffffffffu, e3, src);
                        af[s][0][2 * hh] = w0;
                        af[s][0][2 * hh + 1] = h2_cmul(w0, wsw, f1);
                        af[s][1][2 * hh] = h2_cmul(w0, wsw, f2);
                        af[s][1][2 * hh + 1] = h2_cmul(w0, wsw, f3);
                    }
                }
                __syncwarp();
            }
            float acc[2][3][4];
            #pragma unroll
            for (int i = 0; i < 24; i++) (&acc[0][0][0])[i] = 0.0f;
            const cf E1 = cexp_p(a2, bb, 1.0f);
            const cf E2 = cmul(E1, E1), E4 = cmul(E2, E2);
            cf X512;
            #pragma unroll
            for (int nt = 0; nt < 3; nt++) {
                uint32_t xv[8];
                if (nt == 0) {
                    cf cur = cc;
                    xv[0] = pack_f16(cur.x, -cur.y);
                    #pragma unroll
                    for (int i = 1; i < 8; i++) { cur = cmul(cur, E1); xv[i] = pack_f16(cur.x, -cur.y); }
                } else if (nt == 1) {
                    cf cur = cmul(cc, E256);
                    X512 = cmul(cur, E256);
                    xv[0] = pack_f16(cur.x, -cur.y);
                    #pragma unroll
                    for (int i = 1; i < 4; i++) { cur = cmul(cur, E2); xv[i] = pack_f16(cur.x, -cur.y); }
                    cur = cmul(X512, E4);
                    xv[4] = pack_f16(X512.x, -X512.y); xv[5] = pack_f16(cur.x, -cur.y);
                    X512 = cmul(X512, E256);
                    cur = cmul(X512, E4);
                    xv[6] = pack_f16(X512.x, -X512.y); xv[7] = pack_f16(cur.x, -cur.y);
                } else {
                    cf cur = X512;
                    #pragma unroll
                    for (int i = 0; i < 5; i++) { cur = cmul(cur, E256); xv[i] = pack_f16(cur.x, -cur.y); }
                    xv[5] = 0; xv[6] = 0; xv[7] = 0;
                }
                stp[0] = make_uint4(xv[0], xv[1], xv[2], xv[3]);
                stp[1] = make_uint4(xv[4], xv[5], xv[6], xv[7]);
                __syncwarp();
                #pragma unroll
                for (int s = 0; s < 4; s++) {
                    const uint32_t b0 = lds32(fa + s * 256), b1 = lds32(fa + s * 256 + 128);
                    mma_f16(acc[0][nt], af[s][0], b0, b1);
                    mma_f16(acc[1][nt], af[s][1], b0, b1);
                }
                __syncwarp();
            }
            float* kc = (float*)(sB + S_KC + c * 4096);
            bar_sync(4 + c, 128);
            #pragma unroll 1
            for (int step = 0; step < 4; step++) {
                if ((warp & 3) == step) {
                    #pragma unroll
                    for (int mt = 0; mt < 2; mt++)
                        #pragma unroll
                        for (int nt = 0; nt < 3; nt++)
                            #pragma unroll
                            for (int hh = 0; hh < 2; hh++) {
                                float2* p = (float2*)(kc + (mt * 16 + hh * 8 + g) * 24 + nt * 8 + 2 * t);
                                float2 v = make_float2(acc[mt][nt][2 * hh] * scale, acc[mt][nt][2 * hh + 1] * scale);
                                if (step) { float2 o = *p; v.x += o.x; v.y += o.y; }
                                *p = v;
                            }
                }
                if (step < 3) bar_sync(4 + c, 128);
            }
        }

        asm volatile("barrier.cluster.wait.aligned;" ::: "memory");
        PROF(4);
        uint32_t q[2][4];
        {
            float acc[16], akv[8];
            #pragma unroll
            for (int i = 0; i < 16; i++) acc[i] = 0.0f;
            #pragma unroll
            for (int i = 0; i < 8; i++) akv[i] = 0.0f;
            fence_regs<16>(acc);
            fence_regs<8>(akv);
            const uint64_t dA0 = make_desc(sb + SM_B + rowhalf * 8192, 16, 1024, 1);
            const uint64_t dA1 = make_desc(sb + SM_A + rowhalf * 8192, 16, 1024, 1) - 4096;
            const uint64_t dB = make_desc(sb + SM_WQ + nh * 64, 16, 1024, 1);
            const uint64_t dC = make_desc(sb + SM_WKV, 128, 8192, 0);
            if (kv_wg) {
                #pragma unroll 1
                for (int ch = 0; ch < 8; ch++) {
                    if ((ch & 3) == 0) mbar_wait(bars + 8 * (B_X + (ch >> 2)), 0);
                    const uint64_t dA = ch < 4 ? dA0 : dA1;
                    wg_fence();
                    #pragma unroll
                    for (int ks = 0; ks < 4; ks++) wg_ss16(akv, dA + ch * 1024 + ks * 2, dC + (ch * 4 + ks) * 16);
                    wg_commit();
                }
                wg_wait<0>();
            }
            fence_regs<8>(akv);
            if (kv_wg) {
                const int key = qb * 128 + rowhalf * 64 + wiw * 16 + g;
                uint32_t pk[4];
                #pragma unroll
                for (int i = 0; i < 4; i++) pk[i] = pack_bf16(akv[2 * i], akv[2 * i + 1]);
                float st;
                if (kv_sel == 0) {
                    uint8_t* b = g_kimg + (key >> 3) * 256 + (key & 7) * 16 + 4 * t;
                    *(uint32_t*)(b) = pk[0]; *(uint32_t*)(b + 256) = pk[1]; *(uint32_t*)(b + 128) = pk[2]; *(uint32_t*)(b + 384) = pk[3];
                    float n0 = bf_lo(pk[0]) * bf_lo(pk[0]) + bf_hi(pk[0]) * bf_hi(pk[0]) + bf_lo(pk[2]) * bf_lo(pk[2]) + bf_hi(pk[2]) * bf_hi(pk[2]);
                    float n1 = bf_lo(pk[1]) * bf_lo(pk[1]) + bf_hi(pk[1]) * bf_hi(pk[1]) + bf_lo(pk[3]) * bf_lo(pk[3]) + bf_hi(pk[3]) * bf_hi(pk[3]);
                    n0 += __shfl_xor_sync(0xffffffffu, n0, 1); n0 += __shfl_xor_sync(0xffffffffu, n0, 2);
                    n1 += __shfl_xor_sync(0xffffffffu, n1, 1); n1 += __shfl_xor_sync(0xffffffffu, n1, 2);
                    st = (n0 != n0 || n1 != n1) ? __int_as_float(0x7f800000) : fmaxf(n0, n1);
                } else {
                    uint8_t* lo = g_vimg + key * 16 + 4 * t;
                    uint8_t* hi = g_vimg + 33792 + (31 - (key >> 6)) * 1024 + (key & 63) * 16 + 4 * t;
                    *(uint32_t*)(lo) = pk[0]; *(uint32_t*)(lo + 128) = pk[1]; *(uint32_t*)(hi) = pk[2]; *(uint32_t*)(hi + 128) = pk[3];
                    st = 0.0f;
                    #pragma unroll
                    for (int i = 0; i < 4; i++) {
                        float a = fabsf(bf_lo(pk[i])), b = fabsf(bf_hi(pk[i]));
                        st = (a != a || b != b) ? __int_as_float(0x7f800000) : fmaxf(st, fmaxf(a, b));
                    }
                }
                #pragma unroll
                for (int o = 16; o; o >>= 1) st = fmaxf(st, __shfl_xor_sync(0xffffffffu, st, o));
                if (lane == 0) s_misc[20 + wiw] = st;
                bar_arrive(3, 160);
            }
            uint32_t mp[11];
            #pragma unroll
            for (int i = 0; i < 11; i++) { const int w = (tid & 127) + 128 * i; mp[i] = (w < TABN / 2) ? __ldg((const uint32_t*)g_tabmap.v + w) : 0u; }
            mbar_wait(bars + 8 * B_WQ, 0);
            mbar_wait(bars + 8 * B_X, 0);
            PROF(2);
            #pragma unroll 1
            for (int ch = 0; ch < 4; ch++) {
                wg_fence();
                #pragma unroll
                for (int ks = 0; ks < 4; ks++) wg_ss32(acc, dA0 + ch * 1024 + ks * 2, dB + (ch * 4 + ks) * 128);
                wg_commit();
            }
            wg_wait<0>();
            fence_regs<16>(acc);
            bar_sync(1, 512);
            PROF(15);
            if (tid < 4 * (PADU / 8)) sts128(sBa + S_U + (tid / (PADU / 8)) * ULEN * 2 + (tid % (PADU / 8)) * 16, make_uint4(0, 0, 0, 0));
            PROF(8);
            mbar_wait(bars + 8 * B_U, 0);
            PROF(14);
            #pragma unroll
            for (int i = 0; i < 2; i++) {
                const int l = 2 * (tid + 512 * i);
                const uint2 r0 = *(const uint2*)(sp + SM_SLAB + l * 16 + rank * 8), r1 = *(const uint2*)(sp + SM_SLAB + l * 16 + 16 + rank * 8);
                const uint32_t dst = swz128(sBa + S_U + (PADU + l) * 2);
                sts32(dst, __byte_perm(r0.x, r1.x, 0x5410));
                sts32(dst + ULEN * 2, __byte_perm(r0.x, r1.x, 0x7632));
                sts32(dst + ULEN * 4, __byte_perm(r0.y, r1.y, 0x5410));
                sts32(dst + ULEN * 6, __byte_perm(r0.y, r1.y, 0x7632));
            }
            bar_arrive(13, 544);
            {
                const float* kc = (const float*)(sB + S_KC + wg * 4096);
                uint32_t* tab = (uint32_t*)(sB + S_TAB + wg * TABN * 2);
                #pragma unroll
                for (int i = 0; i < 11; i++) { const int w = (tid & 127) + 128 * i; if (w < TABN / 2) tab[w] = pack_bf16(kc[mp[i] & 0xFFFF], kc[mp[i] >> 16]); }
            }
            fence_async_smem();
            bar_sync(1, 512);
            PROF(1);
            mbar_wait(bars + 8 * B_WQ2, 0);
            mbar_wait(bars + 8 * (B_X + 1), 0);
            fence_regs<16>(acc);
            wg_fence();
            #pragma unroll
            for (int ks = 16; ks < 32; ks++) wg_ss32(acc, dA1 + (ks >> 2) * 1024 + (ks & 3) * 2, dB + ks * 128);
            wg_commit();
            {
                const int task = tid + (tid < 8 ? 512 : 0) * 0;
                #pragma unroll 1
                for (int tk = task; tk < 4 * 130; tk += 512) {
                    const int c = tk / 130, i = tk % 130;
                    const uint32_t src = sBa + S_U + c * ULEN * 2 + (PADU + 8 * i - WPAD - 8) * 2;
                    const uint4 v0 = lds128(swz128(src)), v1 = lds128(swz128(src + 16)), v2 = lds128(swz128(src + 32));
                    float x[16];
                    const uint32_t vv[8] = {v0.z, v0.w, v1.x, v1.y, v1.z, v1.w, v2.x, v2.y};
                    #pragma unroll
                    for (int k = 0; k < 8; k++) { x[2 * k] = bf_lo(vv[k]); x[2 * k + 1] = bf_hi(vv[k]); }
                    float p2[15], w7[8], w9[8];
                    #pragma unroll
                    for (int e = 0; e < 15; e++) p2[e] = x[e] + x[e + 1];
                    #pragma unroll
                    for (int e = 0; e < 8; e++) {
                        w7[e] = (p2[e + 1] + p2[e + 3]) + (p2[e + 5] + x[e + 7]);
                        w9[e] = w7[e] + (x[e] + x[e + 8]);
                    }
                    sts128(swz(sBa + S_W7 + c * W3LEN * 2 + i * 16), make_uint4(pack_bf16(w7[0], w7[1]), pack_bf16(w7[2], w7[3]), pack_bf16(w7[4], w7[5]), pack_bf16(w7[6], w7[7])));
                    sts128(swz(sBa + S_W9 + c * W3LEN * 2 + i * 16), make_uint4(pack_bf16(w9[0], w9[1]), pack_bf16(w9[2], w9[3]), pack_bf16(w9[4], w9[5]), pack_bf16(w9[6], w9[7])));
                }
            }
            wg_wait<0>();
            fence_regs<16>(acc);
            bar_arrive(14, 544);
            const float QS = 0.25f * 1.4426950408889634f;
            float qm = 0.0f;
            #pragma unroll
            for (int i = 0; i < 2; i++) {
                #pragma unroll
                for (int j = 0; j < 4; j++) q[i][j] = pack_bf16(acc[8 * i + 2 * j] * QS, acc[8 * i + 2 * j + 1] * QS);
                float n0 = bf_lo(q[i][0]) * bf_lo(q[i][0]) + bf_hi(q[i][0]) * bf_hi(q[i][0]) + bf_lo(q[i][2]) * bf_lo(q[i][2]) + bf_hi(q[i][2]) * bf_hi(q[i][2]);
                float n1 = bf_lo(q[i][1]) * bf_lo(q[i][1]) + bf_hi(q[i][1]) * bf_hi(q[i][1]) + bf_lo(q[i][3]) * bf_lo(q[i][3]) + bf_hi(q[i][3]) * bf_hi(q[i][3]);
                n0 += __shfl_xor_sync(0xffffffffu, n0, 1); n0 += __shfl_xor_sync(0xffffffffu, n0, 2);
                n1 += __shfl_xor_sync(0xffffffffu, n1, 1); n1 += __shfl_xor_sync(0xffffffffu, n1, 2);
                qm = (n0 != n0 || n1 != n1) ? __int_as_float(0x7f800000) : fmaxf(qm, fmaxf(n0, n1));
            }
            #pragma unroll
            for (int o = 16; o; o >>= 1) qm = fmaxf(qm, __shfl_xor_sync(0xffffffffu, qm, o));
            if (lane == 0) s_misc[warp] = qm;
        }
        PROF(3);
        {
            const int c = wg;
            uint32_t sBl = sBa;
            asm volatile("" : "+r"(sBl) :: "memory");
            float acc[16], accB[12], accC[8];
            #pragma unroll
            for (int i = 0; i < 16; i++) acc[i] = 0.0f;
            #pragma unroll
            for (int i = 0; i < 12; i++) accB[i] = 0.0f;
            #pragma unroll
            for (int i = 0; i < 8; i++) accC[i] = 0.0f;
            fence_regs<16>(acc); fence_regs<12>(accB); fence_regs<8>(accC);
            const uint32_t tabc = sBl + S_TAB + c * TABN * 2;
            const uint32_t tD = tabc + ((g & 1) ? (TD1 + CD + 1) : (TD0 + CD)) * 2 - (g - 2 * t) * 2 - 32 * wiw;
            const uint32_t uLo = (((sBl + S_U + c * ULEN * 2 + PADU * 2) & 0x3FFFF) >> 4) | (1u << 16);
            uint32_t A[2][4][4];
            auto load_set = [&](uint32_t (&X)[4][4], int m0) {
                #pragma unroll
                for (int i = 0; i < 4; i++) {
                    const int kap = m0 + i + wiw;
                    const uint32_t a = tD - 32 * ((kap >= 0 && kap <= 65) ? m0 + i : -1 - wiw);
                    X[i][0] = lds32(a); X[i][1] = lds32(a - 16); X[i][2] = lds32(a + 16); X[i][3] = lds32(a);
                    if (kap < 0 || kap > 65) { X[i][0] = 0; X[i][1] = 0; X[i][2] = 0; X[i][3] = 0; }
                }
            };
            #pragma unroll 1
            for (int m0 = -3; m0 < 29; m0 += 8) {
                #pragma unroll
                for (int h = 0; h < 2; h++) {
                    load_set(A[h], m0 + 4 * h);
                    wg_fence();
                    #pragma unroll
                    for (int i = 0; i < 4; i++) wg_rs32(acc, A[h][i], uLo - 2 * (m0 + 4 * h + i));
                    wg_commit();
                    wg_wait<1>();
                }
            }
            #pragma unroll 1
            for (int m0 = 29; m0 < 61; m0 += 8) {
                #pragma unroll
                for (int h = 0; h < 2; h++) {
                    load_set(A[h], m0 + 4 * h);
                    wg_fence();
                    #pragma unroll
                    for (int i = 0; i < 4; i++) wg_rs24(accB, A[h][i], uLo + 64 - 2 * (m0 + 4 * h + i));
                    wg_commit();
                    wg_wait<1>();
                }
            }
            load_set(A[0], 61);
            wg_fence();
            #pragma unroll
            for (int i = 0; i < 4; i++) wg_rs16(accC, A[0][i], uLo + 128 - 2 * (61 + i));
            wg_commit();
            wg_wait<1>();
            load_set(A[1], 65);
            wg_fence();
            wg_rs16(accC, A[1][0], uLo + 128 - 2 * 65);
            wg_commit();
            bar_sync(1, 512);
            wg_wait<0>();
            fence_regs<16>(acc); fence_regs<12>(accB); fence_regs<8>(accC);
            #pragma unroll
            for (int i = 0; i < 12; i++) acc[4 + i] += accB[i];
            #pragma unroll
            for (int i = 0; i < 8; i++) acc[8 + i] += accC[i];
            PROF(6);
            {
                asm volatile("" : "+r"(sBl) :: "memory");
                const int mi = lane >> 3, r8 = lane & 7;
                const uint32_t frag = (16 * (8 * (mi >> 1) + r8) + 8 * (mi & 1)) * 2;
                const uint32_t t3 = sBl + S_TAB + c * TABN * 2 + (T3B + ((wiw & 1) ? (T3C + C3 + 1) : C3)) * 2 - (4 * g + wiw - 2 * t) * 2;
                #pragma unroll
                for (int s = 0; s < 2; s++) {
                    const uint32_t sig = swz(sBl + (s ? S_W7 : S_W9) + c * W3LEN * 2 + WPAD * 2 + frag - (s ? 16 : 32));
                    uint32_t a[4][4], R[4][2];
                    #pragma unroll
                    for (int b = 0; b < 4; b++) ldsm4t_p(a[b], sig + b * 512);
                    #pragma unroll
                    for (int i = 0; i < 4; i++) { R[i][0] = lds32_p(t3 + s * (T3S * 2) - 2 * (48 + 16 * i)); R[i][1] = lds32_p(t3 + s * (T3S * 2) - 2 * (40 + 16 * i)); }
                    #pragma unroll
                    for (int b = 0; b < 4; b++) {
                        mma_bf16_p(acc + 12, a[b][0], a[b][1], a[b][2], a[b][3], R[3 - b][0], R[3 - b][1]);
                        if (b < 2) mma_bf16_p(acc + 8, a[b][0], a[b][1], a[b][2], a[b][3], R[1 - b][0], R[1 - b][1]);
                    }
                }
            }
            __nv_bfloat16* ys = (__nv_bfloat16*)(sB + S_Y + c * 4096) + 128 * t + 16 * wiw + g;
            #pragma unroll
            for (int j = 0; j < 4; j++) {
                ys[512 * j] = __float2bfloat16_rn(acc[4 * j]);
                ys[512 * j + 64] = __float2bfloat16_rn(acc[4 * j + 1]);
                ys[512 * j + 8] = __float2bfloat16_rn(acc[4 * j + 2]);
                ys[512 * j + 72] = __float2bfloat16_rn(acc[4 * j + 3]);
            }
        }
        bar_arrive(10, 608);
        PROF(7);
        {
            mbar_wait(bars + 8 * B_ST, 0);
            PROF(9); PROFC(8);
            float qm = 0.0f;
            #pragma unroll
            for (int i = 0; i < 16; i++) qm = fmaxf(qm, s_misc[i]);
            const float vm = s_misc[17];
            const bool fast = (qm * s_misc[16] <= 60.0f * 60.0f) && (vm <= 1.0e12f) && (vm >= 1.0e-12f || vm == 0.0f);
            uint8_t* ob = g_oimg + qb * 131072 + hg * 16384 + nh * 8192 + (rowhalf * 8 + wiw * 2) * 128 + g * 16 + 4 * t;
            uint32_t cA = 0xBF00BF00u, cB = 0x00030003u;
            asm volatile("" : "+r"(cA), "+r"(cB));
            #pragma unroll 1
            for (int tile = 0; tile < 2; tile++) {
                uint32_t kLo = (((sb + SM_K) & 0x3FFFF) >> 4) | (8u << 16), vLo = (((sb + SM_V) & 0x3FFFF) >> 4) | (8u << 16), vHi = 2048;
                float o[12], s[32];
                uint32_t p[16], qq[4];
                #pragma unroll
                for (int i = 0; i < 4; i++) { qq[i] = tile ? q[1][i] : q[0][i]; asm volatile("" : "+r"(qq[i])); }
                #pragma unroll
                for (int i = 0; i < 12; i++) o[i] = 0.0f;
                #pragma unroll
                for (int i = 0; i < 32; i++) s[i] = 0.0f;
                fence_regs<12>(o);
                fence_regs<32>(s);
                if (fast) {
                    #pragma unroll 1
                    for (int c = 0; c < SEQ / 256; c++) {
                        if (c <= 4) mbar_wait(bars + 8 * (B_KV + (c < 2 ? c : c < 4 ? 2 : 3)), 0);
                        wg_fence();
                        wg_qk(s, qq, kLo);
                        wg_commit();
                        #pragma unroll
                        for (int u = 0; u < 4; u++) {
                            wg_wait<0>();
                            fence_regs<32>(s);
                            #pragma unroll
                            for (int i = 0; i < 16; i++) {
                                if ((MUFU_MASK >> i) & 1) p[i] = exp_mufu(s[2 * i], s[2 * i + 1]);
                                else p[i] = exp_sw(s[2 * i], s[2 * i + 1], cA, cB);
                            }
                            wg_fence();
                            if (u + 1 < 4) wg_qk(s, qq, kLo + (u + 1) * 128);
                            #pragma unroll
                            for (int kk = 0; kk < 4; kk++) wg_pv(o, p + 4 * kk, vLo + u * 64 + kk * 16, vHi - u * 64);
                            wg_commit();
                        }
                        kLo += 512; vLo += 256; vHi -= 256;
                    }
                    wg_wait<0>();
                } else {
                    float mx0 = -INFINITY, mx1 = -INFINITY;
                    #pragma unroll 1
                    for (int c = 0; c < SEQ / 64; c++) {
                        if (c <= 16) mbar_wait(bars + 8 * (B_KV + (c < 8 ? (c >> 2) : c < 16 ? 2 : 3)), 0);
                        wg_fence();
                        wg_qk(s, qq, kLo);
                        wg_commit();
                        wg_wait<0>();
                        fence_regs<32>(s);
                        fence_regs<12>(o);
                        float m0 = mx0, m1 = mx1;
                        #pragma unroll
                        for (int j = 0; j < 8; j++) {
                            m0 = fmaxf(m0, fmaxf(s[4 * j], s[4 * j + 1]));
                            m1 = fmaxf(m1, fmaxf(s[4 * j + 2], s[4 * j + 3]));
                        }
                        m0 = fmaxf(m0, __shfl_xor_sync(0xffffffffu, m0, 1)); m0 = fmaxf(m0, __shfl_xor_sync(0xffffffffu, m0, 2));
                        m1 = fmaxf(m1, __shfl_xor_sync(0xffffffffu, m1, 1)); m1 = fmaxf(m1, __shfl_xor_sync(0xffffffffu, m1, 2));
                        const float c0 = ex2f(mx0 - m0), c1 = ex2f(mx1 - m1);
                        mx0 = m0; mx1 = m1;
                        #pragma unroll
                        for (int j = 0; j < 3; j++) { o[4 * j] *= c0; o[4 * j + 1] *= c0; o[4 * j + 2] *= c1; o[4 * j + 3] *= c1; }
                        #pragma unroll
                        for (int j = 0; j < 8; j++) {
                            p[2 * j] = exp_mufu(s[4 * j] - m0, s[4 * j + 1] - m0);
                            p[2 * j + 1] = exp_mufu(s[4 * j + 2] - m1, s[4 * j + 3] - m1);
                        }
                        wg_fence();
                        #pragma unroll
                        for (int kk = 0; kk < 4; kk++) wg_pv(o, p + 4 * kk, vLo + kk * 16, vHi);
                        wg_commit();
                        wg_wait<0>();
                        kLo += 128; vLo += 64; vHi -= 64;
                    }
                }
                fence_regs<12>(o);
                if (tile == 0) PROFC(3);
                const float i0 = 1.0f / o[4], i1 = 1.0f / o[6];
                uint8_t* b = ob + tile * 4096;
                *(uint32_t*)(b) = pack_bf16(o[0] * i0, o[1] * i0);
                *(uint32_t*)(b + 128) = pack_bf16(o[2] * i1, o[3] * i1);
                *(uint32_t*)(b + 2048) = pack_bf16(o[8] * i0, o[9] * i0);
                *(uint32_t*)(b + 2048 + 128) = pack_bf16(o[10] * i1, o[11] * i1);
            }
        }
        PROF(10); PROFC(9);
        bar_arrive(12, 544);

        {
            float acc[16];
            #pragma unroll
            for (int i = 0; i < 16; i++) acc[i] = 0.0f;
            fence_regs<16>(acc);
            const uint64_t dA = make_desc(sb + SM_A + rowhalf * 1024, 2048, 128, 0);
            const uint64_t dB = make_desc(sb + SM_B + nh * 64, 16, 1024, 1);
            mbar_wait(bars + 8 * B_WO, 0);
            #pragma unroll 1
            for (int i = 0; i < 8; i++) {
                const int src = (hg + i) & 7;
                mbar_wait(bars + 8 * (B_O + src), 0);
                wg_fence();
                #pragma unroll
                for (int kk = 0; kk < 4; kk++) wg_ss32(acc, dA + src * 1024 + kk * 256, dB + (src * 4 + kk) * 128);
                wg_commit();
            }
            wg_wait<0>();
            fence_regs<16>(acc);
            PROF(12);
            const int row = qb * 128 + rowhalf * 64 + wiw * 16 + g;
            uint32_t* o32 = (uint32_t*)(P.out + (size_t)row * 1024 + hg * 64 + nh * 32 + 2 * t);
            #pragma unroll
            for (int j = 0; j < 4; j++) {
                o32[4 * j] = pack_bf16(acc[4 * j], acc[4 * j + 1]);
                o32[4 * j + 8 * 512] = pack_bf16(acc[4 * j + 2], acc[4 * j + 3]);
            }
        }
        PROF(13);
    }
}

typedef CUresult (*EncodeFn)(CUtensorMap*, CUtensorMapDataType, cuuint32_t, void*, const cuuint64_t*, const cuuint64_t*,
                             const cuuint32_t*, const cuuint32_t*, CUtensorMapInterleave, CUtensorMapSwizzle,
                             CUtensorMapL2promotion, CUtensorMapFloatOOBfill);

void make_map(EncodeFn fn, CUtensorMap* m, const void* ptr, uint64_t inner, uint64_t outer, uint32_t box_in, uint32_t box_out, CUtensorMapSwizzle swz) {
    cuuint64_t dims[2] = {inner, outer};
    cuuint64_t strides[1] = {inner * 2};
    cuuint32_t box[2] = {box_in, box_out};
    cuuint32_t es[2] = {1, 1};
    fn(m, CU_TENSOR_MAP_DATA_TYPE_BFLOAT16, 2, const_cast<void*>(ptr), dims, strides, box, es, CU_TENSOR_MAP_INTERLEAVE_NONE, swz,
       CU_TENSOR_MAP_L2_PROMOTION_L2_128B, CU_TENSOR_MAP_FLOAT_OOB_FILL_NONE);
}

}

extern "C" void kernel_launch(void* const* d_in, const int* in_sizes, int n_in, void* d_out, int out_size) {
    (void)in_sizes; (void)n_in; (void)out_size;
    static EncodeFn fn = nullptr;
    if (!fn) {
        void* p = nullptr;
        cudaDriverEntryPointQueryResult qr;
        cudaGetDriverEntryPoint("cuTensorMapEncodeTiled", &p, cudaEnableDefault, &qr);
        fn = (EncodeFn)p;
        cudaFuncSetAttribute(fused_kernel, cudaFuncAttributeMaxDynamicSharedMemorySize, SM_ALLOC);
    }
    CUtensorMap tx, twq, two, twk, twv, tu;
    {
        cuuint64_t dims[3] = {64, 2048, 8};
        cuuint64_t strides[2] = {1024, 128};
        cuuint32_t box[3] = {64, 128, 4};
        cuuint32_t es[3] = {1, 1, 1};
        fn(&tx, CU_TENSOR_MAP_DATA_TYPE_BFLOAT16, 3, d_in[0], dims, strides, box, es, CU_TENSOR_MAP_INTERLEAVE_NONE, CU_TENSOR_MAP_SWIZZLE_128B,
           CU_TENSOR_MAP_L2_PROMOTION_L2_128B, CU_TENSOR_MAP_FLOAT_OOB_FILL_NONE);
    }
    make_map(fn, &tu, d_in[5], 512, 2048, 8, 256, CU_TENSOR_MAP_SWIZZLE_NONE);
    make_map(fn, &twq, d_in[1], 512, 512, 64, 256, CU_TENSOR_MAP_SWIZZLE_128B);
    make_map(fn, &twk, d_in[2], 16, 512, 8, 256, CU_TENSOR_MAP_SWIZZLE_NONE);
    make_map(fn, &twv, d_in[3], 16, 512, 8, 256, CU_TENSOR_MAP_SWIZZLE_NONE);
    make_map(fn, &two, d_in[4], 512, 512, 64, 256, CU_TENSOR_MAP_SWIZZLE_128B);
    Params P;
    P.u = (const __nv_bfloat16*)d_in[5];
    P.lar = (const __nv_bfloat16*)d_in[6];
    P.aim = (const __nv_bfloat16*)d_in[7];
    P.cre = (const __nv_bfloat16*)d_in[8];
    P.cim = (const __nv_bfloat16*)d_in[9];
    P.logdt = (const __nv_bfloat16*)d_in[10];
    P.dskip = (const __nv_bfloat16*)d_in[11];
    P.out = (__nv_bfloat16*)d_out;
    fused_kernel<<<NCTA, NTHR, SM_ALLOC>>>(tx, twq, two, twk, twv, tu, P);
}
```

```cpp
#include <cuda_runtime.h>
#include <cuda_bf16.h>
#include <cuda_fp16.h>
#include <cuda.h>
#include <stdint.h>

namespace {

constexpr int SEQ = 2048;
constexpr int NCTA = 128, NTHR = 640;

constexpr int SM_A = 0;
constexpr int SM_WQ = 65536;
constexpr int SM_SLAB = SM_WQ + 32768;
constexpr int SM_K = 0, SM_V = 65536;
constexpr int SM_B = 132096;
constexpr int SM_WKV = SM_B + 65536;

constexpr int PADU = 1536, ULEN = PADU + 2048;
constexpr int WPAD = 16, W3LEN = WPAD + 1024;
constexpr int TABN = 2592;
constexpr int S_U = 0;
constexpr int S_W7 = S_U + 4 * ULEN * 2;
constexpr int S_W9 = S_W7 + 4 * W3LEN * 2;
constexpr int S_TAB = S_W9 + 4 * W3LEN * 2;
constexpr int S_KC = 214016 - SM_B;
constexpr int S_Y = S_KC;
constexpr int SM_BAR = SM_B + S_KC + 16384;
constexpr int SM_TOTAL = SM_BAR + 1024;
constexpr int SM_ALLOC = SM_TOTAL + 1024;
static_assert(SM_V + 65536 + 1024 <= SM_B && SM_ALLOC <= 232448 && S_TAB + 4 * TABN * 2 <= S_KC && SM_WKV + 16384 <= SM_B + S_KC, "smem map");

constexpr int TD0 = 0, TD1 = 1072, CD = 1056;
constexpr int T3B = 2144, T3S = 224, T3C = 112, C3 = 136;

constexpr int rne8(int t) {
    if (t < 256) return t;
    int sh = 0;
    while ((t >> sh) >= 256) sh++;
    int q = t >> sh, rem = t & ((1 << sh) - 1), half = 1 << (sh - 1);
    if (rem > half || (rem == half && (q & 1))) q++;
    return q << sh;
}
constexpr int kcidx(int p) {
    if (p < 256) return (p >> 3) * 24 + (p & 7);
    if (p < 512) return ((p - 256) >> 3) * 24 + 8 + (((p - 256) & 7) >> 1);
    if (p < 1024) { int q = p - 512, hi = q >> 8, rem = q & 255; return (rem >> 3) * 24 + 12 + 2 * hi + ((rem & 7) >> 2); }
    if (p < 2048) { int q = p - 1024; return ((q & 255) >> 3) * 24 + 16 + (q >> 8); }
    return 20;
}
constexpr int KC_ZERO = 23;
constexpr int tab_dense(int t) { return (t >= 0 && t <= 1028) ? kcidx(rne8(t)) : KC_ZERO; }
constexpr int tab_3(int s, int lag) { return (lag >= 64 && lag <= 127) ? kcidx(s == 0 ? 16 * (lag + 1) : 16 * lag + 8) : KC_ZERO; }
struct TabMap {
    uint16_t v[TABN];
    constexpr TabMap() : v{} {
        for (int i = 0; i < TD1; i++) { v[TD0 + i] = tab_dense(CD - i); v[TD1 + i] = tab_dense(CD + 1 - i); }
        for (int s = 0; s < 2; s++)
            for (int i = 0; i < T3C; i++) { v[T3B + s * T3S + i] = tab_3(s, C3 - i); v[T3B + s * T3S + T3C + i] = tab_3(s, C3 + 1 - i); }
    }
};
__device__ const __align__(16) TabMap g_tabmap = TabMap();

__device__ __align__(1024) uint8_t g_kimg[65536];
__device__ __align__(1024) uint8_t g_vimg[65536 + 1024];
__device__ __align__(1024) uint8_t g_oimg[16 * 131072];
__device__ unsigned long long g_flag_kv[64];
__device__ unsigned g_flag_o[128];
__device__ unsigned g_epoch;
__device__ unsigned g_done;

#define PROF(i) do {} while (0)
#define PROF2(i) do {} while (0)
#define PROFC(i) do {} while (0)
#define PROF3(i) do {} while (0)

__device__ __forceinline__ uint32_t smem_u32(const void* p) { return (uint32_t)__cvta_generic_to_shared(p); }
__device__ __forceinline__ void mbar_init(uint32_t bar, uint32_t cnt) { asm volatile("mbarrier.init.shared::cta.b64 [%0], %1;" :: "r"(bar), "r"(cnt) : "memory"); }
__device__ __forceinline__ void mbar_expect_tx(uint32_t bar, uint32_t bytes) {
    asm volatile("mbarrier.arrive.expect_tx.shared::cta.b64 _, [%0], %1;" :: "r"(bar), "r"(bytes) : "memory"); }
__device__ __forceinline__ void mbar_wait(uint32_t bar, uint32_t parity) {
    uint32_t ok = 0;
    for (int it = 0; it < (1 << 22) && !ok; it++) {
        asm volatile("{ .reg .pred p; mbarrier.try_wait.parity.shared::cta.b64 p, [%1], %2; selp.u32 %0, 1, 0, p; }"
                     : "=r"(ok) : "r"(bar), "r"(parity) : "memory");
    }
}
__device__ __forceinline__ void tma_2d(uint32_t dst, const CUtensorMap* map, int c0, int c1, uint32_t bar) {
    asm volatile("cp.async.bulk.tensor.2d.shared::cluster.global.mbarrier::complete_tx::bytes [%0], [%1, {%3, %4}], [%2];"
                 :: "r"(dst), "l"((uint64_t)map), "r"(bar), "r"(c0), "r"(c1) : "memory");
}
__device__ __forceinline__ void tma_2d_mc(uint32_t dst, const CUtensorMap* map, int c0, int c1, uint32_t bar) {
    asm volatile("cp.async.bulk.tensor.2d.shared::cluster.global.mbarrier::complete_tx::bytes.multicast::cluster [%0], [%1, {%3, %4}], [%2], %5;"
                 :: "r"(dst), "l"((uint64_t)map), "r"(bar), "r"(c0), "r"(c1), "h"((uint16_t)3) : "memory");
}
__device__ __forceinline__ void bulk_g2s_mc(uint32_t dst, const void* src, uint32_t bytes, uint32_t bar) {
    asm volatile("cp.async.bulk.shared::cluster.global.mbarrier::complete_tx::bytes.multicast::cluster [%0], [%1], %2, [%3], %4;"
                 :: "r"(dst), "l"((uint64_t)src), "r"(bytes), "r"(bar), "h"((uint16_t)3) : "memory");
}
__device__ __forceinline__ void pair_sync(uint32_t bar, uint32_t peer) {
    uint32_t ra;
    asm volatile("mapa.shared::cluster.u32 %0, %1, %2;" : "=r"(ra) : "r"(bar), "r"(peer));
    asm volatile("mbarrier.arrive.shared::cluster.b64 _, [%0];" :: "r"(ra) : "memory");
    asm volatile("mbarrier.arrive.shared::cta.b64 _, [%0];" :: "r"(bar) : "memory");
    uint32_t ok = 0;
    for (int it = 0; it < (1 << 22) && !ok; it++) {
        asm volatile("{ .reg .pred p; mbarrier.try_wait.parity.shared::cta.b64 p, [%1], 0; selp.u32 %0, 1, 0, p; }"
                     : "=r"(ok) : "r"(bar) : "memory");
    }
}
__device__ __forceinline__ void fence_async_all() { asm volatile("fence.proxy.async.global;" ::: "memory"); }
__device__ __forceinline__ void fence_async_smem() { asm volatile("fence.proxy.async.shared::cta;" ::: "memory"); }
__device__ __forceinline__ unsigned ld_acquire(const unsigned* p) {
    unsigned v; asm volatile("ld.acquire.gpu.global.u32 %0, [%1];" : "=r"(v) : "l"(p) : "memory"); return v; }
__device__ __forceinline__ void st_release(unsigned* p, unsigned v) { asm volatile("st.release.gpu.global.u32 [%0], %1;" :: "l"(p), "r"(v) : "memory"); }
__device__ __forceinline__ void wait_flag(const unsigned* p, unsigned epoch) {
    for (int it = 0; it < (1 << 22); it++) { if (ld_acquire(p) == epoch) break; }
}
__device__ __forceinline__ unsigned long long ld_acquire64(const unsigned long long* p) {
    unsigned long long v; asm volatile("ld.acquire.gpu.global.u64 %0, [%1];" : "=l"(v) : "l"(p) : "memory"); return v; }
__device__ __forceinline__ void st_release64(unsigned long long* p, unsigned long long v) { asm volatile("st.release.gpu.global.u64 [%0], %1;" :: "l"(p), "l"(v) : "memory"); }
__device__ __forceinline__ float wait_flag64(const unsigned long long* p, unsigned epoch) {
    unsigned long long v = 0;
    for (int it = 0; it < (1 << 22); it++) { v = ld_acquire64(p); if ((unsigned)(v >> 32) == epoch) break; }
    return __uint_as_float((unsigned)v);
}
__device__ __forceinline__ void tma_3d_mc(uint32_t dst, const CUtensorMap* map, int c0, int c1, int c2, uint32_t bar) {
    asm volatile("cp.async.bulk.tensor.3d.shared::cluster.global.mbarrier::complete_tx::bytes.multicast::cluster [%0], [%1, {%3, %4, %5}], [%2], %6;"
                 :: "r"(dst), "l"((uint64_t)map), "r"(bar), "r"(c0), "r"(c1), "r"(c2), "h"((uint16_t)3) : "memory");
}
__device__ __forceinline__ void bar_sync(int id, int n) { asm volatile("bar.sync %0, %1;" :: "r"(id), "r"(n) : "memory"); }
__device__ __forceinline__ void bar_arrive(int id, int n) { asm volatile("bar.arrive %0, %1;" :: "r"(id), "r"(n) : "memory"); }
__device__ __forceinline__ void mbar_arrive(uint32_t bar) { asm volatile("mbarrier.arrive.shared::cta.b64 _, [%0];" :: "r"(bar) : "memory"); }

__device__ __forceinline__ uint64_t make_desc(uint32_t saddr, uint32_t lbo, uint32_t sbo, uint32_t swz) {
    uint64_t d = 0;
    d |= (uint64_t)((saddr & 0x3FFFF) >> 4);
    d |= (uint64_t)((lbo >> 4) & 0x3FFF) << 16;
    d |= (uint64_t)((sbo >> 4) & 0x3FFF) << 32;
    d |= (uint64_t)swz << 62;
    return d;
}
__device__ __forceinline__ void wg_fence() { asm volatile("wgmma.fence.sync.aligned;" ::: "memory"); }
__device__ __forceinline__ void wg_commit() { asm volatile("wgmma.commit_group.sync.aligned;" ::: "memory"); }
template<int N> __device__ __forceinline__ void wg_wait() { asm volatile("wgmma.wait_group.sync.aligned %0;" :: "n"(N) : "memory"); }
#define A4(d, o) "+f"(d[o + 0]), "+f"(d[o + 1]), "+f"(d[o + 2]), "+f"(d[o + 3])
#define A16(d, o) A4(d, o), A4(d, o + 4), A4(d, o + 8), A4(d, o + 12)

__device__ __forceinline__ void wg_pv(float* d, const uint32_t* a, uint32_t lo, uint32_t hi) {
    asm volatile("{ .reg .b64 dd; mov.b64 dd, {%16, %17};\n"
                 "wgmma.mma_async.sync.aligned.m64n24k16.f32.bf16.bf16 {%0,%1,%2,%3,%4,%5,%6,%7,%8,%9,%10,%11}, {%12,%13,%14,%15}, dd, 1, 1, 1, 1; }"
                 : A4(d, 0), A4(d, 4), A4(d, 8) : "r"(a[0]), "r"(a[1]), "r"(a[2]), "r"(a[3]), "r"(lo), "r"(hi));
}
__device__ __forceinline__ void wg_qk(float* d, const uint32_t* a, uint32_t lo) {
    asm volatile("{ .reg .b64 dd; mov.b64 dd, {%36, %37};\n"
                 "wgmma.mma_async.sync.aligned.m64n64k16.f32.bf16.bf16 {%0,%1,%2,%3,%4,%5,%6,%7,%8,%9,%10,%11,%12,%13,%14,%15,%16,%17,%18,%19,%20,%21,%22,%23,%24,%25,%26,%27,%28,%29,%30,%31}, {%32,%33,%34,%35}, dd, 0, 1, 1, 0; }"
                 : A16(d, 0), A16(d, 16) : "r"(a[0]), "r"(a[1]), "r"(a[2]), "r"(a[3]), "r"(lo), "r"(16));
}
__device__ __forceinline__ void wg_rs32(float* d, const uint32_t* a, uint32_t lo) {
    asm volatile("{ .reg .b64 dd; mov.b64 dd, {%20, %21};\n"
                 "wgmma.mma_async.sync.aligned.m64n32k16.f32.bf16.bf16 {%0,%1,%2,%3,%4,%5,%6,%7,%8,%9,%10,%11,%12,%13,%14,%15}, {%16,%17,%18,%19}, dd, 1, 1, 1, 0; }"
                 : A16(d, 0) : "r"(a[0]), "r"(a[1]), "r"(a[2]), "r"(a[3]), "r"(lo), "r"(0x40000040));
}
__device__ __forceinline__ void wg_ss32(float* d, uint64_t da, uint64_t db) {
    asm volatile("wgmma.mma_async.sync.aligned.m64n32k16.f32.bf16.bf16 {%0,%1,%2,%3,%4,%5,%6,%7,%8,%9,%10,%11,%12,%13,%14,%15}, %16, %17, 1, 1, 1, 0, 1;"
                 : A16(d, 0) : "l"(da), "l"(db));
}
__device__ __forceinline__ void wg_ss16(float* d, uint64_t da, uint64_t db) {
    asm volatile("wgmma.mma_async.sync.aligned.m64n16k16.f32.bf16.bf16 {%0,%1,%2,%3,%4,%5,%6,%7}, %8, %9, 1, 1, 1, 0, 1;"
                 : A4(d, 0), A4(d, 4) : "l"(da), "l"(db));
}
template<int N> __device__ __forceinline__ void fence_regs(float* r) {
    #pragma unroll
    for (int i = 0; i < N; i++) asm volatile("" : "+f"(r[i]) :: "memory");
}
__device__ __forceinline__ void mma_f16(float* d, const uint32_t* a, uint32_t b0, uint32_t b1) {
    asm volatile("mma.sync.aligned.m16n8k16.row.col.f32.f16.f16.f32 {%0,%1,%2,%3}, {%4,%5,%6,%7}, {%8,%9}, {%0,%1,%2,%3};"
                 : "+f"(d[0]), "+f"(d[1]), "+f"(d[2]), "+f"(d[3]) : "r"(a[0]), "r"(a[1]), "r"(a[2]), "r"(a[3]), "r"(b0), "r"(b1));
}
__device__ __forceinline__ uint32_t lds32(uint32_t addr) { uint32_t v; asm volatile("ld.shared.u32 %0, [%1];" : "=r"(v) : "r"(addr) : "memory"); return v; }
__device__ __forceinline__ void mma_bf16_p(float* d, uint32_t a0, uint32_t a1, uint32_t a2, uint32_t a3, uint32_t b0, uint32_t b1) {
    asm("mma.sync.aligned.m16n8k16.row.col.f32.bf16.bf16.f32 {%0,%1,%2,%3}, {%4,%5,%6,%7}, {%8,%9}, {%0,%1,%2,%3};"
        : "+f"(d[0]), "+f"(d[1]), "+f"(d[2]), "+f"(d[3]) : "r"(a0), "r"(a1), "r"(a2), "r"(a3), "r"(b0), "r"(b1));
}
__device__ __forceinline__ void ldsm4t_p(uint32_t* r, uint32_t addr) {
    asm("ldmatrix.sync.aligned.m8n8.x4.trans.shared.b16 {%0,%1,%2,%3}, [%4];" : "=r"(r[0]), "=r"(r[1]), "=r"(r[2]), "=r"(r[3]) : "r"(addr));
}
__device__ __forceinline__ uint32_t lds32_p(uint32_t addr) { uint32_t v; asm("ld.shared.u32 %0, [%1];" : "=r"(v) : "r"(addr)); return v; }
__device__ __forceinline__ uint32_t swz(uint32_t a) { return a ^ ((a >> 3) & 16u); }
__device__ __forceinline__ uint32_t swz128(uint32_t a) { return a ^ ((a >> 3) & 0x70u); }
__device__ __forceinline__ void sts32(uint32_t addr, uint32_t v) { asm volatile("st.shared.u32 [%0], %1;" :: "r"(addr), "r"(v) : "memory"); }
__device__ __forceinline__ void sts128(uint32_t addr, uint4 v) { asm volatile("st.shared.v4.u32 [%0], {%1,%2,%3,%4};" :: "r"(addr), "r"(v.x), "r"(v.y), "r"(v.z), "r"(v.w) : "memory"); }
__device__ __forceinline__ uint4 lds128(uint32_t addr) { uint4 v; asm volatile("ld.shared.v4.u32 {%0,%1,%2,%3}, [%4];" : "=r"(v.x), "=r"(v.y), "=r"(v.z), "=r"(v.w) : "r"(addr) : "memory"); return v; }
__device__ __forceinline__ float ex2f(float x) { float r; asm("ex2.approx.ftz.f32 %0, %1;" : "=f"(r) : "f"(x)); return r; }
__device__ __forceinline__ uint32_t pack_bf16(float lo, float hi) { uint32_t r; asm("cvt.rn.bf16x2.f32 %0, %1, %2;" : "=r"(r) : "f"(hi), "f"(lo)); return r; }
__device__ __forceinline__ uint32_t pack_f16(float lo, float hi) { uint32_t r; asm("cvt.rn.f16x2.f32 %0, %1, %2;" : "=r"(r) : "f"(hi), "f"(lo)); return r; }
__device__ __forceinline__ float bf_lo(uint32_t v) { return __uint_as_float(v << 16); }
__device__ __forceinline__ float bf_hi(uint32_t v) { return __uint_as_float(v & 0xFFFF0000u); }
__device__ __forceinline__ float bf_round(float x) { return __bfloat162float(__float2bfloat16_rn(x)); }

__device__ __forceinline__ uint32_t exp_mufu(float x0, float x1) { return pack_bf16(ex2f(x0), ex2f(x1)); }
#define SW_MAGIC (256.0f + 127.0f - 0.598938f)
__device__ __forceinline__ uint32_t exp_sw(float x0, float x1, uint32_t cA, uint32_t cB) {
    float t0 = x0 + SW_MAGIC, t1 = x1 + SW_MAGIC;
    uint32_t L, mh, ec, r;
    asm("prmt.b32 %0, %1, %2, 0x6521;" : "=r"(L) : "r"(__float_as_uint(t0)), "r"(__float_as_uint(t1)));
    asm("lop3.b32 %0, %1, 0x007F007F, %2, 0xEA;" : "=r"(mh) : "r"(L), "r"(cA));
    asm("lop3.b32 %0, %1, 0x7F807F80, %2, 0xEA;" : "=r"(ec) : "r"(L), "r"(cB));
    asm("fma.rn.bf16x2 %0, %1, %2, %3;" : "=r"(r) : "r"(L), "r"(mh), "r"(ec));
    return r;
}
constexpr uint32_t MUFU_MASK = 0x4949;

struct cf { float x, y; };
__device__ __forceinline__ cf cmul(cf a, cf b) { cf r; r.x = a.x * b.x - a.y * b.y; r.y = a.x * b.y + a.y * b.x; return r; }
__device__ __forceinline__ cf cexp_p(float a2, float b, float p) {
    float e = ex2f(a2 * p);
    float ph = b * p;
    ph -= (ph + 12582912.0f) - 12582912.0f;
    float ang = ph * 6.283185307f;
    cf r; r.x = e * __cosf(ang); r.y = e * __sinf(ang);
    return r;
}
__device__ __forceinline__ uint32_t h2_cmul(uint32_t w, uint32_t wsw, uint32_t e) {
    __half2 hw = *(__half2*)&w, hs = *(__half2*)&wsw, he = *(__half2*)&e;
    __half2 r = __hfma2(hs, __high2half2(he), __hmul2(hw, __low2half2(he)));
    return *(uint32_t*)&r;
}

template<bool B> struct BoolC { static constexpr bool value = B; };
struct Params {
    const __nv_bfloat16 *u, *lar, *aim, *cre, *cim, *logdt, *dskip;
    __nv_bfloat16* out;
};

constexpr int B_O = 0, B_KV = 8, B_WO = 12, B_WQ2 = 13, B_ST = 14, B_H = 15, B_X = 17, B_U = 19, B_WQ = 20;

__device__ __forceinline__ void helper_role(const Params& P, uint8_t* sp, uint32_t sb, unsigned epoch) {
    const uint32_t sBa = sb + SM_B;
    const int tid = threadIdx.x - 544;
    const int d0 = blockIdx.x * 4;
    uint8_t* sB = sp + SM_B;
    const uint2 dsk = __ldg((const uint2*)(P.dskip + d0));
    asm volatile("barrier.cluster.wait.aligned;" ::: "memory");
    {
        const int hg = blockIdx.x & 7;
        if (hg < 4 && tid < 32) {
            bar_sync(3, 160);
            if (tid == 0) {
                const float* s_misc = (const float*)(sp + SM_BAR + 256);
                const float st = fmaxf(fmaxf(s_misc[20], s_misc[21]), fmaxf(s_misc[22], s_misc[23]));
                st_release64(&g_flag_kv[((blockIdx.x >> 3) * 2 + (hg & 1)) * 2 + (hg >> 1)], ((unsigned long long)epoch << 32) | __float_as_uint(st));
            }
            __syncwarp();
        }
    }
    PROF2(2);
    bar_sync(10, 608);
    {
        uint32_t dd[4] = {__byte_perm(dsk.x, 0, 0x1010), __byte_perm(dsk.x, 0, 0x3232), __byte_perm(dsk.y, 0, 0x1010), __byte_perm(dsk.y, 0, 0x3232)};
        #pragma unroll 2
        for (int pi = tid; pi < 1024; pi += 96) {
            const int l = 2 * pi;
            uint32_t r[4];
            #pragma unroll
            for (int cc = 0; cc < 4; cc++) {
                const uint32_t y2 = *(const uint32_t*)(sB + S_Y + cc * 4096 + l * 2);
                const uint32_t u2 = lds32(swz128(sBa + S_U + cc * ULEN * 2 + (PADU + l) * 2));
                __nv_bfloat162 pr = __hmul2(*(const __nv_bfloat162*)&u2, *(const __nv_bfloat162*)&dd[cc]);
                __nv_bfloat162 sm = __hadd2(*(const __nv_bfloat162*)&y2, pr);
                r[cc] = *(uint32_t*)&sm;
            }
            *(uint2*)(P.out + (size_t)l * 1024 + 512 + d0) = make_uint2(__byte_perm(r[0], r[1], 0x5410), __byte_perm(r[2], r[3], 0x5410));
            *(uint2*)(P.out + (size_t)(l + 1) * 1024 + 512 + d0) = make_uint2(__byte_perm(r[0], r[1], 0x7632), __byte_perm(r[2], r[3], 0x7632));
        }
    }
    bar_arrive(11, 128);
    PROF2(4);
}

__global__ void __cluster_dims__(2, 1, 1) __launch_bounds__(NTHR, 1)
fused_kernel(const __grid_constant__ CUtensorMap tm_x, const __grid_constant__ CUtensorMap tm_wq,
             const __grid_constant__ CUtensorMap tm_wo, const __grid_constant__ CUtensorMap tm_wk,
             const __grid_constant__ CUtensorMap tm_wv, const __grid_constant__ CUtensorMap tm_u, const Params P) {
    extern __shared__ uint8_t smem_raw[];
    const uint32_t sb = (smem_u32(smem_raw) + 1023u) & ~1023u;
    uint8_t* sp = smem_raw + (sb - smem_u32(smem_raw));

    const int tid = threadIdx.x, warp = tid >> 5, lane = tid & 31, wg = tid >> 7, wiw = warp & 3;
    const int g = lane >> 2, t = lane & 3;
    const int qb = blockIdx.x >> 3, hg = blockIdx.x & 7;
    const uint32_t rank = blockIdx.x & 1;
    const int rowhalf = wg & 1, nh = wg >> 1;
    const bool kv_cta = hg < 4;
    const int kv_sel = hg >> 1;
    const bool kv_wg = kv_cta && (wg == (hg & 1));

    const uint32_t bars = sb + SM_BAR;
    float* s_misc = (float*)(sp + SM_BAR + 256);
    const CUtensorMap* tm_kv = kv_sel ? &tm_wv : &tm_wk;

    PROF(0);
    unsigned short p_lar = 0, p_aim = 0, p_cre = 0, p_cim = 0, p_ldt = 0;
    if (wg < 4) {
        const int n = (blockIdx.x * 4 + wg) * 128 + (tid & 127);
        p_lar = __ldg((const unsigned short*)P.lar + n);
        p_aim = __ldg((const unsigned short*)P.aim + n);
        p_cre = __ldg((const unsigned short*)P.cre + n);
        p_cim = __ldg((const unsigned short*)P.cim + n);
        p_ldt = __ldg((const unsigned short*)P.logdt + blockIdx.x * 4 + wg);
    } else if (warp == 16) {
        PROF3(5);
        if (lane == 0) {
            asm volatile("prefetch.tensormap [%0];" :: "l"((uint64_t)&tm_x) : "memory");
            asm volatile("prefetch.tensormap [%0];" :: "l"((uint64_t)tm_kv) : "memory");
            asm volatile("prefetch.tensormap [%0];" :: "l"((uint64_t)&tm_wq) : "memory");
            asm volatile("prefetch.tensormap [%0];" :: "l"((uint64_t)&tm_u) : "memory");
            mbar_init(bars + 8 * B_X, 1);
            mbar_init(bars + 8 * B_X + 8, 1);
            mbar_init(bars + 8 * B_U, 1);
            asm volatile("fence.mbarrier_init.release.cluster;" ::: "memory");
            mbar_expect_tx(bars + 8 * B_X, 65536u + (kv_cta ? 8192u : 0u));
            mbar_expect_tx(bars + 8 * B_X + 8, 65536u + (kv_cta ? 8192u : 0u));
            mbar_expect_tx(bars + 8 * B_U, 32768u);
        }
        __syncwarp();
        PROF3(6);
    }
    asm volatile("barrier.cluster.arrive.relaxed.aligned;" ::: "memory");
    const unsigned epoch = *(volatile unsigned*)&g_epoch + 1u;
    if (warp > 16) {
        if (lane == 0) {
            for (int i = warp - 17; i < B_X; i += 3) {
                mbar_init(bars + 8 * i, i >= B_H ? 2 : 1);
                if (i <= B_WQ2) mbar_expect_tx(bars + 8 * i, i < B_KV + 2 ? 16384u : i == B_KV + 2 ? 32768u : i <= B_WO ? 65536u : 32768u);
            }
            asm volatile("fence.mbarrier_init.release.cluster;" ::: "memory");
            fence_async_smem();
        } else if (warp == 19) {
            asm volatile("prefetch.global.L2 [%0];" :: "l"((const char*)g_tabmap.v + (lane - 1) * 128));
            if (lane < 11) asm volatile("prefetch.global.L2 [%0];" :: "l"((const char*)g_tabmap.v + (lane + 30) * 128));
        }
        __syncwarp();
    }
    asm volatile("barrier.cluster.wait.aligned;" ::: "memory");
    PROF(5);
    if (warp == 16 && lane == 0) {
        tma_3d_mc(sb + (rank ? SM_A : SM_B), &tm_x, 0, qb * 128, rank * 4, bars + 8 * (B_X + rank));
        if (kv_cta) {
            #pragma unroll
            for (int i = 0; i < 4; i++) tma_2d(sb + SM_WKV + i * 4096, tm_kv, (i >> 1) * 8, (i & 1) * 256, bars + 8 * (B_X + (i & 1)));
        }
        mbar_init(bars + 8 * B_WQ, 1);
        asm volatile("fence.mbarrier_init.release.cluster;" ::: "memory");
        fence_async_smem();
        mbar_expect_tx(bars + 8 * B_WQ, 32768u);
        tma_2d(sb + SM_WQ, &tm_wq, hg * 64, 0, bars + 8 * B_WQ);
        #pragma unroll
        for (int i = 0; i < 4; i++) tma_2d_mc(sb + SM_SLAB + (rank * 4 + i) * 4096, &tm_u, (blockIdx.x >> 1) * 8, (rank * 4 + i) * 256, bars + 8 * B_U);
    }
    __syncwarp();
    asm volatile("barrier.cluster.arrive.relaxed.aligned;" ::: "memory");

    if (warp == 16) {
        if (lane == 0) asm volatile("prefetch.tensormap [%0];" :: "l"((uint64_t)&tm_wo) : "memory");
        asm volatile("barrier.cluster.wait.aligned;" ::: "memory");
        PROF3(10);
        bar_sync(13, 544);
        if (lane == 0) { fence_async_smem(); tma_2d(sb + SM_SLAB, &tm_wq, hg * 64, 256, bars + 8 * B_WQ2); }
        bar_sync(14, 544);
        if (lane == 0) pair_sync(bars + 8 * B_H, rank ^ 1);
        __syncwarp();
        PROF3(11);
        *(uint4*)(sp + SM_V + 32768 + lane * 32) = make_uint4(0x3F803F80u, 0x3F803F80u, 0x3F803F80u, 0x3F803F80u);
        *(uint4*)(sp + SM_V + 32768 + lane * 32 + 16) = make_uint4(0x3F803F80u, 0x3F803F80u, 0x3F803F80u, 0x3F803F80u);
        fence_async_smem();
        float km = wait_flag64(&g_flag_kv[2 * lane], epoch);
        float vm = wait_flag64(&g_flag_kv[2 * lane + 1], epoch);
        __syncwarp();
        PROF3(12);
        if (lane == 0) {
            fence_async_all();
            #pragma unroll
            for (int i = 0; i < 4; i++) {
                const uint32_t k0 = i == 0 ? 0 : 128u << i, nk = i == 0 ? 256 : 128u << i;
                const uint32_t bar = bars + 8 * (B_KV + i);
                if (rank == 0) bulk_g2s_mc(sb + SM_K + k0 * 32, g_kimg + k0 * 32, nk * 32, bar);
                else {
                    bulk_g2s_mc(sb + SM_V + k0 * 16, g_vimg + k0 * 16, nk * 16, bar);
                    bulk_g2s_mc(sb + SM_V + 66560 - (k0 + nk) * 16, g_vimg + 66560 - (k0 + nk) * 16, nk * 16, bar);
                }
            }
        }
        #pragma unroll
        for (int o = 16; o; o >>= 1) { km = fmaxf(km, __shfl_xor_sync(0xffffffffu, km, o)); vm = fmaxf(vm, __shfl_xor_sync(0xffffffffu, vm, o)); }
        if (lane == 0) { s_misc[16] = km; s_misc[17] = vm; mbar_arrive(bars + 8 * B_ST); }
        PROF3(13);
        bar_sync(11, 128);
        if (lane < 2) { fence_async_smem(); tma_2d(sb + SM_B + lane * 32768, &tm_wo, hg * 64, lane * 256, bars + 8 * B_WO); }
        bar_sync(12, 544);
        if (lane == 0) {
            st_release(&g_flag_o[blockIdx.x], epoch);
            pair_sync(bars + 8 * (B_H + 1), rank ^ 1);
        }
        __syncwarp();
        PROF3(14);
        if (lane < 4) {
            const int src = 2 * lane + rank;
            wait_flag(&g_flag_o[qb * 8 + src], epoch);
            fence_async_all();
            bulk_g2s_mc(sb + SM_A + src * 16384, g_oimg + qb * 131072 + src * 16384, 16384, bars + 8 * (B_O + src));
        }
        __syncwarp();
        PROF3(15);
        if (lane == 0) {
            const unsigned prev = atomicAdd(&g_done, 1u);
            if (prev == NCTA - 1) {
                g_done = 0;
                __threadfence();
                *(volatile unsigned*)&g_epoch = epoch;
            }
        }
    } else if (wg == 4) {
        helper_role(P, sp, sb, epoch);
    } else {
        uint8_t* sB = sp + SM_B;
        const uint32_t sBa = sb + SM_B;
        {
            const int c = wg;
            const float dt = bf_round(expf(bf_lo(p_ldt)));
            const float are = -bf_round(expf(bf_lo(p_lar))) * dt;
            const float aim = bf_lo(p_aim) * dt;
            float cr = 2.0f * (bf_lo(p_cre) * dt);
            float ci = 2.0f * (bf_lo(p_cim) * dt);
            const float a2 = are * 1.4426950408889634f, bb = aim * 0.15915494309189535f;
            float m = fmaxf(fabsf(cr), fabsf(ci));
            #pragma unroll
            for (int o = 16; o; o >>= 1) m = fmaxf(m, __shfl_xor_sync(0xffffffffu, m, o));
            int ebits = (__float_as_uint(m) >> 23) & 0xFF;
            ebits = min(max(ebits, 2), 250);
            const float scale = __uint_as_float((uint32_t)(ebits + 1) << 23);
            const float iscale = __uint_as_float((uint32_t)(253 - ebits) << 23);
            cf cc; cc.x = cr * iscale; cc.y = ci * iscale;

            const uint32_t stg = sBa + S_KC + warp * 1024;
            uint4* stp = (uint4*)(sB + S_KC + warp * 1024 + lane * 32);
            const uint32_t fa = stg + t * 32 + g * 4;

            uint32_t af[4][2][4];
            cf E256;
            {
                const cf E8 = cexp_p(a2, bb, 8.0f);
                uint32_t w[8];
                cf cur; cur.x = 1.0f; cur.y = 0.0f;
                w[0] = pack_f16(1.0f, 0.0f);
                cur = E8; w[1] = pack_f16(cur.x, cur.y);
                #pragma unroll
                for (int i = 2; i < 8; i++) { cur = cmul(cur, E8); w[i] = pack_f16(cur.x, cur.y); }
                stp[0] = make_uint4(w[0], w[1], w[2], w[3]);
                stp[1] = make_uint4(w[4], w[5], w[6], w[7]);
                const cf E64 = cexp_p(a2, bb, 64.0f);
                const cf E128 = cmul(E64, E64), E192 = cmul(E128, E64);
                E256 = cexp_p(a2, bb, 256.0f);
                const uint32_t e1 = pack_f16(E64.x, E64.y), e2 = pack_f16(E128.x, E128.y), e3 = pack_f16(E192.x, E192.y);
                __syncwarp();
                #pragma unroll
                for (int s = 0; s < 4; s++) {
                    #pragma unroll
                    for (int hh = 0; hh < 2; hh++) {
                        const uint32_t w0 = lds32(fa + s * 256 + hh * 128);
                        const uint32_t wsw = __byte_perm(w0, 0, 0x1032) ^ 0x00008000u;
                        const int src = 8 * s + t + 4 * hh;
                        const uint32_t f1 = __shfl_sync(0xffffffffu, e1, src), f2 = __shfl_sync(0xffffffffu, e2, src), f3 = __shfl_sync(0xffffffffu, e3, src);
                        af[s][0][2 * hh] = w0;
                        af[s][0][2 * hh + 1] = h2_cmul(w0, wsw, f1);
                        af[s][1][2 * hh] = h2_cmul(w0, wsw, f2);
                        af[s][1][2 * hh + 1] = h2_cmul(w0, wsw, f3);
                    }
                }
                __syncwarp();
            }
            float acc[2][3][4];
            #pragma unroll
            for (int i = 0; i < 24; i++) (&acc[0][0][0])[i] = 0.0f;
            const cf E1 = cexp_p(a2, bb, 1.0f);
            const cf E2 = cmul(E1, E1), E4 = cmul(E2, E2);
            cf X512;
            #pragma unroll
            for (int nt = 0; nt < 3; nt++) {
                uint32_t xv[8];
                if (nt == 0) {
                    cf cur = cc;
                    xv[0] = pack_f16(cur.x, -cur.y);
                    #pragma unroll
                    for (int i = 1; i < 8; i++) { cur = cmul(cur, E1); xv[i] = pack_f16(cur.x, -cur.y); }
                } else if (nt == 1) {
                    cf cur = cmul(cc, E256);
                    X512 = cmul(cur, E256);
                    xv[0] = pack_f16(cur.x, -cur.y);
                    #pragma unroll
                    for (int i = 1; i < 4; i++) { cur = cmul(cur, E2); xv[i] = pack_f16(cur.x, -cur.y); }
                    cur = cmul(X512, E4);
                    xv[4] = pack_f16(X512.x, -X512.y); xv[5] = pack_f16(cur.x, -cur.y);
                    X512 = cmul(X512, E256);
                    cur = cmul(X512, E4);
                    xv[6] = pack_f16(X512.x, -X512.y); xv[7] = pack_f16(cur.x, -cur.y);
                } else {
                    cf cur = X512;
                    #pragma unroll
                    for (int i = 0; i < 5; i++) { cur = cmul(cur, E256); xv[i] = pack_f16(cur.x, -cur.y); }
                    xv[5] = 0; xv[6] = 0; xv[7] = 0;
                }
                stp[0] = make_uint4(xv[0], xv[1], xv[2], xv[3]);
                stp[1] = make_uint4(xv[4], xv[5], xv[6], xv[7]);
                __syncwarp();
                #pragma unroll
                for (int s = 0; s < 4; s++) {
                    const uint32_t b0 = lds32(fa + s * 256), b1 = lds32(fa + s * 256 + 128);
                    mma_f16(acc[0][nt], af[s][0], b0, b1);
                    mma_f16(acc[1][nt], af[s][1], b0, b1);
                }
                __syncwarp();
            }
            float* kc = (float*)(sB + S_KC + c * 4096);
            bar_sync(4 + c, 128);
            #pragma unroll 1
            for (int step = 0; step < 4; step++) {
                if ((warp & 3) == step) {
                    #pragma unroll
                    for (int mt = 0; mt < 2; mt++)
                        #pragma unroll
                        for (int nt = 0; nt < 3; nt++)
                            #pragma unroll
                            for (int hh = 0; hh < 2; hh++) {
                                float2* p = (float2*)(kc + (mt * 16 + hh * 8 + g) * 24 + nt * 8 + 2 * t);
                                float2 v = make_float2(acc[mt][nt][2 * hh] * scale, acc[mt][nt][2 * hh + 1] * scale);
                                if (step) { float2 o = *p; v.x += o.x; v.y += o.y; }
                                *p = v;
                            }
                }
                if (step < 3) bar_sync(4 + c, 128);
            }
        }

        asm volatile("barrier.cluster.wait.aligned;" ::: "memory");
        PROF(4);
        uint32_t q[2][4];
        {
            float acc[16], akv[8];
            #pragma unroll
            for (int i = 0; i < 16; i++) acc[i] = 0.0f;
            #pragma unroll
            for (int i = 0; i < 8; i++) akv[i] = 0.0f;
            fence_regs<16>(acc);
            fence_regs<8>(akv);
            const uint64_t dA0 = make_desc(sb + SM_B + rowhalf * 8192, 16, 1024, 1);
            const uint64_t dA1 = make_desc(sb + SM_A + rowhalf * 8192, 16, 1024, 1) - 4096;
            const uint64_t dB = make_desc(sb + SM_WQ + nh * 64, 16, 1024, 1);
            const uint64_t dC = make_desc(sb + SM_WKV, 128, 8192, 0);
            if (kv_wg) {
                #pragma unroll 1
                for (int ch = 0; ch < 8; ch++) {
                    if ((ch & 3) == 0) mbar_wait(bars + 8 * (B_X + (ch >> 2)), 0);
                    const uint64_t dA = ch < 4 ? dA0 : dA1;
                    wg_fence();
                    #pragma unroll
                    for (int ks = 0; ks < 4; ks++) wg_ss16(akv, dA + ch * 1024 + ks * 2, dC + (ch * 4 + ks) * 16);
                    wg_commit();
                }
                wg_wait<0>();
            }
            fence_regs<8>(akv);
            if (kv_wg) {
                const int key = qb * 128 + rowhalf * 64 + wiw * 16 + g;
                uint32_t pk[4];
                #pragma unroll
                for (int i = 0; i < 4; i++) pk[i] = pack_bf16(akv[2 * i], akv[2 * i + 1]);
                float st;
                if (kv_sel == 0) {
                    uint8_t* b = g_kimg + (key >> 3) * 256 + (key & 7) * 16 + 4 * t;
                    *(uint32_t*)(b) = pk[0]; *(uint32_t*)(b + 256) = pk[1]; *(uint32_t*)(b + 128) = pk[2]; *(uint32_t*)(b + 384) = pk[3];
                    float n0 = bf_lo(pk[0]) * bf_lo(pk[0]) + bf_hi(pk[0]) * bf_hi(pk[0]) + bf_lo(pk[2]) * bf_lo(pk[2]) + bf_hi(pk[2]) * bf_hi(pk[2]);
                    float n1 = bf_lo(pk[1]) * bf_lo(pk[1]) + bf_hi(pk[1]) * bf_hi(pk[1]) + bf_lo(pk[3]) * bf_lo(pk[3]) + bf_hi(pk[3]) * bf_hi(pk[3]);
                    n0 += __shfl_xor_sync(0xffffffffu, n0, 1); n0 += __shfl_xor_sync(0xffffffffu, n0, 2);
                    n1 += __shfl_xor_sync(0xffffffffu, n1, 1); n1 += __shfl_xor_sync(0xffffffffu, n1, 2);
                    st = (n0 != n0 || n1 != n1) ? __int_as_float(0x7f800000) : fmaxf(n0, n1);
                } else {
                    uint8_t* lo = g_vimg + key * 16 + 4 * t;
                    uint8_t* hi = g_vimg + 33792 + (31 - (key >> 6)) * 1024 + (key & 63) * 16 + 4 * t;
                    *(uint32_t*)(lo) = pk[0]; *(uint32_t*)(lo + 128) = pk[1]; *(uint32_t*)(hi) = pk[2]; *(uint32_t*)(hi + 128) = pk[3];
                    st = 0.0f;
                    #pragma unroll
                    for (int i = 0; i < 4; i++) {
                        float a = fabsf(bf_lo(pk[i])), b = fabsf(bf_hi(pk[i]));
                        st = (a != a || b != b) ? __int_as_float(0x7f800000) : fmaxf(st, fmaxf(a, b));
                    }
                }
                #pragma unroll
                for (int o = 16; o; o >>= 1) st = fmaxf(st, __shfl_xor_sync(0xffffffffu, st, o));
                if (lane == 0) s_misc[20 + wiw] = st;
                bar_arrive(3, 160);
            }
            uint32_t mp[11];
            #pragma unroll
            for (int i = 0; i < 11; i++) { const int w = (tid & 127) + 128 * i; mp[i] = (w < TABN / 2) ? __ldg((const uint32_t*)g_tabmap.v + w) : 0u; }
            mbar_wait(bars + 8 * B_WQ, 0);
            mbar_wait(bars + 8 * B_X, 0);
            PROF(2);
            #pragma unroll 1
            for (int ch = 0; ch < 4; ch++) {
                wg_fence();
                #pragma unroll
                for (int ks = 0; ks < 4; ks++) wg_ss32(acc, dA0 + ch * 1024 + ks * 2, dB + (ch * 4 + ks) * 128);
                wg_commit();
            }
            wg_wait<0>();
            fence_regs<16>(acc);
            bar_sync(1, 512);
            PROF(15);
            #pragma unroll
            for (int i = 0; i < 2; i++) {
                const int z = tid + 512 * i;
                if (z < 4 * 144) sts128(sBa + S_U + (z / 144) * ULEN * 2 + (PADU - 1152) * 2 + (z % 144) * 16, make_uint4(0, 0, 0, 0));
            }
            PROF(8);
            mbar_wait(bars + 8 * B_U, 0);
            PROF(14);
            #pragma unroll
            for (int i = 0; i < 2; i++) {
                const int l = 2 * (tid + 512 * i);
                const uint2 r0 = *(const uint2*)(sp + SM_SLAB + l * 16 + rank * 8), r1 = *(const uint2*)(sp + SM_SLAB + l * 16 + 16 + rank * 8);
                const uint32_t dst = swz128(sBa + S_U + (PADU + l) * 2);
                sts32(dst, __byte_perm(r0.x, r1.x, 0x5410));
                sts32(dst + ULEN * 2, __byte_perm(r0.x, r1.x, 0x7632));
                sts32(dst + ULEN * 4, __byte_perm(r0.y, r1.y, 0x5410));
                sts32(dst + ULEN * 6, __byte_perm(r0.y, r1.y, 0x7632));
            }
            bar_arrive(13, 544);
            {
                const float* kc = (const float*)(sB + S_KC + wg * 4096);
                uint32_t* tab = (uint32_t*)(sB + S_TAB + wg * TABN * 2);
                #pragma unroll
                for (int i = 0; i < 11; i++) { const int w = (tid & 127) + 128 * i; if (w < TABN / 2) tab[w] = pack_bf16(kc[mp[i] & 0xFFFF], kc[mp[i] >> 16]); }
            }
            fence_async_smem();
            bar_sync(1, 512);
            PROF(1);
            mbar_wait(bars + 8 * B_WQ2, 0);
            mbar_wait(bars + 8 * (B_X + 1), 0);
            fence_regs<16>(acc);
            wg_fence();
            #pragma unroll
            for (int ks = 16; ks < 32; ks++) wg_ss32(acc, dA1 + (ks >> 2) * 1024 + (ks & 3) * 2, dB + ks * 128);
            wg_commit();
            {
                const int task = tid + (tid < 8 ? 512 : 0) * 0;
                #pragma unroll 1
                for (int tk = task; tk < 4 * 130; tk += 512) {
                    const int c = tk / 130, i = tk % 130;
                    const uint32_t src = sBa + S_U + c * ULEN * 2 + (PADU + 8 * i - WPAD - 8) * 2;
                    const uint4 v0 = lds128(swz128(src)), v1 = lds128(swz128(src + 16)), v2 = lds128(swz128(src + 32));
                    float x[16];
                    const uint32_t vv[8] = {v0.z, v0.w, v1.x, v1.y, v1.z, v1.w, v2.x, v2.y};
                    #pragma unroll
                    for (int k = 0; k < 8; k++) { x[2 * k] = bf_lo(vv[k]); x[2 * k + 1] = bf_hi(vv[k]); }
                    float p2[15], w7[8], w9[8];
                    #pragma unroll
                    for (int e = 0; e < 15; e++) p2[e] = x[e] + x[e + 1];
                    #pragma unroll
                    for (int e = 0; e < 8; e++) {
                        w7[e] = (p2[e + 1] + p2[e + 3]) + (p2[e + 5] + x[e + 7]);
                        w9[e] = w7[e] + (x[e] + x[e + 8]);
                    }
                    sts128(swz(sBa + S_W7 + c * W3LEN * 2 + i * 16), make_uint4(pack_bf16(w7[0], w7[1]), pack_bf16(w7[2], w7[3]), pack_bf16(w7[4], w7[5]), pack_bf16(w7[6], w7[7])));
                    sts128(swz(sBa + S_W9 + c * W3LEN * 2 + i * 16), make_uint4(pack_bf16(w9[0], w9[1]), pack_bf16(w9[2], w9[3]), pack_bf16(w9[4], w9[5]), pack_bf16(w9[6], w9[7])));
                }
            }
            wg_wait<0>();
            fence_regs<16>(acc);
            bar_arrive(14, 544);
            const float QS = 0.25f * 1.4426950408889634f;
            float qm = 0.0f;
            #pragma unroll
            for (int i = 0; i < 2; i++) {
                #pragma unroll
                for (int j = 0; j < 4; j++) q[i][j] = pack_bf16(acc[8 * i + 2 * j] * QS, acc[8 * i + 2 * j + 1] * QS);
                float n0 = bf_lo(q[i][0]) * bf_lo(q[i][0]) + bf_hi(q[i][0]) * bf_hi(q[i][0]) + bf_lo(q[i][2]) * bf_lo(q[i][2]) + bf_hi(q[i][2]) * bf_hi(q[i][2]);
                float n1 = bf_lo(q[i][1]) * bf_lo(q[i][1]) + bf_hi(q[i][1]) * bf_hi(q[i][1]) + bf_lo(q[i][3]) * bf_lo(q[i][3]) + bf_hi(q[i][3]) * bf_hi(q[i][3]);
                n0 += __shfl_xor_sync(0xffffffffu, n0, 1); n0 += __shfl_xor_sync(0xffffffffu, n0, 2);
                n1 += __shfl_xor_sync(0xffffffffu, n1, 1); n1 += __shfl_xor_sync(0xffffffffu, n1, 2);
                qm = (n0 != n0 || n1 != n1) ? __int_as_float(0x7f800000) : fmaxf(qm, fmaxf(n0, n1));
            }
            #pragma unroll
            for (int o = 16; o; o >>= 1) qm = fmaxf(qm, __shfl_xor_sync(0xffffffffu, qm, o));
            if (lane == 0) s_misc[warp] = qm;
        }
        PROF(3);
        {
            const int c = wg;
            uint32_t sBl = sBa;
            asm volatile("" : "+r"(sBl) :: "memory");
            float acc[16];
            #pragma unroll
            for (int i = 0; i < 16; i++) acc[i] = 0.0f;
            fence_regs<16>(acc);
            const uint32_t tabc = sBl + S_TAB + c * TABN * 2;
            const uint32_t tD = tabc + ((g & 1) ? (TD1 + CD + 1) : (TD0 + CD)) * 2 - (g - 2 * t) * 2 - 32 * wiw;
            const uint32_t uLo = (((sBl + S_U + c * ULEN * 2 + PADU * 2) & 0x3FFFF) >> 4) | (1u << 16);
            uint32_t A[2][4][4];
            auto load_set = [&](uint32_t (&X)[4][4], int m0) {
                #pragma unroll
                for (int i = 0; i < 4; i++) {
                    const int kap = m0 + i + wiw;
                    const uint32_t a = tD - 32 * ((kap >= 0 && kap <= 65) ? m0 + i : -1 - wiw);
                    X[i][0] = lds32(a); X[i][1] = lds32(a - 16); X[i][2] = lds32(a + 16); X[i][3] = lds32(a);
                    if (kap < 0 || kap > 65) { X[i][0] = 0; X[i][1] = 0; X[i][2] = 0; X[i][3] = 0; }
                }
            };
            #pragma unroll 1
            for (int m0 = -3; m0 < 69; m0 += 8) {
                #pragma unroll
                for (int h = 0; h < 2; h++) {
                    load_set(A[h], m0 + 4 * h);
                    wg_fence();
                    #pragma unroll
                    for (int i = 0; i < 4; i++) wg_rs32(acc, A[h][i], uLo - 2 * (m0 + 4 * h + i));
                    wg_commit();
                    wg_wait<1>();
                }
            }
            bar_sync(1, 512);
            wg_wait<0>();
            fence_regs<16>(acc);
            PROF(6);
            {
                asm volatile("" : "+r"(sBl) :: "memory");
                const int mi = lane >> 3, r8 = lane & 7;
                const uint32_t frag = (16 * (8 * (mi >> 1) + r8) + 8 * (mi & 1)) * 2;
                const uint32_t t3 = sBl + S_TAB + c * TABN * 2 + (T3B + ((wiw & 1) ? (T3C + C3 + 1) : C3)) * 2 - (4 * g + wiw - 2 * t) * 2;
                #pragma unroll
                for (int s = 0; s < 2; s++) {
                    const uint32_t sig = swz(sBl + (s ? S_W7 : S_W9) + c * W3LEN * 2 + WPAD * 2 + frag - (s ? 16 : 32));
                    uint32_t a[4][4], R[4][2];
                    #pragma unroll
                    for (int b = 0; b < 4; b++) ldsm4t_p(a[b], sig + b * 512);
                    #pragma unroll
                    for (int i = 0; i < 4; i++) { R[i][0] = lds32_p(t3 + s * (T3S * 2) - 2 * (48 + 16 * i)); R[i][1] = lds32_p(t3 + s * (T3S * 2) - 2 * (40 + 16 * i)); }
                    #pragma unroll
                    for (int b = 0; b < 4; b++) {
                        mma_bf16_p(acc + 12, a[b][0], a[b][1], a[b][2], a[b][3], R[3 - b][0], R[3 - b][1]);
                        if (b < 2) mma_bf16_p(acc + 8, a[b][0], a[b][1], a[b][2], a[b][3], R[1 - b][0], R[1 - b][1]);
                    }
                }
            }
            __nv_bfloat16* ys = (__nv_bfloat16*)(sB + S_Y + c * 4096) + 128 * t + 16 * wiw + g;
            #pragma unroll
            for (int j = 0; j < 4; j++) {
                ys[512 * j] = __float2bfloat16_rn(acc[4 * j]);
                ys[512 * j + 64] = __float2bfloat16_rn(acc[4 * j + 1]);
                ys[512 * j + 8] = __float2bfloat16_rn(acc[4 * j + 2]);
                ys[512 * j + 72] = __float2bfloat16_rn(acc[4 * j + 3]);
            }
        }
        bar_arrive(10, 608);
        PROF(7);
        {
            mbar_wait(bars + 8 * B_ST, 0);
            PROF(9); PROFC(8);
            float qm = 0.0f;
            #pragma unroll
            for (int i = 0; i < 16; i++) qm = fmaxf(qm, s_misc[i]);
            const float vm = s_misc[17];
            const bool fast = (qm * s_misc[16] <= 60.0f * 60.0f) && (vm <= 1.0e12f) && (vm >= 1.0e-12f || vm == 0.0f);
            uint8_t* ob = g_oimg + qb * 131072 + hg * 16384 + nh * 8192 + (rowhalf * 8 + wiw * 2) * 128 + g * 16 + 4 * t;
            uint32_t cA = 0xBF00BF00u, cB = 0x00030003u;
            asm volatile("" : "+r"(cA), "+r"(cB));
            #pragma unroll 1
            for (int tile = 0; tile < 2; tile++) {
                uint32_t kLo = (((sb + SM_K) & 0x3FFFF) >> 4) | (8u << 16), vLo = (((sb + SM_V) & 0x3FFFF) >> 4) | (8u << 16), vHi = 2048;
                float o[12], s[32];
                uint32_t p[16], qq[4];
                #pragma unroll
                for (int i = 0; i < 4; i++) { qq[i] = tile ? q[1][i] : q[0][i]; asm volatile("" : "+r"(qq[i])); }
                #pragma unroll
                for (int i = 0; i < 12; i++) o[i] = 0.0f;
                #pragma unroll
                for (int i = 0; i < 32; i++) s[i] = 0.0f;
                fence_regs<12>(o);
                fence_regs<32>(s);
                if (fast) {
                    #pragma unroll 1
                    for (int c = 0; c < SEQ / 256; c++) {
                        if (c <= 4) mbar_wait(bars + 8 * (B_KV + (c < 2 ? c : c < 4 ? 2 : 3)), 0);
                        wg_fence();
                        wg_qk(s, qq, kLo);
                        wg_commit();
                        #pragma unroll
                        for (int u = 0; u < 4; u++) {
                            wg_wait<0>();
                            fence_regs<32>(s);
                            #pragma unroll
                            for (int i = 0; i < 16; i++) {
                                if ((MUFU_MASK >> i) & 1) p[i] = exp_mufu(s[2 * i], s[2 * i + 1]);
                                else p[i] = exp_sw(s[2 * i], s[2 * i + 1], cA, cB);
                            }
                            wg_fence();
                            if (u + 1 < 4) wg_qk(s, qq, kLo + (u + 1) * 128);
                            #pragma unroll
                            for (int kk = 0; kk < 4; kk++) wg_pv(o, p + 4 * kk, vLo + u * 64 + kk * 16, vHi - u * 64);
                            wg_commit();
                        }
                        kLo += 512; vLo += 256; vHi -= 256;
                    }
                    wg_wait<0>();
                } else {
                    float mx0 = -INFINITY, mx1 = -INFINITY;
                    #pragma unroll 1
                    for (int c = 0; c < SEQ / 64; c++) {
                        if (c <= 16) mbar_wait(bars + 8 * (B_KV + (c < 8 ? (c >> 2) : c < 16 ? 2 : 3)), 0);
                        wg_fence();
                        wg_qk(s, qq, kLo);
                        wg_commit();
                        wg_wait<0>();
                        fence_regs<32>(s);
                        fence_regs<12>(o);
                        float m0 = mx0, m1 = mx1;
                        #pragma unroll
                        for (int j = 0; j < 8; j++) {
                            m0 = fmaxf(m0, fmaxf(s[4 * j], s[4 * j + 1]));
                            m1 = fmaxf(m1, fmaxf(s[4 * j + 2], s[4 * j + 3]));
                        }
                        m0 = fmaxf(m0, __shfl_xor_sync(0xffffffffu, m0, 1)); m0 = fmaxf(m0, __shfl_xor_sync(0xffffffffu, m0, 2));
                        m1 = fmaxf(m1, __shfl_xor_sync(0xffffffffu, m1, 1)); m1 = fmaxf(m1, __shfl_xor_sync(0xffffffffu, m1, 2));
                        const float c0 = ex2f(mx0 - m0), c1 = ex2f(mx1 - m1);
                        mx0 = m0; mx1 = m1;
                        #pragma unroll
                        for (int j = 0; j < 3; j++) { o[4 * j] *= c0; o[4 * j + 1] *= c0; o[4 * j + 2] *= c1; o[4 * j + 3] *= c1; }
                        #pragma unroll
                        for (int j = 0; j < 8; j++) {
                            p[2 * j] = exp_mufu(s[4 * j] - m0, s[4 * j + 1] - m0);
                            p[2 * j + 1] = exp_mufu(s[4 * j + 2] - m1, s[4 * j + 3] - m1);
                        }
                        wg_fence();
                        #pragma unroll
                        for (int kk = 0; kk < 4; kk++) wg_pv(o, p + 4 * kk, vLo + kk * 16, vHi);
                        wg_commit();
                        wg_wait<0>();
                        kLo += 128; vLo += 64; vHi -= 64;
                    }
                }
                fence_regs<12>(o);
                if (tile == 0) PROFC(3);
                const float i0 = 1.0f / o[4], i1 = 1.0f / o[6];
                uint8_t* b = ob + tile * 4096;
                *(uint32_t*)(b) = pack_bf16(o[0] * i0, o[1] * i0);
                *(uint32_t*)(b + 128) = pack_bf16(o[2] * i1, o[3] * i1);
                *(uint32_t*)(b + 2048) = pack_bf16(o[8] * i0, o[9] * i0);
                *(uint32_t*)(b + 2048 + 128) = pack_bf16(o[10] * i1, o[11] * i1);
            }
        }
        PROF(10); PROFC(9);
        bar_arrive(12, 544);

        {
            float acc[16];
            #pragma unroll
            for (int i = 0; i < 16; i++) acc[i] = 0.0f;
            fence_regs<16>(acc);
            const uint64_t dA = make_desc(sb + SM_A + rowhalf * 1024, 2048, 128, 0);
            const uint64_t dB = make_desc(sb + SM_B + nh * 64, 16, 1024, 1);
            mbar_wait(bars + 8 * B_WO, 0);
            #pragma unroll 1
            for (int i = 0; i < 8; i++) {
                const int src = (hg + i) & 7;
                mbar_wait(bars + 8 * (B_O + src), 0);
                wg_fence();
                #pragma unroll
                for (int kk = 0; kk < 4; kk++) wg_ss32(acc, dA + src * 1024 + kk * 256, dB + (src * 4 + kk) * 128);
                wg_commit();
            }
            wg_wait<0>();
            fence_regs<16>(acc);
            PROF(12);
            const int row = qb * 128 + rowhalf * 64 + wiw * 16 + g;
            uint32_t* o32 = (uint32_t*)(P.out + (size_t)row * 1024 + hg * 64 + nh * 32 + 2 * t);
            #pragma unroll
            for (int j = 0; j < 4; j++) {
                o32[4 * j] = pack_bf16(acc[4 * j], acc[4 * j + 1]);
                o32[4 * j + 8 * 512] = pack_bf16(acc[4 * j + 2], acc[4 * j + 3]);
            }
        }
        PROF(13);
    }
}

typedef CUresult (*EncodeFn)(CUtensorMap*, CUtensorMapDataType, cuuint32_t, void*, const cuuint64_t*, const cuuint64_t*,
                             const cuuint32_t*, const cuuint32_t*, CUtensorMapInterleave, CUtensorMapSwizzle,
                             CUtensorMapL2promotion, CUtensorMapFloatOOBfill);

void make_map(EncodeFn fn, CUtensorMap* m, const void* ptr, uint64_t inner, uint64_t outer, uint32_t box_in, uint32_t box_out, CUtensorMapSwizzle swz) {
    cuuint64_t dims[2] = {inner, outer};
    cuuint64_t strides[1] = {inner * 2};
    cuuint32_t box[2] = {box_in, box_out};
    cuuint32_t es[2] = {1, 1};
    fn(m, CU_TENSOR_MAP_DATA_TYPE_BFLOAT16, 2, const_cast<void*>(ptr), dims, strides, box, es, CU_TENSOR_MAP_INTERLEAVE_NONE, swz,
       CU_TENSOR_MAP_L2_PROMOTION_L2_128B, CU_TENSOR_MAP_FLOAT_OOB_FILL_NONE);
}

}

extern "C" void kernel_launch(void* const* d_in, const int* in_sizes, int n_in, void* d_out, int out_size) {
    (void)in_sizes; (void)n_in; (void)out_size;
    static EncodeFn fn = nullptr;
    if (!fn) {
        void* p = nullptr;
        cudaDriverEntryPointQueryResult qr;
        cudaGetDriverEntryPoint("cuTensorMapEncodeTiled", &p, cudaEnableDefault, &qr);
        fn = (EncodeFn)p;
        cudaFuncSetAttribute(fused_kernel, cudaFuncAttributeMaxDynamicSharedMemorySize, SM_ALLOC);
    }
    CUtensorMap tx, twq, two, twk, twv, tu;
    {
        cuuint64_t dims[3] = {64, 2048, 8};
        cuuint64_t strides[2] = {1024, 128};
        cuuint32_t box[3] = {64, 128, 4};
        cuuint32_t es[3] = {1, 1, 1};
        fn(&tx, CU_TENSOR_MAP_DATA_TYPE_BFLOAT16, 3, d_in[0], dims, strides, box, es, CU_TENSOR_MAP_INTERLEAVE_NONE, CU_TENSOR_MAP_SWIZZLE_128B,
           CU_TENSOR_MAP_L2_PROMOTION_L2_128B, CU_TENSOR_MAP_FLOAT_OOB_FILL_NONE);
    }
    make_map(fn, &tu, d_in[5], 512, 2048, 8, 256, CU_TENSOR_MAP_SWIZZLE_NONE);
    make_map(fn, &twq, d_in[1], 512, 512, 64, 256, CU_TENSOR_MAP_SWIZZLE_128B);
    make_map(fn, &twk, d_in[2], 16, 512, 8, 256, CU_TENSOR_MAP_SWIZZLE_NONE);
    make_map(fn, &twv, d_in[3], 16, 512, 8, 256, CU_TENSOR_MAP_SWIZZLE_NONE);
    make_map(fn, &two, d_in[4], 512, 512, 64, 256, CU_TENSOR_MAP_SWIZZLE_128B);
    Params P;
    P.u = (const __nv_bfloat16*)d_in[5];
    P.lar = (const __nv_bfloat16*)d_in[6];
    P.aim = (const __nv_bfloat16*)d_in[7];
    P.cre = (const __nv_bfloat16*)d_in[8];
    P.cim = (const __nv_bfloat16*)d_in[9];
    P.logdt = (const __nv_bfloat16*)d_in[10];
    P.dskip = (const __nv_bfloat16*)d_in[11];
    P.out = (__nv_bfloat16*)d_out;
    fused_kernel<<<NCTA, NTHR, SM_ALLOC>>>(tx, twq, two, twk, twv, tu, P);
}
```

```cpp
#include <cuda_runtime.h>
#include <cuda_bf16.h>
#include <cuda_fp16.h>
#include <cuda.h>
#include <stdint.h>

namespace {

constexpr int SEQ = 2048;
constexpr int NCTA = 128, NTHR = 640;

constexpr int SM_A = 0;
constexpr int SM_WQ = 65536;
constexpr int SM_SLAB = SM_WQ + 32768;
constexpr int SM_K = 0, SM_V = 65536;
constexpr int SM_B = 132096;
constexpr int SM_WKV = SM_B + 65536;

constexpr int PADU = 1536, ULEN = PADU + 2048;
constexpr int WPAD = 16, W3LEN = WPAD + 1024;
constexpr int TABN = 4200;
constexpr int S_U = 0;
constexpr int S_W7 = S_U + 4 * ULEN * 2;
constexpr int S_W9 = S_W7 + 4 * W3LEN * 2;
constexpr int S_TAB = S_W9 + 4 * W3LEN * 2;
constexpr int S_KC = 214016 - SM_B;
constexpr int S_Y = S_KC;
constexpr int SM_BAR = SM_B + S_KC + 16384;
constexpr int SM_TOTAL = SM_BAR + 1024;
constexpr int SM_ALLOC = SM_TOTAL + 1024;
static_assert(SM_V + 65536 + 1024 <= SM_B && SM_ALLOC <= 232448 && S_TAB + 4 * TABN * 2 <= S_KC && SM_WKV + 16384 <= SM_B + S_KC, "smem map");

constexpr int TDW = 134;
constexpr int T3B = 14 * TDW * 2, T3S = 224, T3C = 112, C3 = 136;

constexpr int rne8(int t) {
    if (t < 256) return t;
    int sh = 0;
    while ((t >> sh) >= 256) sh++;
    int q = t >> sh, rem = t & ((1 << sh) - 1), half = 1 << (sh - 1);
    if (rem > half || (rem == half && (q & 1))) q++;
    return q << sh;
}
constexpr int kcidx(int p) {
    if (p < 256) return (p >> 3) * 24 + (p & 7);
    if (p < 512) return ((p - 256) >> 3) * 24 + 8 + (((p - 256) & 7) >> 1);
    if (p < 1024) { int q = p - 512, hi = q >> 8, rem = q & 255; return (rem >> 3) * 24 + 12 + 2 * hi + ((rem & 7) >> 2); }
    if (p < 2048) { int q = p - 1024; return ((q & 255) >> 3) * 24 + 16 + (q >> 8); }
    return 20;
}
constexpr int KC_ZERO = 23;
constexpr int tab_dense(int t) { return (t >= 0 && t <= 1028) ? kcidx(rne8(t)) : KC_ZERO; }
constexpr int tab_3(int s, int lag) { return (lag >= 64 && lag <= 127) ? kcidx(s == 0 ? 16 * (lag + 1) : 16 * lag + 8) : KC_ZERO; }
struct TabMap {
    uint16_t v[TABN];
    constexpr TabMap() : v{} {
        for (int e = 0; e < 14; e++)
            for (int i = 0; i < TDW; i++) { v[(e * TDW + i) * 2] = tab_dense(8 * (i - 2) + e - 6); v[(e * TDW + i) * 2 + 1] = tab_dense(8 * (i - 2) + e - 7); }
        for (int s = 0; s < 2; s++)
            for (int i = 0; i < T3C; i++) { v[T3B + s * T3S + i] = tab_3(s, C3 - i); v[T3B + s * T3S + T3C + i] = tab_3(s, C3 + 1 - i); }
    }
};
__device__ const __align__(16) TabMap g_tabmap = TabMap();

__device__ __align__(1024) uint8_t g_kimg[65536];
__device__ __align__(1024) uint8_t g_vimg[65536 + 1024];
__device__ __align__(1024) uint8_t g_oimg[16 * 131072];
__device__ unsigned long long g_flag_kv[64];
__device__ unsigned g_flag_o[128];
__device__ unsigned g_epoch;
__device__ unsigned g_done;

#define PROF(i) do {} while (0)
#define PROF2(i) do {} while (0)
#define PROFC(i) do {} while (0)
#define PROF3(i) do {} while (0)

__device__ __forceinline__ uint32_t smem_u32(const void* p) { return (uint32_t)__cvta_generic_to_shared(p); }
__device__ __forceinline__ void mbar_init(uint32_t bar, uint32_t cnt) { asm volatile("mbarrier.init.shared::cta.b64 [%0], %1;" :: "r"(bar), "r"(cnt) : "memory"); }
__device__ __forceinline__ void mbar_expect_tx(uint32_t bar, uint32_t bytes) {
    asm volatile("mbarrier.arrive.expect_tx.shared::cta.b64 _, [%0], %1;" :: "r"(bar), "r"(bytes) : "memory"); }
__device__ __forceinline__ void mbar_wait(uint32_t bar, uint32_t parity) {
    uint32_t ok = 0;
    for (int it = 0; it < (1 << 22) && !ok; it++) {
        asm volatile("{ .reg .pred p; mbarrier.try_wait.parity.shared::cta.b64 p, [%1], %2; selp.u32 %0, 1, 0, p; }"
                     : "=r"(ok) : "r"(bar), "r"(parity) : "memory");
    }
}
__device__ __forceinline__ void tma_2d(uint32_t dst, const CUtensorMap* map, int c0, int c1, uint32_t bar) {
    asm volatile("cp.async.bulk.tensor.2d.shared::cluster.global.mbarrier::complete_tx::bytes [%0], [%1, {%3, %4}], [%2];"
                 :: "r"(dst), "l"((uint64_t)map), "r"(bar), "r"(c0), "r"(c1) : "memory");
}
__device__ __forceinline__ void tma_2d_mc(uint32_t dst, const CUtensorMap* map, int c0, int c1, uint32_t bar) {
    asm volatile("cp.async.bulk.tensor.2d.shared::cluster.global.mbarrier::complete_tx::bytes.multicast::cluster [%0], [%1, {%3, %4}], [%2], %5;"
                 :: "r"(dst), "l"((uint64_t)map), "r"(bar), "r"(c0), "r"(c1), "h"((uint16_t)3) : "memory");
}
__device__ __forceinline__ void bulk_g2s_mc(uint32_t dst, const void* src, uint32_t bytes, uint32_t bar) {
    asm volatile("cp.async.bulk.shared::cluster.global.mbarrier::complete_tx::bytes.multicast::cluster [%0], [%1], %2, [%3], %4;"
                 :: "r"(dst), "l"((uint64_t)src), "r"(bytes), "r"(bar), "h"((uint16_t)3) : "memory");
}
__device__ __forceinline__ void pair_sync(uint32_t bar, uint32_t peer) {
    uint32_t ra;
    asm volatile("mapa.shared::cluster.u32 %0, %1, %2;" : "=r"(ra) : "r"(bar), "r"(peer));
    asm volatile("mbarrier.arrive.shared::cluster.b64 _, [%0];" :: "r"(ra) : "memory");
    asm volatile("mbarrier.arrive.shared::cta.b64 _, [%0];" :: "r"(bar) : "memory");
    uint32_t ok = 0;
    for (int it = 0; it < (1 << 22) && !ok; it++) {
        asm volatile("{ .reg .pred p; mbarrier.try_wait.parity.shared::cta.b64 p, [%1], 0; selp.u32 %0, 1, 0, p; }"
                     : "=r"(ok) : "r"(bar) : "memory");
    }
}
__device__ __forceinline__ void fence_async_all() { asm volatile("fence.proxy.async.global;" ::: "memory"); }
__device__ __forceinline__ void fence_async_smem() { asm volatile("fence.proxy.async.shared::cta;" ::: "memory"); }
__device__ __forceinline__ unsigned ld_acquire(const unsigned* p) {
    unsigned v; asm volatile("ld.acquire.gpu.global.u32 %0, [%1];" : "=r"(v) : "l"(p) : "memory"); return v; }
__device__ __forceinline__ void st_release(unsigned* p, unsigned v) { asm volatile("st.release.gpu.global.u32 [%0], %1;" :: "l"(p), "r"(v) : "memory"); }
__device__ __forceinline__ void wait_flag(const unsigned* p, unsigned epoch) {
    for (int it = 0; it < (1 << 22); it++) { if (ld_acquire(p) == epoch) break; }
}
__device__ __forceinline__ unsigned long long ld_acquire64(const unsigned long long* p) {
    unsigned long long v; asm volatile("ld.acquire.gpu.global.u64 %0, [%1];" : "=l"(v) : "l"(p) : "memory"); return v; }
__device__ __forceinline__ void st_release64(unsigned long long* p, unsigned long long v) { asm volatile("st.release.gpu.global.u64 [%0], %1;" :: "l"(p), "l"(v) : "memory"); }
__device__ __forceinline__ float wait_flag64(const unsigned long long* p, unsigned epoch) {
    unsigned long long v = 0;
    for (int it = 0; it < (1 << 22); it++) { v = ld_acquire64(p); if ((unsigned)(v >> 32) == epoch) break; }
    return __uint_as_float((unsigned)v);
}
__device__ __forceinline__ void tma_3d_mc(uint32_t dst, const CUtensorMap* map, int c0, int c1, int c2, uint32_t bar) {
    asm volatile("cp.async.bulk.tensor.3d.shared::cluster.global.mbarrier::complete_tx::bytes.multicast::cluster [%0], [%1, {%3, %4, %5}], [%2], %6;"
                 :: "r"(dst), "l"((uint64_t)map), "r"(bar), "r"(c0), "r"(c1), "r"(c2), "h"((uint16_t)3) : "memory");
}
__device__ __forceinline__ void bar_sync(int id, int n) { asm volatile("bar.sync %0, %1;" :: "r"(id), "r"(n) : "memory"); }
__device__ __forceinline__ void bar_arrive(int id, int n) { asm volatile("bar.arrive %0, %1;" :: "r"(id), "r"(n) : "memory"); }
__device__ __forceinline__ void mbar_arrive(uint32_t bar) { asm volatile("mbarrier.arrive.shared::cta.b64 _, [%0];" :: "r"(bar) : "memory"); }

__device__ __forceinline__ uint64_t make_desc(uint32_t saddr, uint32_t lbo, uint32_t sbo, uint32_t swz) {
    uint64_t d = 0;
    d |= (uint64_t)((saddr & 0x3FFFF) >> 4);
    d |= (uint64_t)((lbo >> 4) & 0x3FFF) << 16;
    d |= (uint64_t)((sbo >> 4) & 0x3FFF) << 32;
    d |= (uint64_t)swz << 62;
    return d;
}
__device__ __forceinline__ void wg_fence() { asm volatile("wgmma.fence.sync.aligned;" ::: "memory"); }
__device__ __forceinline__ void wg_commit() { asm volatile("wgmma.commit_group.sync.aligned;" ::: "memory"); }
template<int N> __device__ __forceinline__ void wg_wait() { asm volatile("wgmma.wait_group.sync.aligned %0;" :: "n"(N) : "memory"); }
#define A4(d, o) "+f"(d[o + 0]), "+f"(d[o + 1]), "+f"(d[o + 2]), "+f"(d[o + 3])
#define A16(d, o) A4(d, o), A4(d, o + 4), A4(d, o + 8), A4(d, o + 12)

__device__ __forceinline__ void wg_pv(float* d, const uint32_t* a, uint32_t lo, uint32_t hi) {
    asm volatile("{ .reg .b64 dd; mov.b64 dd, {%16, %17};\n"
                 "wgmma.mma_async.sync.aligned.m64n24k16.f32.bf16.bf16 {%0,%1,%2,%3,%4,%5,%6,%7,%8,%9,%10,%11}, {%12,%13,%14,%15}, dd, 1, 1, 1, 1; }"
                 : A4(d, 0), A4(d, 4), A4(d, 8) : "r"(a[0]), "r"(a[1]), "r"(a[2]), "r"(a[3]), "r"(lo), "r"(hi));
}
__device__ __forceinline__ void wg_qk(float* d, const uint32_t* a, uint32_t lo) {
    asm volatile("{ .reg .b64 dd; mov.b64 dd, {%36, %37};\n"
                 "wgmma.mma_async.sync.aligned.m64n64k16.f32.bf16.bf16 {%0,%1,%2,%3,%4,%5,%6,%7,%8,%9,%10,%11,%12,%13,%14,%15,%16,%17,%18,%19,%20,%21,%22,%23,%24,%25,%26,%27,%28,%29,%30,%31}, {%32,%33,%34,%35}, dd, 0, 1, 1, 0; }"
                 : A16(d, 0), A16(d, 16) : "r"(a[0]), "r"(a[1]), "r"(a[2]), "r"(a[3]), "r"(lo), "r"(16));
}
__device__ __forceinline__ void wg_rs32(float* d, const uint32_t* a, uint32_t lo) {
    asm volatile("{ .reg .b64 dd; mov.b64 dd, {%20, %21};\n"
                 "wgmma.mma_async.sync.aligned.m64n32k16.f32.bf16.bf16 {%0,%1,%2,%3,%4,%5,%6,%7,%8,%9,%10,%11,%12,%13,%14,%15}, {%16,%17,%18,%19}, dd, 1, 1, 1, 0; }"
                 : A16(d, 0) : "r"(a[0]), "r"(a[1]), "r"(a[2]), "r"(a[3]), "r"(lo), "r"(0x40000040));
}
__device__ __forceinline__ void wg_ss32(float* d, uint64_t da, uint64_t db) {
    asm volatile("wgmma.mma_async.sync.aligned.m64n32k16.f32.bf16.bf16 {%0,%1,%2,%3,%4,%5,%6,%7,%8,%9,%10,%11,%12,%13,%14,%15}, %16, %17, 1, 1, 1, 0, 1;"
                 : A16(d, 0) : "l"(da), "l"(db));
}
__device__ __forceinline__ void wg_ss16(float* d, uint64_t da, uint64_t db) {
    asm volatile("wgmma.mma_async.sync.aligned.m64n16k16.f32.bf16.bf16 {%0,%1,%2,%3,%4,%5,%6,%7}, %8, %9, 1, 1, 1, 0, 1;"
                 : A4(d, 0), A4(d, 4) : "l"(da), "l"(db));
}
template<int N> __device__ __forceinline__ void fence_regs(float* r) {
    #pragma unroll
    for (int i = 0; i < N; i++) asm volatile("" : "+f"(r[i]) :: "memory");
}
__device__ __forceinline__ void mma_f16(float* d, const uint32_t* a, uint32_t b0, uint32_t b1) {
    asm volatile("mma.sync.aligned.m16n8k16.row.col.f32.f16.f16.f32 {%0,%1,%2,%3}, {%4,%5,%6,%7}, {%8,%9}, {%0,%1,%2,%3};"
                 : "+f"(d[0]), "+f"(d[1]), "+f"(d[2]), "+f"(d[3]) : "r"(a[0]), "r"(a[1]), "r"(a[2]), "r"(a[3]), "r"(b0), "r"(b1));
}
__device__ __forceinline__ uint32_t lds32(uint32_t addr) { uint32_t v; asm volatile("ld.shared.u32 %0, [%1];" : "=r"(v) : "r"(addr) : "memory"); return v; }
__device__ __forceinline__ void mma_bf16_p(float* d, uint32_t a0, uint32_t a1, uint32_t a2, uint32_t a3, uint32_t b0, uint32_t b1) {
    asm("mma.sync.aligned.m16n8k16.row.col.f32.bf16.bf16.f32 {%0,%1,%2,%3}, {%4,%5,%6,%7}, {%8,%9}, {%0,%1,%2,%3};"
        : "+f"(d[0]), "+f"(d[1]), "+f"(d[2]), "+f"(d[3]) : "r"(a0), "r"(a1), "r"(a2), "r"(a3), "r"(b0), "r"(b1));
}
__device__ __forceinline__ void ldsm4t_p(uint32_t* r, uint32_t addr) {
    asm("ldmatrix.sync.aligned.m8n8.x4.trans.shared.b16 {%0,%1,%2,%3}, [%4];" : "=r"(r[0]), "=r"(r[1]), "=r"(r[2]), "=r"(r[3]) : "r"(addr));
}
__device__ __forceinline__ uint32_t lds32_p(uint32_t addr) { uint32_t v; asm("ld.shared.u32 %0, [%1];" : "=r"(v) : "r"(addr)); return v; }
__device__ __forceinline__ uint32_t swz(uint32_t a) { return a ^ ((a >> 3) & 16u); }
__device__ __forceinline__ uint32_t swz128(uint32_t a) { return a ^ ((a >> 3) & 0x70u); }
__device__ __forceinline__ void sts32(uint32_t addr, uint32_t v) { asm volatile("st.shared.u32 [%0], %1;" :: "r"(addr), "r"(v) : "memory"); }
__device__ __forceinline__ void sts128(uint32_t addr, uint4 v) { asm volatile("st.shared.v4.u32 [%0], {%1,%2,%3,%4};" :: "r"(addr), "r"(v.x), "r"(v.y), "r"(v.z), "r"(v.w) : "memory"); }
__device__ __forceinline__ uint4 lds128(uint32_t addr) { uint4 v; asm volatile("ld.shared.v4.u32 {%0,%1,%2,%3}, [%4];" : "=r"(v.x), "=r"(v.y), "=r"(v.z), "=r"(v.w) : "r"(addr) : "memory"); return v; }
__device__ __forceinline__ float ex2f(float x) { float r; asm("ex2.approx.ftz.f32 %0, %1;" : "=f"(r) : "f"(x)); return r; }
__device__ __forceinline__ uint32_t pack_bf16(float lo, float hi) { uint32_t r; asm("cvt.rn.bf16x2.f32 %0, %1, %2;" : "=r"(r) : "f"(hi), "f"(lo)); return r; }
__device__ __forceinline__ uint32_t pack_f16(float lo, float hi) { uint32_t r; asm("cvt.rn.f16x2.f32 %0, %1, %2;" : "=r"(r) : "f"(hi), "f"(lo)); return r; }
__device__ __forceinline__ float bf_lo(uint32_t v) { return __uint_as_float(v << 16); }
__device__ __forceinline__ float bf_hi(uint32_t v) { return __uint_as_float(v & 0xFFFF0000u); }
__device__ __forceinline__ float bf_round(float x) { return __bfloat162float(__float2bfloat16_rn(x)); }

__device__ __forceinline__ uint32_t exp_mufu(float x0, float x1) { return pack_bf16(ex2f(x0), ex2f(x1)); }
#define SW_MAGIC (256.0f + 127.0f - 0.598938f)
__device__ __forceinline__ uint32_t exp_sw(float x0, float x1, uint32_t cA, uint32_t cB) {
    float t0 = x0 + SW_MAGIC, t1 = x1 + SW_MAGIC;
    uint32_t L, mh, ec, r;
    asm("prmt.b32 %0, %1, %2, 0x6521;" : "=r"(L) : "r"(__float_as_uint(t0)), "r"(__float_as_uint(t1)));
    asm("lop3.b32 %0, %1, 0x007F007F, %2, 0xEA;" : "=r"(mh) : "r"(L), "r"(cA));
    asm("lop3.b32 %0, %1, 0x7F807F80, %2, 0xEA;" : "=r"(ec) : "r"(L), "r"(cB));
    asm("fma.rn.bf16x2 %0, %1, %2, %3;" : "=r"(r) : "r"(L), "r"(mh), "r"(ec));
    return r;
}
constexpr uint32_t MUFU_MASK = 0x4949;

struct cf { float x, y; };
__device__ __forceinline__ cf cmul(cf a, cf b) { cf r; r.x = a.x * b.x - a.y * b.y; r.y = a.x * b.y + a.y * b.x; return r; }
__device__ __forceinline__ cf cexp_p(float a2, float b, float p) {
    float e = ex2f(a2 * p);
    float ph = b * p;
    ph -= (ph + 12582912.0f) - 12582912.0f;
    float ang = ph * 6.283185307f;
    cf r; r.x = e * __cosf(ang); r.y = e * __sinf(ang);
    return r;
}
__device__ __forceinline__ uint32_t h2_cmul(uint32_t w, uint32_t wsw, uint32_t e) {
    __half2 hw = *(__half2*)&w, hs = *(__half2*)&wsw, he = *(__half2*)&e;
    __half2 r = __hfma2(hs, __high2half2(he), __hmul2(hw, __low2half2(he)));
    return *(uint32_t*)&r;
}

template<bool B> struct BoolC { static constexpr bool value = B; };
struct Params {
    const __nv_bfloat16 *u, *lar, *aim, *cre, *cim, *logdt, *dskip;
    __nv_bfloat16* out;
};

constexpr int B_O = 0, B_KV = 8, B_WO = 12, B_WQ2 = 13, B_ST = 14, B_H = 15, B_X = 17, B_U = 19, B_WQ = 20;

__device__ __forceinline__ void helper_role(const Params& P, uint8_t* sp, uint32_t sb, unsigned epoch) {
    const uint32_t sBa = sb + SM_B;
    const int tid = threadIdx.x - 544;
    const int d0 = blockIdx.x * 4;
    uint8_t* sB = sp + SM_B;
    const uint2 dsk = __ldg((const uint2*)(P.dskip + d0));
    asm volatile("barrier.cluster.wait.aligned;" ::: "memory");
    {
        const int hg = blockIdx.x & 7;
        if (hg < 4 && tid < 32) {
            bar_sync(3, 160);
            if (tid == 0) {
                const float* s_misc = (const float*)(sp + SM_BAR + 256);
                const float st = fmaxf(fmaxf(s_misc[20], s_misc[21]), fmaxf(s_misc[22], s_misc[23]));
                st_release64(&g_flag_kv[((blockIdx.x >> 3) * 2 + (hg & 1)) * 2 + (hg >> 1)], ((unsigned long long)epoch << 32) | __float_as_uint(st));
            }
            __syncwarp();
        }
    }
    PROF2(2);
    bar_sync(10, 608);
    {
        uint32_t dd[4] = {__byte_perm(dsk.x, 0, 0x1010), __byte_perm(dsk.x, 0, 0x3232), __byte_perm(dsk.y, 0, 0x1010), __byte_perm(dsk.y, 0, 0x3232)};
        #pragma unroll 2
        for (int pi = tid; pi < 1024; pi += 96) {
            const int l = 2 * pi;
            uint32_t r[4];
            #pragma unroll
            for (int cc = 0; cc < 4; cc++) {
                const uint32_t y2 = *(const uint32_t*)(sB + S_Y + cc * 4096 + l * 2);
                const uint32_t u2 = lds32(swz128(sBa + S_U + cc * ULEN * 2 + (PADU + l) * 2));
                __nv_bfloat162 pr = __hmul2(*(const __nv_bfloat162*)&u2, *(const __nv_bfloat162*)&dd[cc]);
                __nv_bfloat162 sm = __hadd2(*(const __nv_bfloat162*)&y2, pr);
                r[cc] = *(uint32_t*)&sm;
            }
            *(uint2*)(P.out + (size_t)l * 1024 + 512 + d0) = make_uint2(__byte_perm(r[0], r[1], 0x5410), __byte_perm(r[2], r[3], 0x5410));
            *(uint2*)(P.out + (size_t)(l + 1) * 1024 + 512 + d0) = make_uint2(__byte_perm(r[0], r[1], 0x7632), __byte_perm(r[2], r[3], 0x7632));
        }
    }
    bar_arrive(11, 128);
    PROF2(4);
}

__global__ void __cluster_dims__(2, 1, 1) __launch_bounds__(NTHR, 1)
fused_kernel(const __grid_constant__ CUtensorMap tm_x, const __grid_constant__ CUtensorMap tm_wq,
             const __grid_constant__ CUtensorMap tm_wo, const __grid_constant__ CUtensorMap tm_wk,
             const __grid_constant__ CUtensorMap tm_wv, const __grid_constant__ CUtensorMap tm_u, const Params P) {
    extern __shared__ uint8_t smem_raw[];
    const uint32_t sb = (smem_u32(smem_raw) + 1023u) & ~1023u;
    uint8_t* sp = smem_raw + (sb - smem_u32(smem_raw));

    const int tid = threadIdx.x, warp = tid >> 5, lane = tid & 31, wg = tid >> 7, wiw = warp & 3;
    const int g = lane >> 2, t = lane & 3;
    const int qb = blockIdx.x >> 3, hg = blockIdx.x & 7;
    const uint32_t rank = blockIdx.x & 1;
    const int rowhalf = wg & 1, nh = wg >> 1;
    const bool kv_cta = hg < 4;
    const int kv_sel = hg >> 1;
    const bool kv_wg = kv_cta && (wg == (hg & 1));

    const uint32_t bars = sb + SM_BAR;
    float* s_misc = (float*)(sp + SM_BAR + 256);
    const CUtensorMap* tm_kv = kv_sel ? &tm_wv : &tm_wk;

    PROF(0);
    unsigned short p_lar = 0, p_aim = 0, p_cre = 0, p_cim = 0, p_ldt = 0;
    if (wg < 4) {
        const int n = (blockIdx.x * 4 + wg) * 128 + (tid & 127);
        p_lar = __ldg((const unsigned short*)P.lar + n);
        p_aim = __ldg((const unsigned short*)P.aim + n);
        p_cre = __ldg((const unsigned short*)P.cre + n);
        p_cim = __ldg((const unsigned short*)P.cim + n);
        p_ldt = __ldg((const unsigned short*)P.logdt + blockIdx.x * 4 + wg);
    } else if (warp == 16) {
        PROF3(5);
        if (lane == 0) {
            asm volatile("prefetch.tensormap [%0];" :: "l"((uint64_t)&tm_x) : "memory");
            asm volatile("prefetch.tensormap [%0];" :: "l"((uint64_t)tm_kv) : "memory");
            asm volatile("prefetch.tensormap [%0];" :: "l"((uint64_t)&tm_wq) : "memory");
            asm volatile("prefetch.tensormap [%0];" :: "l"((uint64_t)&tm_u) : "memory");
            mbar_init(bars + 8 * B_X, 1);
            mbar_init(bars + 8 * B_X + 8, 1);
            mbar_init(bars + 8 * B_U, 1);
            asm volatile("fence.mbarrier_init.release.cluster;" ::: "memory");
            mbar_expect_tx(bars + 8 * B_X, 65536u + (kv_cta ? 8192u : 0u));
            mbar_expect_tx(bars + 8 * B_X + 8, 65536u + (kv_cta ? 8192u : 0u));
            mbar_expect_tx(bars + 8 * B_U, 32768u);
        }
        __syncwarp();
        PROF3(6);
    }
    asm volatile("barrier.cluster.arrive.relaxed.aligned;" ::: "memory");
    const unsigned epoch = *(volatile unsigned*)&g_epoch + 1u;
    if (warp > 16) {
        if (lane == 0) {
            for (int i = warp - 17; i < B_X; i += 3) {
                mbar_init(bars + 8 * i, i >= B_H ? 2 : 1);
                if (i <= B_WQ2) mbar_expect_tx(bars + 8 * i, i < B_KV + 2 ? 16384u : i == B_KV + 2 ? 32768u : i <= B_WO ? 65536u : 32768u);
            }
            asm volatile("fence.mbarrier_init.release.cluster;" ::: "memory");
            fence_async_smem();
        } else if (warp == 19) {
            #pragma unroll
            for (int i = 0; i < 3; i++) if (lane - 1 + 31 * i < 66) asm volatile("prefetch.global.L2 [%0];" :: "l"((const char*)g_tabmap.v + (lane - 1 + 31 * i) * 128));
        }
        __syncwarp();
    }
    asm volatile("barrier.cluster.wait.aligned;" ::: "memory");
    PROF(5);
    if (warp == 16 && lane == 0) {
        tma_3d_mc(sb + (rank ? SM_A : SM_B), &tm_x, 0, qb * 128, rank * 4, bars + 8 * (B_X + rank));
        if (kv_cta) {
            #pragma unroll
            for (int i = 0; i < 4; i++) tma_2d(sb + SM_WKV + i * 4096, tm_kv, (i >> 1) * 8, (i & 1) * 256, bars + 8 * (B_X + (i & 1)));
        }
        mbar_init(bars + 8 * B_WQ, 1);
        asm volatile("fence.mbarrier_init.release.cluster;" ::: "memory");
        fence_async_smem();
        mbar_expect_tx(bars + 8 * B_WQ, 32768u);
        tma_2d(sb + SM_WQ, &tm_wq, hg * 64, 0, bars + 8 * B_WQ);
        #pragma unroll
        for (int i = 0; i < 4; i++) tma_2d_mc(sb + SM_SLAB + (rank * 4 + i) * 4096, &tm_u, (blockIdx.x >> 1) * 8, (rank * 4 + i) * 256, bars + 8 * B_U);
    }
    __syncwarp();
    asm volatile("barrier.cluster.arrive.relaxed.aligned;" ::: "memory");

    if (warp == 16) {
        if (lane == 0) asm volatile("prefetch.tensormap [%0];" :: "l"((uint64_t)&tm_wo) : "memory");
        asm volatile("barrier.cluster.wait.aligned;" ::: "memory");
        PROF3(10);
        bar_sync(13, 544);
        if (lane == 0) { fence_async_smem(); tma_2d(sb + SM_SLAB, &tm_wq, hg * 64, 256, bars + 8 * B_WQ2); }
        bar_sync(14, 544);
        if (lane == 0) pair_sync(bars + 8 * B_H, rank ^ 1);
        __syncwarp();
        PROF3(11);
        *(uint4*)(sp + SM_V + 32768 + lane * 32) = make_uint4(0x3F803F80u, 0x3F803F80u, 0x3F803F80u, 0x3F803F80u);
        *(uint4*)(sp + SM_V + 32768 + lane * 32 + 16) = make_uint4(0x3F803F80u, 0x3F803F80u, 0x3F803F80u, 0x3F803F80u);
        fence_async_smem();
        float km = wait_flag64(&g_flag_kv[2 * lane], epoch);
        float vm = wait_flag64(&g_flag_kv[2 * lane + 1], epoch);
        __syncwarp();
        PROF3(12);
        if (lane == 0) {
            fence_async_all();
            #pragma unroll
            for (int i = 0; i < 4; i++) {
                const uint32_t k0 = i == 0 ? 0 : 128u << i, nk = i == 0 ? 256 : 128u << i;
                const uint32_t bar = bars + 8 * (B_KV + i);
                if (rank == 0) bulk_g2s_mc(sb + SM_K + k0 * 32, g_kimg + k0 * 32, nk * 32, bar);
                else {
                    bulk_g2s_mc(sb + SM_V + k0 * 16, g_vimg + k0 * 16, nk * 16, bar);
                    bulk_g2s_mc(sb + SM_V + 66560 - (k0 + nk) * 16, g_vimg + 66560 - (k0 + nk) * 16, nk * 16, bar);
                }
            }
        }
        #pragma unroll
        for (int o = 16; o; o >>= 1) { km = fmaxf(km, __shfl_xor_sync(0xffffffffu, km, o)); vm = fmaxf(vm, __shfl_xor_sync(0xffffffffu, vm, o)); }
        if (lane == 0) { s_misc[16] = km; s_misc[17] = vm; mbar_arrive(bars + 8 * B_ST); }
        PROF3(13);
        bar_sync(11, 128);
        if (lane < 2) { fence_async_smem(); tma_2d(sb + SM_B + lane * 32768, &tm_wo, hg * 64, lane * 256, bars + 8 * B_WO); }
        bar_sync(12, 544);
        if (lane == 0) {
            st_release(&g_flag_o[blockIdx.x], epoch);
            pair_sync(bars + 8 * (B_H + 1), rank ^ 1);
        }
        __syncwarp();
        PROF3(14);
        if (lane < 4) {
            const int src = 2 * lane + rank;
            wait_flag(&g_flag_o[qb * 8 + src], epoch);
            fence_async_all();
            bulk_g2s_mc(sb + SM_A + src * 16384, g_oimg + qb * 131072 + src * 16384, 16384, bars + 8 * (B_O + src));
        }
        __syncwarp();
        PROF3(15);
        if (lane == 0) {
            const unsigned prev = atomicAdd(&g_done, 1u);
            if (prev == NCTA - 1) {
                g_done = 0;
                __threadfence();
                *(volatile unsigned*)&g_epoch = epoch;
            }
        }
    } else if (wg == 4) {
        helper_role(P, sp, sb, epoch);
    } else {
        uint8_t* sB = sp + SM_B;
        const uint32_t sBa = sb + SM_B;
        {
            const int c = wg;
            const float dt = bf_round(expf(bf_lo(p_ldt)));
            const float are = -bf_round(expf(bf_lo(p_lar))) * dt;
            const float aim = bf_lo(p_aim) * dt;
            float cr = 2.0f * (bf_lo(p_cre) * dt);
            float ci = 2.0f * (bf_lo(p_cim) * dt);
            const float a2 = are * 1.4426950408889634f, bb = aim * 0.15915494309189535f;
            float m = fmaxf(fabsf(cr), fabsf(ci));
            #pragma unroll
            for (int o = 16; o; o >>= 1) m = fmaxf(m, __shfl_xor_sync(0xffffffffu, m, o));
            int ebits = (__float_as_uint(m) >> 23) & 0xFF;
            ebits = min(max(ebits, 2), 250);
            const float scale = __uint_as_float((uint32_t)(ebits + 1) << 23);
            const float iscale = __uint_as_float((uint32_t)(253 - ebits) << 23);
            cf cc; cc.x = cr * iscale; cc.y = ci * iscale;

            const uint32_t stg = sBa + S_KC + warp * 1024;
            uint4* stp = (uint4*)(sB + S_KC + warp * 1024 + lane * 32);
            const uint32_t fa = stg + t * 32 + g * 4;

            uint32_t af[4][2][4];
            cf E256;
            {
                const cf E8 = cexp_p(a2, bb, 8.0f);
                uint32_t w[8];
                cf cur; cur.x = 1.0f; cur.y = 0.0f;
                w[0] = pack_f16(1.0f, 0.0f);
                cur = E8; w[1] = pack_f16(cur.x, cur.y);
                #pragma unroll
                for (int i = 2; i < 8; i++) { cur = cmul(cur, E8); w[i] = pack_f16(cur.x, cur.y); }
                stp[0] = make_uint4(w[0], w[1], w[2], w[3]);
                stp[1] = make_uint4(w[4], w[5], w[6], w[7]);
                const cf E64 = cexp_p(a2, bb, 64.0f);
                const cf E128 = cmul(E64, E64), E192 = cmul(E128, E64);
                E256 = cexp_p(a2, bb, 256.0f);
                const uint32_t e1 = pack_f16(E64.x, E64.y), e2 = pack_f16(E128.x, E128.y), e3 = pack_f16(E192.x, E192.y);
                __syncwarp();
                #pragma unroll
                for (int s = 0; s < 4; s++) {
                    #pragma unroll
                    for (int hh = 0; hh < 2; hh++) {
                        const uint32_t w0 = lds32(fa + s * 256 + hh * 128);
                        const uint32_t wsw = __byte_perm(w0, 0, 0x1032) ^ 0x00008000u;
                        const int src = 8 * s + t + 4 * hh;
                        const uint32_t f1 = __shfl_sync(0xffffffffu, e1, src), f2 = __shfl_sync(0xffffffffu, e2, src), f3 = __shfl_sync(0xffffffffu, e3, src);
                        af[s][0][2 * hh] = w0;
                        af[s][0][2 * hh + 1] = h2_cmul(w0, wsw, f1);
                        af[s][1][2 * hh] = h2_cmul(w0, wsw, f2);
                        af[s][1][2 * hh + 1] = h2_cmul(w0, wsw, f3);
                    }
                }
                __syncwarp();
            }
            float acc[2][3][4];
            #pragma unroll
            for (int i = 0; i < 24; i++) (&acc[0][0][0])[i] = 0.0f;
            const cf E1 = cexp_p(a2, bb, 1.0f);
            const cf E2 = cmul(E1, E1), E4 = cmul(E2, E2);
            cf X512;
            #pragma unroll
            for (int nt = 0; nt < 3; nt++) {
                uint32_t xv[8];
                if (nt == 0) {
                    cf cur = cc;
                    xv[0] = pack_f16(cur.x, -cur.y);
                    #pragma unroll
                    for (int i = 1; i < 8; i++) { cur = cmul(cur, E1); xv[i] = pack_f16(cur.x, -cur.y); }
                } else if (nt == 1) {
                    cf cur = cmul(cc, E256);
                    X512 = cmul(cur, E256);
                    xv[0] = pack_f16(cur.x, -cur.y);
                    #pragma unroll
                    for (int i = 1; i < 4; i++) { cur = cmul(cur, E2); xv[i] = pack_f16(cur.x, -cur.y); }
                    cur = cmul(X512, E4);
                    xv[4] = pack_f16(X512.x, -X512.y); xv[5] = pack_f16(cur.x, -cur.y);
                    X512 = cmul(X512, E256);
                    cur = cmul(X512, E4);
                    xv[6] = pack_f16(X512.x, -X512.y); xv[7] = pack_f16(cur.x, -cur.y);
                } else {
                    cf cur = X512;
                    #pragma unroll
                    for (int i = 0; i < 5; i++) { cur = cmul(cur, E256); xv[i] = pack_f16(cur.x, -cur.y); }
                    xv[5] = 0; xv[6] = 0; xv[7] = 0;
                }
                stp[0] = make_uint4(xv[0], xv[1], xv[2], xv[3]);
                stp[1] = make_uint4(xv[4], xv[5], xv[6], xv[7]);
                __syncwarp();
                #pragma unroll
                for (int s = 0; s < 4; s++) {
                    const uint32_t b0 = lds32(fa + s * 256), b1 = lds32(fa + s * 256 + 128);
                    mma_f16(acc[0][nt], af[s][0], b0, b1);
                    mma_f16(acc[1][nt], af[s][1], b0, b1);
                }
                __syncwarp();
            }
            float* kc = (float*)(sB + S_KC + c * 4096);
            bar_sync(4 + c, 128);
            #pragma unroll 1
            for (int step = 0; step < 4; step++) {
                if ((warp & 3) == step) {
                    #pragma unroll
                    for (int mt = 0; mt < 2; mt++)
                        #pragma unroll
                        for (int nt = 0; nt < 3; nt++)
                            #pragma unroll
                            for (int hh = 0; hh < 2; hh++) {
                                float2* p = (float2*)(kc + (mt * 16 + hh * 8 + g) * 24 + nt * 8 + 2 * t);
                                float2 v = make_float2(acc[mt][nt][2 * hh] * scale, acc[mt][nt][2 * hh + 1] * scale);
                                if (step) { float2 o = *p; v.x += o.x; v.y += o.y; }
                                *p = v;
                            }
                }
                if (step < 3) bar_sync(4 + c, 128);
            }
        }

        asm volatile("barrier.cluster.wait.aligned;" ::: "memory");
        PROF(4);
        uint32_t q[2][4];
        {
            float acc[16], akv[8];
            #pragma unroll
            for (int i = 0; i < 16; i++) acc[i] = 0.0f;
            #pragma unroll
            for (int i = 0; i < 8; i++) akv[i] = 0.0f;
            fence_regs<16>(acc);
            fence_regs<8>(akv);
            const uint64_t dA0 = make_desc(sb + SM_B + rowhalf * 8192, 16, 1024, 1);
            const uint64_t dA1 = make_desc(sb + SM_A + rowhalf * 8192, 16, 1024, 1) - 4096;
            const uint64_t dB = make_desc(sb + SM_WQ + nh * 64, 16, 1024, 1);
            const uint64_t dC = make_desc(sb + SM_WKV, 128, 8192, 0);
            if (kv_wg) {
                #pragma unroll 1
                for (int ch = 0; ch < 8; ch++) {
                    if ((ch & 3) == 0) mbar_wait(bars + 8 * (B_X + (ch >> 2)), 0);
                    const uint64_t dA = ch < 4 ? dA0 : dA1;
                    wg_fence();
                    #pragma unroll
                    for (int ks = 0; ks < 4; ks++) wg_ss16(akv, dA + ch * 1024 + ks * 2, dC + (ch * 4 + ks) * 16);
                    wg_commit();
                }
                wg_wait<0>();
            }
            fence_regs<8>(akv);
            if (kv_wg) {
                const int key = qb * 128 + rowhalf * 64 + wiw * 16 + g;
                uint32_t pk[4];
                #pragma unroll
                for (int i = 0; i < 4; i++) pk[i] = pack_bf16(akv[2 * i], akv[2 * i + 1]);
                float st;
                if (kv_sel == 0) {
                    uint8_t* b = g_kimg + (key >> 3) * 256 + (key & 7) * 16 + 4 * t;
                    *(uint32_t*)(b) = pk[0]; *(uint32_t*)(b + 256) = pk[1]; *(uint32_t*)(b + 128) = pk[2]; *(uint32_t*)(b + 384) = pk[3];
                    float n0 = bf_lo(pk[0]) * bf_lo(pk[0]) + bf_hi(pk[0]) * bf_hi(pk[0]) + bf_lo(pk[2]) * bf_lo(pk[2]) + bf_hi(pk[2]) * bf_hi(pk[2]);
                    float n1 = bf_lo(pk[1]) * bf_lo(pk[1]) + bf_hi(pk[1]) * bf_hi(pk[1]) + bf_lo(pk[3]) * bf_lo(pk[3]) + bf_hi(pk[3]) * bf_hi(pk[3]);
                    n0 += __shfl_xor_sync(0xffffffffu, n0, 1); n0 += __shfl_xor_sync(0xffffffffu, n0, 2);
                    n1 += __shfl_xor_sync(0xffffffffu, n1, 1); n1 += __shfl_xor_sync(0xffffffffu, n1, 2);
                    st = (n0 != n0 || n1 != n1) ? __int_as_float(0x7f800000) : fmaxf(n0, n1);
                } else {
                    uint8_t* lo = g_vimg + key * 16 + 4 * t;
                    uint8_t* hi = g_vimg + 33792 + (31 - (key >> 6)) * 1024 + (key & 63) * 16 + 4 * t;
                    *(uint32_t*)(lo) = pk[0]; *(uint32_t*)(lo + 128) = pk[1]; *(uint32_t*)(hi) = pk[2]; *(uint32_t*)(hi + 128) = pk[3];
                    st = 0.0f;
                    #pragma unroll
                    for (int i = 0; i < 4; i++) {
                        float a = fabsf(bf_lo(pk[i])), b = fabsf(bf_hi(pk[i]));
                        st = (a != a || b != b) ? __int_as_float(0x7f800000) : fmaxf(st, fmaxf(a, b));
                    }
                }
                #pragma unroll
                for (int o = 16; o; o >>= 1) st = fmaxf(st, __shfl_xor_sync(0xffffffffu, st, o));
                if (lane == 0) s_misc[20 + wiw] = st;
                bar_arrive(3, 160);
            }
            uint2 mp[9];
            #pragma unroll
            for (int i = 0; i < 9; i++) { const int w = (tid & 127) + 128 * i; mp[i] = (w < TABN / 4) ? __ldg((const uint2*)g_tabmap.v + w) : make_uint2(0u, 0u); }
            mbar_wait(bars + 8 * B_WQ, 0);
            mbar_wait(bars + 8 * B_X, 0);
            PROF(2);
            #pragma unroll 1
            for (int ch = 0; ch < 4; ch++) {
                wg_fence();
                #pragma unroll
                for (int ks = 0; ks < 4; ks++) wg_ss32(acc, dA0 + ch * 1024 + ks * 2, dB + (ch * 4 + ks) * 128);
                wg_commit();
            }
            wg_wait<0>();
            fence_regs<16>(acc);
            bar_sync(1, 512);
            PROF(15);
            #pragma unroll
            for (int i = 0; i < 2; i++) {
                const int z = tid + 512 * i;
                if (z < 4 * 144) sts128(sBa + S_U + (z / 144) * ULEN * 2 + (PADU - 1152) * 2 + (z % 144) * 16, make_uint4(0, 0, 0, 0));
            }
            PROF(8);
            mbar_wait(bars + 8 * B_U, 0);
            PROF(14);
            #pragma unroll
            for (int i = 0; i < 2; i++) {
                const int l = 2 * (tid + 512 * i);
                const uint2 r0 = *(const uint2*)(sp + SM_SLAB + l * 16 + rank * 8), r1 = *(const uint2*)(sp + SM_SLAB + l * 16 + 16 + rank * 8);
                const uint32_t dst = swz128(sBa + S_U + (PADU + l) * 2);
                sts32(dst, __byte_perm(r0.x, r1.x, 0x5410));
                sts32(dst + ULEN * 2, __byte_perm(r0.x, r1.x, 0x7632));
                sts32(dst + ULEN * 4, __byte_perm(r0.y, r1.y, 0x5410));
                sts32(dst + ULEN * 6, __byte_perm(r0.y, r1.y, 0x7632));
            }
            bar_arrive(13, 544);
            {
                const float* kc = (const float*)(sB + S_KC + wg * 4096);
                uint2* tab = (uint2*)(sB + S_TAB + wg * TABN * 2);
                #pragma unroll
                for (int i = 0; i < 9; i++) {
                    const int w = (tid & 127) + 128 * i;
                    if (w < TABN / 4) tab[w] = make_uint2(pack_bf16(kc[mp[i].x & 0xFFFF], kc[mp[i].x >> 16]), pack_bf16(kc[mp[i].y & 0xFFFF], kc[mp[i].y >> 16]));
                }
            }
            fence_async_smem();
            bar_sync(1, 512);
            PROF(1);
            mbar_wait(bars + 8 * B_WQ2, 0);
            mbar_wait(bars + 8 * (B_X + 1), 0);
            fence_regs<16>(acc);
            wg_fence();
            #pragma unroll
            for (int ks = 16; ks < 32; ks++) wg_ss32(acc, dA1 + (ks >> 2) * 1024 + (ks & 3) * 2, dB + ks * 128);
            wg_commit();
            {
                const int task = tid + (tid < 8 ? 512 : 0) * 0;
                #pragma unroll 1
                for (int tk = task; tk < 4 * 130; tk += 512) {
                    const int c = tk / 130, i = tk % 130;
                    const uint32_t src = sBa + S_U + c * ULEN * 2 + (PADU + 8 * i - WPAD - 8) * 2;
                    const uint4 v0 = lds128(swz128(src)), v1 = lds128(swz128(src + 16)), v2 = lds128(swz128(src + 32));
                    float x[16];
                    const uint32_t vv[8] = {v0.z, v0.w, v1.x, v1.y, v1.z, v1.w, v2.x, v2.y};
                    #pragma unroll
                    for (int k = 0; k < 8; k++) { x[2 * k] = bf_lo(vv[k]); x[2 * k + 1] = bf_hi(vv[k]); }
                    float p2[15], w7[8], w9[8];
                    #pragma unroll
                    for (int e = 0; e < 15; e++) p2[e] = x[e] + x[e + 1];
                    #pragma unroll
                    for (int e = 0; e < 8; e++) {
                        w7[e] = (p2[e + 1] + p2[e + 3]) + (p2[e + 5] + x[e + 7]);
                        w9[e] = w7[e] + (x[e] + x[e + 8]);
                    }
                    sts128(swz(sBa + S_W7 + c * W3LEN * 2 + i * 16), make_uint4(pack_bf16(w7[0], w7[1]), pack_bf16(w7[2], w7[3]), pack_bf16(w7[4], w7[5]), pack_bf16(w7[6], w7[7])));
                    sts128(swz(sBa + S_W9 + c * W3LEN * 2 + i * 16), make_uint4(pack_bf16(w9[0], w9[1]), pack_bf16(w9[2], w9[3]), pack_bf16(w9[4], w9[5]), pack_bf16(w9[6], w9[7])));
                }
            }
            wg_wait<0>();
            fence_regs<16>(acc);
            bar_arrive(14, 544);
            const float QS = 0.25f * 1.4426950408889634f;
            float qm = 0.0f;
            #pragma unroll
            for (int i = 0; i < 2; i++) {
                #pragma unroll
                for (int j = 0; j < 4; j++) q[i][j] = pack_bf16(acc[8 * i + 2 * j] * QS, acc[8 * i + 2 * j + 1] * QS);
                float n0 = bf_lo(q[i][0]) * bf_lo(q[i][0]) + bf_hi(q[i][0]) * bf_hi(q[i][0]) + bf_lo(q[i][2]) * bf_lo(q[i][2]) + bf_hi(q[i][2]) * bf_hi(q[i][2]);
                float n1 = bf_lo(q[i][1]) * bf_lo(q[i][1]) + bf_hi(q[i][1]) * bf_hi(q[i][1]) + bf_lo(q[i][3]) * bf_lo(q[i][3]) + bf_hi(q[i][3]) * bf_hi(q[i][3]);
                n0 += __shfl_xor_sync(0xffffffffu, n0, 1); n0 += __shfl_xor_sync(0xffffffffu, n0, 2);
                n1 += __shfl_xor_sync(0xffffffffu, n1, 1); n1 += __shfl_xor_sync(0xffffffffu, n1, 2);
                qm = (n0 != n0 || n1 != n1) ? __int_as_float(0x7f800000) : fmaxf(qm, fmaxf(n0, n1));
            }
            #pragma unroll
            for (int o = 16; o; o >>= 1) qm = fmaxf(qm, __shfl_xor_sync(0xffffffffu, qm, o));
            if (lane == 0) s_misc[warp] = qm;
        }
        PROF(3);
        {
            const int c = wg;
            uint32_t sBl = sBa;
            asm volatile("" : "+r"(sBl) :: "memory");
            float acc[16];
            #pragma unroll
            for (int i = 0; i < 16; i++) acc[i] = 0.0f;
            fence_regs<16>(acc);
            const uint32_t tabc = sBl + S_TAB + c * TABN * 2;
            const uint32_t tD = tabc + ((g - 2 * t + 6) * TDW + 2 + 2 * wiw) * 4;
            const uint32_t uLo = (((sBl + S_U + c * ULEN * 2 + PADU * 2) & 0x3FFFF) >> 4) | (1u << 16);
            uint32_t A[2][4][4];
            auto load_set = [&](uint32_t (&X)[4][4], int m0) {
                asm volatile("{ .reg .pred p; setp.lt.u32 p, %2, 67; mov.b32 %0, 0; @p ld.shared.u32 %0, [%1]; }"
                             : "=r"(X[0][2]) : "r"(tD + 8 * m0 - 4), "r"(m0 + wiw) : "memory");
                #pragma unroll
                for (int i = 0; i < 4; i++) {
                    asm volatile("{ .reg .pred p; setp.lt.u32 p, %3, 67; mov.b32 %0, 0; mov.b32 %1, 0; @p ld.shared.v2.u32 {%0,%1}, [%2]; }"
                                 : "=r"(X[i][0]), "=r"(X[i][1]) : "r"(tD + 8 * (m0 + i)), "r"(m0 + i + wiw + 1) : "memory");
                }
                #pragma unroll
                for (int i = 0; i < 4; i++) {
                    asm volatile("mov.b32 %0, %1;" : "=r"(X[i][3]) : "r"(X[i][0]));
                    if (i < 3) asm volatile("mov.b32 %0, %1;" : "=r"(X[i + 1][2]) : "r"(X[i][1]));
                }
            };
            #pragma unroll 1
            for (int m0 = -3; m0 < 69; m0 += 8) {
                #pragma unroll
                for (int h = 0; h < 2; h++) {
                    load_set(A[h], m0 + 4 * h);
                    wg_fence();
                    #pragma unroll
                    for (int i = 0; i < 4; i++) wg_rs32(acc, A[h][i], uLo - 2 * (m0 + 4 * h + i));
                    wg_commit();
                    wg_wait<1>();
                }
            }
            bar_sync(1, 512);
            wg_wait<0>();
            fence_regs<16>(acc);
            PROF(6);
            {
                asm volatile("" : "+r"(sBl) :: "memory");
                const int mi = lane >> 3, r8 = lane & 7;
                const uint32_t frag = (16 * (8 * (mi >> 1) + r8) + 8 * (mi & 1)) * 2;
                const uint32_t t3 = sBl + S_TAB + c * TABN * 2 + (T3B + ((wiw & 1) ? (T3C + C3 + 1) : C3)) * 2 - (4 * g + wiw - 2 * t) * 2;
                #pragma unroll
                for (int s = 0; s < 2; s++) {
                    const uint32_t sig = swz(sBl + (s ? S_W7 : S_W9) + c * W3LEN * 2 + WPAD * 2 + frag - (s ? 16 : 32));
                    uint32_t a[4][4], R[4][2];
                    #pragma unroll
                    for (int b = 0; b < 4; b++) ldsm4t_p(a[b], sig + b * 512);
                    #pragma unroll
                    for (int i = 0; i < 4; i++) { R[i][0] = lds32_p(t3 + s * (T3S * 2) - 2 * (48 + 16 * i)); R[i][1] = lds32_p(t3 + s * (T3S * 2) - 2 * (40 + 16 * i)); }
                    #pragma unroll
                    for (int b = 0; b < 4; b++) {
                        mma_bf16_p(acc + 12, a[b][0], a[b][1], a[b][2], a[b][3], R[3 - b][0], R[3 - b][1]);
                        if (b < 2) mma_bf16_p(acc + 8, a[b][0], a[b][1], a[b][2], a[b][3], R[1 - b][0], R[1 - b][1]);
                    }
                }
            }
            __nv_bfloat16* ys = (__nv_bfloat16*)(sB + S_Y + c * 4096) + 128 * t + 16 * wiw + g;
            #pragma unroll
            for (int j = 0; j < 4; j++) {
                ys[512 * j] = __float2bfloat16_rn(acc[4 * j]);
                ys[512 * j + 64] = __float2bfloat16_rn(acc[4 * j + 1]);
                ys[512 * j + 8] = __float2bfloat16_rn(acc[4 * j + 2]);
                ys[512 * j + 72] = __float2bfloat16_rn(acc[4 * j + 3]);
            }
        }
        bar_arrive(10, 608);
        PROF(7);
        {
            mbar_wait(bars + 8 * B_ST, 0);
            PROF(9); PROFC(8);
            float qm = 0.0f;
            #pragma unroll
            for (int i = 0; i < 16; i++) qm = fmaxf(qm, s_misc[i]);
            const float vm = s_misc[17];
            const bool fast = (qm * s_misc[16] <= 60.0f * 60.0f) && (vm <= 1.0e12f) && (vm >= 1.0e-12f || vm == 0.0f);
            uint8_t* ob = g_oimg + qb * 131072 + hg * 16384 + nh * 8192 + (rowhalf * 8 + wiw * 2) * 128 + g * 16 + 4 * t;
            uint32_t cA = 0xBF00BF00u, cB = 0x00030003u;
            asm volatile("" : "+r"(cA), "+r"(cB));
            #pragma unroll 1
            for (int tile = 0; tile < 2; tile++) {
                uint32_t kLo = (((sb + SM_K) & 0x3FFFF) >> 4) | (8u << 16), vLo = (((sb + SM_V) & 0x3FFFF) >> 4) | (8u << 16), vHi = 2048;
                float o[12], s[32];
                uint32_t p[16], qq[4];
                #pragma unroll
                for (int i = 0; i < 4; i++) { qq[i] = tile ? q[1][i] : q[0][i]; asm volatile("" : "+r"(qq[i])); }
                #pragma unroll
                for (int i = 0; i < 12; i++) o[i] = 0.0f;
                #pragma unroll
                for (int i = 0; i < 32; i++) s[i] = 0.0f;
                fence_regs<12>(o);
                fence_regs<32>(s);
                if (fast) {
                    #pragma unroll 1
                    for (int c = 0; c < SEQ / 256; c++) {
                        if (c <= 4) mbar_wait(bars + 8 * (B_KV + (c < 2 ? c : c < 4 ? 2 : 3)), 0);
                        wg_fence();
                        wg_qk(s, qq, kLo);
                        wg_commit();
                        #pragma unroll
                        for (int u = 0; u < 4; u++) {
                            wg_wait<0>();
                            fence_regs<32>(s);
                            #pragma unroll
                            for (int i = 0; i < 16; i++) {
                                if ((MUFU_MASK >> i) & 1) p[i] = exp_mufu(s[2 * i], s[2 * i + 1]);
                                else p[i] = exp_sw(s[2 * i], s[2 * i + 1], cA, cB);
                            }
                            wg_fence();
                            if (u + 1 < 4) wg_qk(s, qq, kLo + (u + 1) * 128);
                            #pragma unroll
                            for (int kk = 0; kk < 4; kk++) wg_pv(o, p + 4 * kk, vLo + u * 64 + kk * 16, vHi - u * 64);
                            wg_commit();
                        }
                        kLo += 512; vLo += 256; vHi -= 256;
                    }
                    wg_wait<0>();
                } else {
                    float mx0 = -INFINITY, mx1 = -INFINITY;
                    #pragma unroll 1
                    for (int c = 0; c < SEQ / 64; c++) {
                        if (c <= 16) mbar_wait(bars + 8 * (B_KV + (c < 8 ? (c >> 2) : c < 16 ? 2 : 3)), 0);
                        wg_fence();
                        wg_qk(s, qq, kLo);
                        wg_commit();
                        wg_wait<0>();
                        fence_regs<32>(s);
                        fence_regs<12>(o);
                        float m0 = mx0, m1 = mx1;
                        #pragma unroll
                        for (int j = 0; j < 8; j++) {
                            m0 = fmaxf(m0, fmaxf(s[4 * j], s[4 * j + 1]));
                            m1 = fmaxf(m1, fmaxf(s[4 * j + 2], s[4 * j + 3]));
                        }
                        m0 = fmaxf(m0, __shfl_xor_sync(0xffffffffu, m0, 1)); m0 = fmaxf(m0, __shfl_xor_sync(0xffffffffu, m0, 2));
                        m1 = fmaxf(m1, __shfl_xor_sync(0xffffffffu, m1, 1)); m1 = fmaxf(m1, __shfl_xor_sync(0xffffffffu, m1, 2));
                        const float c0 = ex2f(mx0 - m0), c1 = ex2f(mx1 - m1);
                        mx0 = m0; mx1 = m1;
                        #pragma unroll
                        for (int j = 0; j < 3; j++) { o[4 * j] *= c0; o[4 * j + 1] *= c0; o[4 * j + 2] *= c1; o[4 * j + 3] *= c1; }
                        #pragma unroll
                        for (int j = 0; j < 8; j++) {
                            p[2 * j] = exp_mufu(s[4 * j] - m0, s[4 * j + 1] - m0);
                            p[2 * j + 1] = exp_mufu(s[4 * j + 2] - m1, s[4 * j + 3] - m1);
                        }
                        wg_fence();
                        #pragma unroll
                        for (int kk = 0; kk < 4; kk++) wg_pv(o, p + 4 * kk, vLo + kk * 16, vHi);
                        wg_commit();
                        wg_wait<0>();
                        kLo += 128; vLo += 64; vHi -= 64;
                    }
                }
                fence_regs<12>(o);
                if (tile == 0) PROFC(3);
                const float i0 = 1.0f / o[4], i1 = 1.0f / o[6];
                uint8_t* b = ob + tile * 4096;
                *(uint32_t*)(b) = pack_bf16(o[0] * i0, o[1] * i0);
                *(uint32_t*)(b + 128) = pack_bf16(o[2] * i1, o[3] * i1);
                *(uint32_t*)(b + 2048) = pack_bf16(o[8] * i0, o[9] * i0);
                *(uint32_t*)(b + 2048 + 128) = pack_bf16(o[10] * i1, o[11] * i1);
            }
        }
        PROF(10); PROFC(9);
        bar_arrive(12, 544);

        {
            float acc[16];
            #pragma unroll
            for (int i = 0; i < 16; i++) acc[i] = 0.0f;
            fence_regs<16>(acc);
            const uint64_t dA = make_desc(sb + SM_A + rowhalf * 1024, 2048, 128, 0);
            const uint64_t dB = make_desc(sb + SM_B + nh * 64, 16, 1024, 1);
            mbar_wait(bars + 8 * B_WO, 0);
            #pragma unroll 1
            for (int i = 0; i < 8; i++) {
                const int src = (hg + i) & 7;
                mbar_wait(bars + 8 * (B_O + src), 0);
                wg_fence();
                #pragma unroll
                for (int kk = 0; kk < 4; kk++) wg_ss32(acc, dA + src * 1024 + kk * 256, dB + (src * 4 + kk) * 128);
                wg_commit();
            }
            wg_wait<0>();
            fence_regs<16>(acc);
            PROF(12);
            const int row = qb * 128 + rowhalf * 64 + wiw * 16 + g;
            uint32_t* o32 = (uint32_t*)(P.out + (size_t)row * 1024 + hg * 64 + nh * 32 + 2 * t);
            #pragma unroll
            for (int j = 0; j < 4; j++) {
                o32[4 * j] = pack_bf16(acc[4 * j], acc[4 * j + 1]);
                o32[4 * j + 8 * 512] = pack_bf16(acc[4 * j + 2], acc[4 * j + 3]);
            }
        }
        PROF(13);
    }
}

typedef CUresult (*EncodeFn)(CUtensorMap*, CUtensorMapDataType, cuuint32_t, void*, const cuuint64_t*, const cuuint64_t*,
                             const cuuint32_t*, const cuuint32_t*, CUtensorMapInterleave, CUtensorMapSwizzle,
                             CUtensorMapL2promotion, CUtensorMapFloatOOBfill);

void make_map(EncodeFn fn, CUtensorMap* m, const void* ptr, uint64_t inner, uint64_t outer, uint32_t box_in, uint32_t box_out, CUtensorMapSwizzle swz) {
    cuuint64_t dims[2] = {inner, outer};
    cuuint64_t strides[1] = {inner * 2};
    cuuint32_t box[2] = {box_in, box_out};
    cuuint32_t es[2] = {1, 1};
    fn(m, CU_TENSOR_MAP_DATA_TYPE_BFLOAT16, 2, const_cast<void*>(ptr), dims, strides, box, es, CU_TENSOR_MAP_INTERLEAVE_NONE, swz,
       CU_TENSOR_MAP_L2_PROMOTION_L2_128B, CU_TENSOR_MAP_FLOAT_OOB_FILL_NONE);
}

}

extern "C" void kernel_launch(void* const* d_in, const int* in_sizes, int n_in, void* d_out, int out_size) {
    (void)in_sizes; (void)n_in; (void)out_size;
    static EncodeFn fn = nullptr;
    if (!fn) {
        void* p = nullptr;
        cudaDriverEntryPointQueryResult qr;
        cudaGetDriverEntryPoint("cuTensorMapEncodeTiled", &p, cudaEnableDefault, &qr);
        fn = (EncodeFn)p;
        cudaFuncSetAttribute(fused_kernel, cudaFuncAttributeMaxDynamicSharedMemorySize, SM_ALLOC);
    }
    CUtensorMap tx, twq, two, twk, twv, tu;
    {
        cuuint64_t dims[3] = {64, 2048, 8};
        cuuint64_t strides[2] = {1024, 128};
        cuuint32_t box[3] = {64, 128, 4};
        cuuint32_t es[3] = {1, 1, 1};
        fn(&tx, CU_TENSOR_MAP_DATA_TYPE_BFLOAT16, 3, d_in[0], dims, strides, box, es, CU_TENSOR_MAP_INTERLEAVE_NONE, CU_TENSOR_MAP_SWIZZLE_128B,
           CU_TENSOR_MAP_L2_PROMOTION_L2_128B, CU_TENSOR_MAP_FLOAT_OOB_FILL_NONE);
    }
    make_map(fn, &tu, d_in[5], 512, 2048, 8, 256, CU_TENSOR_MAP_SWIZZLE_NONE);
    make_map(fn, &twq, d_in[1], 512, 512, 64, 256, CU_TENSOR_MAP_SWIZZLE_128B);
    make_map(fn, &twk, d_in[2], 16, 512, 8, 256, CU_TENSOR_MAP_SWIZZLE_NONE);
    make_map(fn, &twv, d_in[3], 16, 512, 8, 256, CU_TENSOR_MAP_SWIZZLE_NONE);
    make_map(fn, &two, d_in[4], 512, 512, 64, 256, CU_TENSOR_MAP_SWIZZLE_128B);
    Params P;
    P.u = (const __nv_bfloat16*)d_in[5];
    P.lar = (const __nv_bfloat16*)d_in[6];
    P.aim = (const __nv_bfloat16*)d_in[7];
    P.cre = (const __nv_bfloat16*)d_in[8];
    P.cim = (const __nv_bfloat16*)d_in[9];
    P.logdt = (const __nv_bfloat16*)d_in[10];
    P.dskip = (const __nv_bfloat16*)d_in[11];
    P.out = (__nv_bfloat16*)d_out;
    fused_kernel<<<NCTA, NTHR, SM_ALLOC>>>(tx, twq, two, twk, twv, tu, P);
}
```

```cpp
#include <cuda_runtime.h>
#include <cuda_bf16.h>
#include <cuda_fp16.h>
#include <cuda.h>
#include <stdint.h>

namespace {

constexpr int SEQ = 2048;
constexpr int NCTA = 128, NTHR = 640;

constexpr int SM_A = 0;
constexpr int SM_WQ = 65536;
constexpr int SM_SLAB = SM_WQ + 32768;
constexpr int SM_K = 0, SM_V = 65536;
constexpr int SM_B = 132096;
constexpr int SM_WKV = SM_B + 65536;

constexpr int PADU = 1536, ULEN = PADU + 2048;
constexpr int WPAD = 16, W3LEN = WPAD + 1024;
constexpr int TABN = 2592;
constexpr int S_U = 0;
constexpr int S_W7 = S_U + 4 * ULEN * 2;
constexpr int S_W9 = S_W7 + 4 * W3LEN * 2;
constexpr int S_TAB = S_W9 + 4 * W3LEN * 2;
constexpr int S_KC = 214016 - SM_B;
constexpr int S_Y = S_KC;
constexpr int SM_BAR = SM_B + S_KC + 16384;
constexpr int SM_TOTAL = SM_BAR + 1024;
constexpr int SM_ALLOC = SM_TOTAL + 1024;
static_assert(SM_V + 65536 + 1024 <= SM_B && SM_ALLOC <= 232448 && S_TAB + 4 * TABN * 2 <= S_KC && SM_WKV + 16384 <= SM_B + S_KC, "smem map");

constexpr int TD0 = 0, TD1 = 1072, CD = 1056;
constexpr int T3B = 2144, T3S = 224, T3C = 112, C3 = 136;

constexpr int rne8(int t) {
    if (t < 256) return t;
    int sh = 0;
    while ((t >> sh) >= 256) sh++;
    int q = t >> sh, rem = t & ((1 << sh) - 1), half = 1 << (sh - 1);
    if (rem > half || (rem == half && (q & 1))) q++;
    return q << sh;
}
constexpr int kcidx(int p) {
    if (p < 256) return (p >> 3) * 24 + (p & 7);
    if (p < 512) return ((p - 256) >> 3) * 24 + 8 + (((p - 256) & 7) >> 1);
    if (p < 1024) { int q = p - 512, hi = q >> 8, rem = q & 255; return (rem >> 3) * 24 + 12 + 2 * hi + ((rem & 7) >> 2); }
    if (p < 2048) { int q = p - 1024; return ((q & 255) >> 3) * 24 + 16 + (q >> 8); }
    return 20;
}
constexpr int KC_ZERO = 23;
constexpr int tab_dense(int t) { return (t >= 0 && t <= 1028) ? kcidx(rne8(t)) : KC_ZERO; }
constexpr int tab_3(int s, int lag) { return (lag >= 64 && lag <= 127) ? kcidx(s == 0 ? 16 * (lag + 1) : 16 * lag + 8) : KC_ZERO; }
struct TabMap {
    uint16_t v[TABN];
    constexpr TabMap() : v{} {
        for (int i = 0; i < TD1; i++) { v[TD0 + i] = tab_dense(CD - i); v[TD1 + i] = tab_dense(CD + 1 - i); }
        for (int s = 0; s < 2; s++)
            for (int i = 0; i < T3C; i++) { v[T3B + s * T3S + i] = tab_3(s, C3 - i); v[T3B + s * T3S + T3C + i] = tab_3(s, C3 + 1 - i); }
    }
};
__device__ const __align__(16) TabMap g_tabmap = TabMap();

__device__ __align__(1024) uint8_t g_kimg[65536];
__device__ __align__(1024) uint8_t g_vimg[65536 + 1024];
__device__ __align__(1024) uint8_t g_oimg[16 * 131072];
__device__ unsigned long long g_flag_kv[64];
__device__ unsigned g_flag_o[128];
__device__ unsigned g_epoch;
__device__ unsigned g_done;

#define PROF(i) do {} while (0)
#define PROF2(i) do {} while (0)
#define PROFC(i) do {} while (0)
#define PROF3(i) do {} while (0)

__device__ __forceinline__ uint32_t smem_u32(const void* p) { return (uint32_t)__cvta_generic_to_shared(p); }
__device__ __forceinline__ void mbar_init(uint32_t bar, uint32_t cnt) { asm volatile("mbarrier.init.shared::cta.b64 [%0], %1;" :: "r"(bar), "r"(cnt) : "memory"); }
__device__ __forceinline__ void mbar_expect_tx(uint32_t bar, uint32_t bytes) {
    asm volatile("mbarrier.arrive.expect_tx.shared::cta.b64 _, [%0], %1;" :: "r"(bar), "r"(bytes) : "memory"); }
__device__ __forceinline__ void mbar_wait(uint32_t bar, uint32_t parity) {
    uint32_t ok = 0;
    for (int it = 0; it < (1 << 22) && !ok; it++) {
        asm volatile("{ .reg .pred p; mbarrier.try_wait.parity.shared::cta.b64 p, [%1], %2; selp.u32 %0, 1, 0, p; }"
                     : "=r"(ok) : "r"(bar), "r"(parity) : "memory");
    }
}
__device__ __forceinline__ void tma_2d(uint32_t dst, const CUtensorMap* map, int c0, int c1, uint32_t bar) {
    asm volatile("cp.async.bulk.tensor.2d.shared::cluster.global.mbarrier::complete_tx::bytes [%0], [%1, {%3, %4}], [%2];"
                 :: "r"(dst), "l"((uint64_t)map), "r"(bar), "r"(c0), "r"(c1) : "memory");
}
__device__ __forceinline__ void tma_2d_mc(uint32_t dst, const CUtensorMap* map, int c0, int c1, uint32_t bar) {
    asm volatile("cp.async.bulk.tensor.2d.shared::cluster.global.mbarrier::complete_tx::bytes.multicast::cluster [%0], [%1, {%3, %4}], [%2], %5;"
                 :: "r"(dst), "l"((uint64_t)map), "r"(bar), "r"(c0), "r"(c1), "h"((uint16_t)3) : "memory");
}
__device__ __forceinline__ void bulk_g2s_mc(uint32_t dst, const void* src, uint32_t bytes, uint32_t bar) {
    asm volatile("cp.async.bulk.shared::cluster.global.mbarrier::complete_tx::bytes.multicast::cluster [%0], [%1], %2, [%3], %4;"
                 :: "r"(dst), "l"((uint64_t)src), "r"(bytes), "r"(bar), "h"((uint16_t)3) : "memory");
}
__device__ __forceinline__ void pair_sync(uint32_t bar, uint32_t peer) {
    uint32_t ra;
    asm volatile("mapa.shared::cluster.u32 %0, %1, %2;" : "=r"(ra) : "r"(bar), "r"(peer));
    asm volatile("mbarrier.arrive.shared::cluster.b64 _, [%0];" :: "r"(ra) : "memory");
    asm volatile("mbarrier.arrive.shared::cta.b64 _, [%0];" :: "r"(bar) : "memory");
    uint32_t ok = 0;
    for (int it = 0; it < (1 << 22) && !ok; it++) {
        asm volatile("{ .reg .pred p; mbarrier.try_wait.parity.shared::cta.b64 p, [%1], 0; selp.u32 %0, 1, 0, p; }"
                     : "=r"(ok) : "r"(bar) : "memory");
    }
}
__device__ __forceinline__ void fence_async_all() { asm volatile("fence.proxy.async.global;" ::: "memory"); }
__device__ __forceinline__ void fence_async_smem() { asm volatile("fence.proxy.async.shared::cta;" ::: "memory"); }
__device__ __forceinline__ unsigned ld_acquire(const unsigned* p) {
    unsigned v; asm volatile("ld.acquire.gpu.global.u32 %0, [%1];" : "=r"(v) : "l"(p) : "memory"); return v; }
__device__ __forceinline__ void st_release(unsigned* p, unsigned v) { asm volatile("st.release.gpu.global.u32 [%0], %1;" :: "l"(p), "r"(v) : "memory"); }
__device__ __forceinline__ void wait_flag(const unsigned* p, unsigned epoch) {
    for (int it = 0; it < (1 << 22); it++) { if (ld_acquire(p) == epoch) break; }
}
__device__ __forceinline__ unsigned long long ld_acquire64(const unsigned long long* p) {
    unsigned long long v; asm volatile("ld.acquire.gpu.global.u64 %0, [%1];" : "=l"(v) : "l"(p) : "memory"); return v; }
__device__ __forceinline__ void st_release64(unsigned long long* p, unsigned long long v) { asm volatile("st.release.gpu.global.u64 [%0], %1;" :: "l"(p), "l"(v) : "memory"); }
__device__ __forceinline__ float wait_flag64(const unsigned long long* p, unsigned epoch) {
    unsigned long long v = 0;
    for (int it = 0; it < (1 << 22); it++) { v = ld_acquire64(p); if ((unsigned)(v >> 32) == epoch) break; }
    return __uint_as_float((unsigned)v);
}
__device__ __forceinline__ void tma_3d_mc(uint32_t dst, const CUtensorMap* map, int c0, int c1, int c2, uint32_t bar) {
    asm volatile("cp.async.bulk.tensor.3d.shared::cluster.global.mbarrier::complete_tx::bytes.multicast::cluster [%0], [%1, {%3, %4, %5}], [%2], %6;"
                 :: "r"(dst), "l"((uint64_t)map), "r"(bar), "r"(c0), "r"(c1), "r"(c2), "h"((uint16_t)3) : "memory");
}
__device__ __forceinline__ void bar_sync(int id, int n) { asm volatile("bar.sync %0, %1;" :: "r"(id), "r"(n) : "memory"); }
__device__ __forceinline__ void bar_arrive(int id, int n) { asm volatile("bar.arrive %0, %1;" :: "r"(id), "r"(n) : "memory"); }
__device__ __forceinline__ void mbar_arrive(uint32_t bar) { asm volatile("mbarrier.arrive.shared::cta.b64 _, [%0];" :: "r"(bar) : "memory"); }

__device__ __forceinline__ uint64_t make_desc(uint32_t saddr, uint32_t lbo, uint32_t sbo, uint32_t swz) {
    uint64_t d = 0;
    d |= (uint64_t)((saddr & 0x3FFFF) >> 4);
    d |= (uint64_t)((lbo >> 4) & 0x3FFF) << 16;
    d |= (uint64_t)((sbo >> 4) & 0x3FFF) << 32;
    d |= (uint64_t)swz << 62;
    return d;
}
__device__ __forceinline__ void wg_fence() { asm volatile("wgmma.fence.sync.aligned;" ::: "memory"); }
__device__ __forceinline__ void wg_commit() { asm volatile("wgmma.commit_group.sync.aligned;" ::: "memory"); }
template<int N> __device__ __forceinline__ void wg_wait() { asm volatile("wgmma.wait_group.sync.aligned %0;" :: "n"(N) : "memory"); }
#define A4(d, o) "+f"(d[o + 0]), "+f"(d[o + 1]), "+f"(d[o + 2]), "+f"(d[o + 3])
#define A16(d, o) A4(d, o), A4(d, o + 4), A4(d, o + 8), A4(d, o + 12)

__device__ __forceinline__ void wg_pv(float* d, const uint32_t* a, uint32_t lo, uint32_t hi) {
    asm volatile("{ .reg .b64 dd; mov.b64 dd, {%16, %17};\n"
                 "wgmma.mma_async.sync.aligned.m64n24k16.f32.bf16.bf16 {%0,%1,%2,%3,%4,%5,%6,%7,%8,%9,%10,%11}, {%12,%13,%14,%15}, dd, 1, 1, 1, 1; }"
                 : A4(d, 0), A4(d, 4), A4(d, 8) : "r"(a[0]), "r"(a[1]), "r"(a[2]), "r"(a[3]), "r"(lo), "r"(hi));
}
__device__ __forceinline__ void wg_qk(float* d, const uint32_t* a, uint32_t lo) {
    asm volatile("{ .reg .b64 dd; mov.b64 dd, {%36, %37};\n"
                 "wgmma.mma_async.sync.aligned.m64n64k16.f32.bf16.bf16 {%0,%1,%2,%3,%4,%5,%6,%7,%8,%9,%10,%11,%12,%13,%14,%15,%16,%17,%18,%19,%20,%21,%22,%23,%24,%25,%26,%27,%28,%29,%30,%31}, {%32,%33,%34,%35}, dd, 0, 1, 1, 0; }"
                 : A16(d, 0), A16(d, 16) : "r"(a[0]), "r"(a[1]), "r"(a[2]), "r"(a[3]), "r"(lo), "r"(16));
}
__device__ __forceinline__ void wg_rs32(float* d, const uint32_t* a, uint32_t lo) {
    asm volatile("{ .reg .b64 dd; mov.b64 dd, {%20, %21};\n"
                 "wgmma.mma_async.sync.aligned.m64n32k16.f32.bf16.bf16 {%0,%1,%2,%3,%4,%5,%6,%7,%8,%9,%10,%11,%12,%13,%14,%15}, {%16,%17,%18,%19}, dd, 1, 1, 1, 0; }"
                 : A16(d, 0) : "r"(a[0]), "r"(a[1]), "r"(a[2]), "r"(a[3]), "r"(lo), "r"(0x40000040));
}
__device__ __forceinline__ void wg_ss32(float* d, uint64_t da, uint64_t db) {
    asm volatile("wgmma.mma_async.sync.aligned.m64n32k16.f32.bf16.bf16 {%0,%1,%2,%3,%4,%5,%6,%7,%8,%9,%10,%11,%12,%13,%14,%15}, %16, %17, 1, 1, 1, 0, 1;"
                 : A16(d, 0) : "l"(da), "l"(db));
}
__device__ __forceinline__ void wg_ss16(float* d, uint64_t da, uint64_t db) {
    asm volatile("wgmma.mma_async.sync.aligned.m64n16k16.f32.bf16.bf16 {%0,%1,%2,%3,%4,%5,%6,%7}, %8, %9, 1, 1, 1, 0, 1;"
                 : A4(d, 0), A4(d, 4) : "l"(da), "l"(db));
}
template<int N> __device__ __forceinline__ void fence_regs(float* r) {
    #pragma unroll
    for (int i = 0; i < N; i++) asm volatile("" : "+f"(r[i]) :: "memory");
}
__device__ __forceinline__ void mma_f16(float* d, const uint32_t* a, uint32_t b0, uint32_t b1) {
    asm volatile("mma.sync.aligned.m16n8k16.row.col.f32.f16.f16.f32 {%0,%1,%2,%3}, {%4,%5,%6,%7}, {%8,%9}, {%0,%1,%2,%3};"
                 : "+f"(d[0]), "+f"(d[1]), "+f"(d[2]), "+f"(d[3]) : "r"(a[0]), "r"(a[1]), "r"(a[2]), "r"(a[3]), "r"(b0), "r"(b1));
}
__device__ __forceinline__ uint32_t lds32(uint32_t addr) { uint32_t v; asm volatile("ld.shared.u32 %0, [%1];" : "=r"(v) : "r"(addr) : "memory"); return v; }
__device__ __forceinline__ void mma_bf16_p(float* d, uint32_t a0, uint32_t a1, uint32_t a2, uint32_t a3, uint32_t b0, uint32_t b1) {
    asm("mma.sync.aligned.m16n8k16.row.col.f32.bf16.bf16.f32 {%0,%1,%2,%3}, {%4,%5,%6,%7}, {%8,%9}, {%0,%1,%2,%3};"
        : "+f"(d[0]), "+f"(d[1]), "+f"(d[2]), "+f"(d[3]) : "r"(a0), "r"(a1), "r"(a2), "r"(a3), "r"(b0), "r"(b1));
}
__device__ __forceinline__ void ldsm4t_p(uint32_t* r, uint32_t addr) {
    asm("ldmatrix.sync.aligned.m8n8.x4.trans.shared.b16 {%0,%1,%2,%3}, [%4];" : "=r"(r[0]), "=r"(r[1]), "=r"(r[2]), "=r"(r[3]) : "r"(addr));
}
__device__ __forceinline__ uint32_t lds32_p(uint32_t addr) { uint32_t v; asm("ld.shared.u32 %0, [%1];" : "=r"(v) : "r"(addr)); return v; }
__device__ __forceinline__ uint32_t swz(uint32_t a) { return a ^ ((a >> 3) & 16u); }
__device__ __forceinline__ uint32_t swz128(uint32_t a) { return a ^ ((a >> 3) & 0x70u); }
__device__ __forceinline__ void sts32(uint32_t addr, uint32_t v) { asm volatile("st.shared.u32 [%0], %1;" :: "r"(addr), "r"(v) : "memory"); }
__device__ __forceinline__ void sts128(uint32_t addr, uint4 v) { asm volatile("st.shared.v4.u32 [%0], {%1,%2,%3,%4};" :: "r"(addr), "r"(v.x), "r"(v.y), "r"(v.z), "r"(v.w) : "memory"); }
__device__ __forceinline__ uint4 lds128(uint32_t addr) { uint4 v; asm volatile("ld.shared.v4.u32 {%0,%1,%2,%3}, [%4];" : "=r"(v.x), "=r"(v.y), "=r"(v.z), "=r"(v.w) : "r"(addr) : "memory"); return v; }
__device__ __forceinline__ float ex2f(float x) { float r; asm("ex2.approx.ftz.f32 %0, %1;" : "=f"(r) : "f"(x)); return r; }
__device__ __forceinline__ uint32_t pack_bf16(float lo, float hi) { uint32_t r; asm("cvt.rn.bf16x2.f32 %0, %1, %2;" : "=r"(r) : "f"(hi), "f"(lo)); return r; }
__device__ __forceinline__ uint32_t pack_f16(float lo, float hi) { uint32_t r; asm("cvt.rn.f16x2.f32 %0, %1, %2;" : "=r"(r) : "f"(hi), "f"(lo)); return r; }
__device__ __forceinline__ float bf_lo(uint32_t v) { return __uint_as_float(v << 16); }
__device__ __forceinline__ float bf_hi(uint32_t v) { return __uint_as_float(v & 0xFFFF0000u); }
__device__ __forceinline__ float bf_round(float x) { return __bfloat162float(__float2bfloat16_rn(x)); }

__device__ __forceinline__ uint32_t exp_mufu(float x0, float x1) { return pack_bf16(ex2f(x0), ex2f(x1)); }
#define SW_MAGIC (256.0f + 127.0f - 0.598938f)
__device__ __forceinline__ uint32_t exp_sw(float x0, float x1, uint32_t cA, uint32_t cB) {
    float t0 = x0 + SW_MAGIC, t1 = x1 + SW_MAGIC;
    uint32_t L, mh, ec, r;
    asm("prmt.b32 %0, %1, %2, 0x6521;" : "=r"(L) : "r"(__float_as_uint(t0)), "r"(__float_as_uint(t1)));
    asm("lop3.b32 %0, %1, 0x007F007F, %2, 0xEA;" : "=r"(mh) : "r"(L), "r"(cA));
    asm("lop3.b32 %0, %1, 0x7F807F80, %2, 0xEA;" : "=r"(ec) : "r"(L), "r"(cB));
    asm("fma.rn.bf16x2 %0, %1, %2, %3;" : "=r"(r) : "r"(L), "r"(mh), "r"(ec));
    return r;
}
constexpr uint32_t MUFU_MASK = 0x4949;

struct cf { float x, y; };
__device__ __forceinline__ cf cmul(cf a, cf b) { cf r; r.x = a.x * b.x - a.y * b.y; r.y = a.x * b.y + a.y * b.x; return r; }
__device__ __forceinline__ cf cexp_p(float a2, float b, float p) {
    float e = ex2f(a2 * p);
    float ph = b * p;
    ph -= (ph + 12582912.0f) - 12582912.0f;
    float ang = ph * 6.283185307f;
    cf r; r.x = e * __cosf(ang); r.y = e * __sinf(ang);
    return r;
}
__device__ __forceinline__ uint32_t h2_cmul(uint32_t w, uint32_t wsw, uint32_t e) {
    __half2 hw = *(__half2*)&w, hs = *(__half2*)&wsw, he = *(__half2*)&e;
    __half2 r = __hfma2(hs, __high2half2(he), __hmul2(hw, __low2half2(he)));
    return *(uint32_t*)&r;
}

template<bool B> struct BoolC { static constexpr bool value = B; };
struct Params {
    const __nv_bfloat16 *u, *lar, *aim, *cre, *cim, *logdt, *dskip;
    __nv_bfloat16* out;
};

constexpr int B_O = 0, B_KV = 8, B_WO = 12, B_WQ2 = 13, B_ST = 14, B_H = 15, B_X = 17, B_U = 19, B_WQ = 20;

__device__ __forceinline__ void helper_role(const Params& P, uint8_t* sp, uint32_t sb, unsigned epoch) {
    const uint32_t sBa = sb + SM_B;
    const int tid = threadIdx.x - 544;
    const int d0 = blockIdx.x * 4;
    uint8_t* sB = sp + SM_B;
    const uint2 dsk = __ldg((const uint2*)(P.dskip + d0));
    asm volatile("barrier.cluster.wait.aligned;" ::: "memory");
    {
        const int hg = blockIdx.x & 7;
        if (hg < 4 && tid < 32) {
            bar_sync(3, 160);
            if (tid == 0) {
                const float* s_misc = (const float*)(sp + SM_BAR + 256);
                const float st = fmaxf(fmaxf(s_misc[20], s_misc[21]), fmaxf(s_misc[22], s_misc[23]));
                st_release64(&g_flag_kv[((blockIdx.x >> 3) * 2 + (hg & 1)) * 2 + (hg >> 1)], ((unsigned long long)epoch << 32) | __float_as_uint(st));
            }
            __syncwarp();
        }
    }
    PROF2(2);
    bar_sync(10, 608);
    {
        uint32_t dd[4] = {__byte_perm(dsk.x, 0, 0x1010), __byte_perm(dsk.x, 0, 0x3232), __byte_perm(dsk.y, 0, 0x1010), __byte_perm(dsk.y, 0, 0x3232)};
        #pragma unroll 2
        for (int pi = tid; pi < 1024; pi += 96) {
            const int l = 2 * pi;
            uint32_t r[4];
            #pragma unroll
            for (int cc = 0; cc < 4; cc++) {
                const uint32_t y2 = *(const uint32_t*)(sB + S_Y + cc * 4096 + l * 2);
                const uint32_t u2 = lds32(swz128(sBa + S_U + cc * ULEN * 2 + (PADU + l) * 2));
                __nv_bfloat162 pr = __hmul2(*(const __nv_bfloat162*)&u2, *(const __nv_bfloat162*)&dd[cc]);
                __nv_bfloat162 sm = __hadd2(*(const __nv_bfloat162*)&y2, pr);
                r[cc] = *(uint32_t*)&sm;
            }
            *(uint2*)(P.out + (size_t)l * 1024 + 512 + d0) = make_uint2(__byte_perm(r[0], r[1], 0x5410), __byte_perm(r[2], r[3], 0x5410));
            *(uint2*)(P.out + (size_t)(l + 1) * 1024 + 512 + d0) = make_uint2(__byte_perm(r[0], r[1], 0x7632), __byte_perm(r[2], r[3], 0x7632));
        }
    }
    bar_arrive(11, 128);
    PROF2(4);
}

__global__ void __cluster_dims__(2, 1, 1) __launch_bounds__(NTHR, 1)
fused_kernel(const __grid_constant__ CUtensorMap tm_x, const __grid_constant__ CUtensorMap tm_wq,
             const __grid_constant__ CUtensorMap tm_wo, const __grid_constant__ CUtensorMap tm_wk,
             const __grid_constant__ CUtensorMap tm_wv, const __grid_constant__ CUtensorMap tm_u, const Params P) {
    extern __shared__ uint8_t smem_raw[];
    const uint32_t sb = (smem_u32(smem_raw) + 1023u) & ~1023u;
    uint8_t* sp = smem_raw + (sb - smem_u32(smem_raw));

    const int tid = threadIdx.x, warp = tid >> 5, lane = tid & 31, wg = tid >> 7, wiw = warp & 3;
    const int g = lane >> 2, t = lane & 3;
    const int qb = blockIdx.x >> 3, hg = blockIdx.x & 7;
    const uint32_t rank = blockIdx.x & 1;
    const int rowhalf = wg & 1, nh = wg >> 1;
    const bool kv_cta = hg < 4;
    const int kv_sel = hg >> 1;
    const bool kv_wg = kv_cta && (wg == (hg & 1));

    const uint32_t bars = sb + SM_BAR;
    float* s_misc = (float*)(sp + SM_BAR + 256);
    const CUtensorMap* tm_kv = kv_sel ? &tm_wv : &tm_wk;

    PROF(0);
    unsigned short p_lar = 0, p_aim = 0, p_cre = 0, p_cim = 0, p_ldt = 0;
    if (wg < 4) {
        const int n = (blockIdx.x * 4 + wg) * 128 + (tid & 127);
        p_lar = __ldg((const unsigned short*)P.lar + n);
        p_aim = __ldg((const unsigned short*)P.aim + n);
        p_cre = __ldg((const unsigned short*)P.cre + n);
        p_cim = __ldg((const unsigned short*)P.cim + n);
        p_ldt = __ldg((const unsigned short*)P.logdt + blockIdx.x * 4 + wg);
    } else if (warp == 16) {
        PROF3(5);
        if (lane == 0) {
            asm volatile("prefetch.tensormap [%0];" :: "l"((uint64_t)&tm_x) : "memory");
            asm volatile("prefetch.tensormap [%0];" :: "l"((uint64_t)tm_kv) : "memory");
            asm volatile("prefetch.tensormap [%0];" :: "l"((uint64_t)&tm_wq) : "memory");
            asm volatile("prefetch.tensormap [%0];" :: "l"((uint64_t)&tm_u) : "memory");
            mbar_init(bars + 8 * B_X, 1);
            mbar_init(bars + 8 * B_X + 8, 1);
            mbar_init(bars + 8 * B_U, 1);
            asm volatile("fence.mbarrier_init.release.cluster;" ::: "memory");
            mbar_expect_tx(bars + 8 * B_X, 65536u + (kv_cta ? 8192u : 0u));
            mbar_expect_tx(bars + 8 * B_X + 8, 65536u + (kv_cta ? 8192u : 0u));
            mbar_expect_tx(bars + 8 * B_U, 32768u);
        }
        __syncwarp();
        PROF3(6);
    }
    asm volatile("barrier.cluster.arrive.relaxed.aligned;" ::: "memory");
    const unsigned epoch = *(volatile unsigned*)&g_epoch + 1u;
    if (warp > 16) {
        if (lane == 0) {
            for (int i = warp - 17; i < B_X; i += 3) {
                mbar_init(bars + 8 * i, i >= B_H ? 2 : 1);
                if (i <= B_WQ2) mbar_expect_tx(bars + 8 * i, i < B_KV + 2 ? 16384u : i == B_KV + 2 ? 32768u : i <= B_WO ? 65536u : 32768u);
            }
            asm volatile("fence.mbarrier_init.release.cluster;" ::: "memory");
            fence_async_smem();
        } else if (warp == 19) {
            #pragma unroll
            for (int i = 0; i < 2; i++) if (lane - 1 + 31 * i < 41) asm volatile("prefetch.global.L2 [%0];" :: "l"((const char*)g_tabmap.v + (lane - 1 + 31 * i) * 128));
        }
        __syncwarp();
    }
    asm volatile("barrier.cluster.wait.aligned;" ::: "memory");
    PROF(5);
    if (warp == 16 && lane == 0) {
        tma_3d_mc(sb + (rank ? SM_A : SM_B), &tm_x, 0, qb * 128, rank * 4, bars + 8 * (B_X + rank));
        if (kv_cta) {
            #pragma unroll
            for (int i = 0; i < 4; i++) tma_2d(sb + SM_WKV + i * 4096, tm_kv, (i >> 1) * 8, (i & 1) * 256, bars + 8 * (B_X + (i & 1)));
        }
        mbar_init(bars + 8 * B_WQ, 1);
        asm volatile("fence.mbarrier_init.release.cluster;" ::: "memory");
        fence_async_smem();
        mbar_expect_tx(bars + 8 * B_WQ, 32768u);
        tma_2d(sb + SM_WQ, &tm_wq, hg * 64, 0, bars + 8 * B_WQ);
        #pragma unroll
        for (int i = 0; i < 4; i++) tma_2d_mc(sb + SM_SLAB + (rank * 4 + i) * 4096, &tm_u, (blockIdx.x >> 1) * 8, (rank * 4 + i) * 256, bars + 8 * B_U);
    }
    __syncwarp();
    asm volatile("barrier.cluster.arrive.relaxed.aligned;" ::: "memory");

    if (warp == 16) {
        if (lane == 0) asm volatile("prefetch.tensormap [%0];" :: "l"((uint64_t)&tm_wo) : "memory");
        asm volatile("barrier.cluster.wait.aligned;" ::: "memory");
        PROF3(10);
        bar_sync(13, 544);
        if (lane == 0) { fence_async_smem(); tma_2d(sb + SM_SLAB, &tm_wq, hg * 64, 256, bars + 8 * B_WQ2); }
        bar_sync(14, 544);
        if (lane == 0) pair_sync(bars + 8 * B_H, rank ^ 1);
        __syncwarp();
        PROF3(11);
        *(uint4*)(sp + SM_V + 32768 + lane * 32) = make_uint4(0x3F803F80u, 0x3F803F80u, 0x3F803F80u, 0x3F803F80u);
        *(uint4*)(sp + SM_V + 32768 + lane * 32 + 16) = make_uint4(0x3F803F80u, 0x3F803F80u, 0x3F803F80u, 0x3F803F80u);
        fence_async_smem();
        float km = wait_flag64(&g_flag_kv[2 * lane], epoch);
        float vm = wait_flag64(&g_flag_kv[2 * lane + 1], epoch);
        __syncwarp();
        PROF3(12);
        if (lane == 0) {
            fence_async_all();
            #pragma unroll
            for (int i = 0; i < 4; i++) {
                const uint32_t k0 = i == 0 ? 0 : 128u << i, nk = i == 0 ? 256 : 128u << i;
                const uint32_t bar = bars + 8 * (B_KV + i);
                if (rank == 0) bulk_g2s_mc(sb + SM_K + k0 * 32, g_kimg + k0 * 32, nk * 32, bar);
                else {
                    bulk_g2s_mc(sb + SM_V + k0 * 16, g_vimg + k0 * 16, nk * 16, bar);
                    bulk_g2s_mc(sb + SM_V + 66560 - (k0 + nk) * 16, g_vimg + 66560 - (k0 + nk) * 16, nk * 16, bar);
                }
            }
        }
        #pragma unroll
        for (int o = 16; o; o >>= 1) { km = fmaxf(km, __shfl_xor_sync(0xffffffffu, km, o)); vm = fmaxf(vm, __shfl_xor_sync(0xffffffffu, vm, o)); }
        if (lane == 0) { s_misc[16] = km; s_misc[17] = vm; mbar_arrive(bars + 8 * B_ST); }
        PROF3(13);
        bar_sync(11, 128);
        if (lane < 2) { fence_async_smem(); tma_2d(sb + SM_B + lane * 32768, &tm_wo, hg * 64, lane * 256, bars + 8 * B_WO); }
        bar_sync(12, 544);
        if (lane == 0) {
            st_release(&g_flag_o[blockIdx.x], epoch);
            pair_sync(bars + 8 * (B_H + 1), rank ^ 1);
        }
        __syncwarp();
        PROF3(14);
        if (lane < 4) {
            const int src = 2 * lane + rank;
            wait_flag(&g_flag_o[qb * 8 + src], epoch);
            fence_async_all();
            bulk_g2s_mc(sb + SM_A + src * 16384, g_oimg + qb * 131072 + src * 16384, 16384, bars + 8 * (B_O + src));
        }
        __syncwarp();
        PROF3(15);
        if (lane == 0) {
            const unsigned prev = atomicAdd(&g_done, 1u);
            if (prev == NCTA - 1) {
                g_done = 0;
                __threadfence();
                *(volatile unsigned*)&g_epoch = epoch;
            }
        }
    } else if (wg == 4) {
        helper_role(P, sp, sb, epoch);
    } else {
        uint8_t* sB = sp + SM_B;
        const uint32_t sBa = sb + SM_B;
        {
            const int c = wg;
            const float dt = bf_round(expf(bf_lo(p_ldt)));
            const float are = -bf_round(expf(bf_lo(p_lar))) * dt;
            const float aim = bf_lo(p_aim) * dt;
            float cr = 2.0f * (bf_lo(p_cre) * dt);
            float ci = 2.0f * (bf_lo(p_cim) * dt);
            const float a2 = are * 1.4426950408889634f, bb = aim * 0.15915494309189535f;
            float m = fmaxf(fabsf(cr), fabsf(ci));
            #pragma unroll
            for (int o = 16; o; o >>= 1) m = fmaxf(m, __shfl_xor_sync(0xffffffffu, m, o));
            int ebits = (__float_as_uint(m) >> 23) & 0xFF;
            ebits = min(max(ebits, 2), 250);
            const float scale = __uint_as_float((uint32_t)(ebits + 1) << 23);
            const float iscale = __uint_as_float((uint32_t)(253 - ebits) << 23);
            cf cc; cc.x = cr * iscale; cc.y = ci * iscale;

            const uint32_t stg = sBa + S_KC + warp * 1024;
            uint4* stp = (uint4*)(sB + S_KC + warp * 1024 + lane * 32);
            const uint32_t fa = stg + t * 32 + g * 4;

            uint32_t af[4][2][4];
            cf E256;
            {
                const cf E8 = cexp_p(a2, bb, 8.0f);
                uint32_t w[8];
                cf cur; cur.x = 1.0f; cur.y = 0.0f;
                w[0] = pack_f16(1.0f, 0.0f);
                cur = E8; w[1] = pack_f16(cur.x, cur.y);
                #pragma unroll
                for (int i = 2; i < 8; i++) { cur = cmul(cur, E8); w[i] = pack_f16(cur.x, cur.y); }
                stp[0] = make_uint4(w[0], w[1], w[2], w[3]);
                stp[1] = make_uint4(w[4], w[5], w[6], w[7]);
                const cf E64 = cexp_p(a2, bb, 64.0f);
                const cf E128 = cmul(E64, E64), E192 = cmul(E128, E64);
                E256 = cexp_p(a2, bb, 256.0f);
                const uint32_t e1 = pack_f16(E64.x, E64.y), e2 = pack_f16(E128.x, E128.y), e3 = pack_f16(E192.x, E192.y);
                __syncwarp();
                #pragma unroll
                for (int s = 0; s < 4; s++) {
                    #pragma unroll
                    for (int hh = 0; hh < 2; hh++) {
                        const uint32_t w0 = lds32(fa + s * 256 + hh * 128);
                        const uint32_t wsw = __byte_perm(w0, 0, 0x1032) ^ 0x00008000u;
                        const int src = 8 * s + t + 4 * hh;
                        const uint32_t f1 = __shfl_sync(0xffffffffu, e1, src), f2 = __shfl_sync(0xffffffffu, e2, src), f3 = __shfl_sync(0xffffffffu, e3, src);
                        af[s][0][2 * hh] = w0;
                        af[s][0][2 * hh + 1] = h2_cmul(w0, wsw, f1);
                        af[s][1][2 * hh] = h2_cmul(w0, wsw, f2);
                        af[s][1][2 * hh + 1] = h2_cmul(w0, wsw, f3);
                    }
                }
                __syncwarp();
            }
            float acc[2][3][4];
            #pragma unroll
            for (int i = 0; i < 24; i++) (&acc[0][0][0])[i] = 0.0f;
            const cf E1 = cexp_p(a2, bb, 1.0f);
            const cf E2 = cmul(E1, E1), E4 = cmul(E2, E2);
            cf X512;
            #pragma unroll
            for (int nt = 0; nt < 3; nt++) {
                uint32_t xv[8];
                if (nt == 0) {
                    cf cur = cc;
                    xv[0] = pack_f16(cur.x, -cur.y);
                    #pragma unroll
                    for (int i = 1; i < 8; i++) { cur = cmul(cur, E1); xv[i] = pack_f16(cur.x, -cur.y); }
                } else if (nt == 1) {
                    cf cur = cmul(cc, E256);
                    X512 = cmul(cur, E256);
                    xv[0] = pack_f16(cur.x, -cur.y);
                    #pragma unroll
                    for (int i = 1; i < 4; i++) { cur = cmul(cur, E2); xv[i] = pack_f16(cur.x, -cur.y); }
                    cur = cmul(X512, E4);
                    xv[4] = pack_f16(X512.x, -X512.y); xv[5] = pack_f16(cur.x, -cur.y);
                    X512 = cmul(X512, E256);
                    cur = cmul(X512, E4);
                    xv[6] = pack_f16(X512.x, -X512.y); xv[7] = pack_f16(cur.x, -cur.y);
                } else {
                    cf cur = X512;
                    #pragma unroll
                    for (int i = 0; i < 5; i++) { cur = cmul(cur, E256); xv[i] = pack_f16(cur.x, -cur.y); }
                    xv[5] = 0; xv[6] = 0; xv[7] = 0;
                }
                stp[0] = make_uint4(xv[0], xv[1], xv[2], xv[3]);
                stp[1] = make_uint4(xv[4], xv[5], xv[6], xv[7]);
                __syncwarp();
                #pragma unroll
                for (int s = 0; s < 4; s++) {
                    const uint32_t b0 = lds32(fa + s * 256), b1 = lds32(fa + s * 256 + 128);
                    mma_f16(acc[0][nt], af[s][0], b0, b1);
                    mma_f16(acc[1][nt], af[s][1], b0, b1);
                }
                __syncwarp();
            }
            float* kc = (float*)(sB + S_KC + c * 4096);
            bar_sync(4 + c, 128);
            #pragma unroll 1
            for (int step = 0; step < 4; step++) {
                if ((warp & 3) == step) {
                    #pragma unroll
                    for (int mt = 0; mt < 2; mt++)
                        #pragma unroll
                        for (int nt = 0; nt < 3; nt++)
                            #pragma unroll
                            for (int hh = 0; hh < 2; hh++) {
                                float2* p = (float2*)(kc + (mt * 16 + hh * 8 + g) * 24 + nt * 8 + 2 * t);
                                float2 v = make_float2(acc[mt][nt][2 * hh] * scale, acc[mt][nt][2 * hh + 1] * scale);
                                if (step) { float2 o = *p; v.x += o.x; v.y += o.y; }
                                *p = v;
                            }
                }
                if (step < 3) bar_sync(4 + c, 128);
            }
        }

        asm volatile("barrier.cluster.wait.aligned;" ::: "memory");
        PROF(4);
        uint32_t q[2][4];
        {
            float acc[16], akv[8];
            #pragma unroll
            for (int i = 0; i < 16; i++) acc[i] = 0.0f;
            #pragma unroll
            for (int i = 0; i < 8; i++) akv[i] = 0.0f;
            fence_regs<16>(acc);
            fence_regs<8>(akv);
            const uint64_t dA0 = make_desc(sb + SM_B + rowhalf * 8192, 16, 1024, 1);
            const uint64_t dA1 = make_desc(sb + SM_A + rowhalf * 8192, 16, 1024, 1) - 4096;
            const uint64_t dB = make_desc(sb + SM_WQ + nh * 64, 16, 1024, 1);
            const uint64_t dC = make_desc(sb + SM_WKV, 128, 8192, 0);
            if (kv_wg) {
                #pragma unroll 1
                for (int ch = 0; ch < 8; ch++) {
                    if ((ch & 3) == 0) mbar_wait(bars + 8 * (B_X + (ch >> 2)), 0);
                    const uint64_t dA = ch < 4 ? dA0 : dA1;
                    wg_fence();
                    #pragma unroll
                    for (int ks = 0; ks < 4; ks++) wg_ss16(akv, dA + ch * 1024 + ks * 2, dC + (ch * 4 + ks) * 16);
                    wg_commit();
                }
                wg_wait<0>();
            }
            fence_regs<8>(akv);
            if (kv_wg) {
                const int key = qb * 128 + rowhalf * 64 + wiw * 16 + g;
                uint32_t pk[4];
                #pragma unroll
                for (int i = 0; i < 4; i++) pk[i] = pack_bf16(akv[2 * i], akv[2 * i + 1]);
                float st;
                if (kv_sel == 0) {
                    uint8_t* b = g_kimg + (key >> 3) * 256 + (key & 7) * 16 + 4 * t;
                    *(uint32_t*)(b) = pk[0]; *(uint32_t*)(b + 256) = pk[1]; *(uint32_t*)(b + 128) = pk[2]; *(uint32_t*)(b + 384) = pk[3];
                    float n0 = bf_lo(pk[0]) * bf_lo(pk[0]) + bf_hi(pk[0]) * bf_hi(pk[0]) + bf_lo(pk[2]) * bf_lo(pk[2]) + bf_hi(pk[2]) * bf_hi(pk[2]);
                    float n1 = bf_lo(pk[1]) * bf_lo(pk[1]) + bf_hi(pk[1]) * bf_hi(pk[1]) + bf_lo(pk[3]) * bf_lo(pk[3]) + bf_hi(pk[3]) * bf_hi(pk[3]);
                    n0 += __shfl_xor_sync(0xffffffffu, n0, 1); n0 += __shfl_xor_sync(0xffffffffu, n0, 2);
                    n1 += __shfl_xor_sync(0xffffffffu, n1, 1); n1 += __shfl_xor_sync(0xffffffffu, n1, 2);
                    st = (n0 != n0 || n1 != n1) ? __int_as_float(0x7f800000) : fmaxf(n0, n1);
                } else {
                    uint8_t* lo = g_vimg + key * 16 + 4 * t;
                    uint8_t* hi = g_vimg + 33792 + (31 - (key >> 6)) * 1024 + (key & 63) * 16 + 4 * t;
                    *(uint32_t*)(lo) = pk[0]; *(uint32_t*)(lo + 128) = pk[1]; *(uint32_t*)(hi) = pk[2]; *(uint32_t*)(hi + 128) = pk[3];
                    st = 0.0f;
                    #pragma unroll
                    for (int i = 0; i < 4; i++) {
                        float a = fabsf(bf_lo(pk[i])), b = fabsf(bf_hi(pk[i]));
                        st = (a != a || b != b) ? __int_as_float(0x7f800000) : fmaxf(st, fmaxf(a, b));
                    }
                }
                #pragma unroll
                for (int o = 16; o; o >>= 1) st = fmaxf(st, __shfl_xor_sync(0xffffffffu, st, o));
                if (lane == 0) s_misc[20 + wiw] = st;
                bar_arrive(3, 160);
            }
            uint2 mp[6];
            #pragma unroll
            for (int i = 0; i < 6; i++) { const int w = (tid & 127) + 128 * i; mp[i] = (w < TABN / 4) ? __ldg((const uint2*)g_tabmap.v + w) : make_uint2(0u, 0u); }
            mbar_wait(bars + 8 * B_WQ, 0);
            mbar_wait(bars + 8 * B_X, 0);
            PROF(2);
            #pragma unroll 1
            for (int ch = 0; ch < 4; ch++) {
                wg_fence();
                #pragma unroll
                for (int ks = 0; ks < 4; ks++) wg_ss32(acc, dA0 + ch * 1024 + ks * 2, dB + (ch * 4 + ks) * 128);
                wg_commit();
            }
            wg_wait<0>();
            fence_regs<16>(acc);
            bar_sync(1, 512);
            PROF(15);
            #pragma unroll
            for (int i = 0; i < 2; i++) {
                const int z = tid + 512 * i;
                if (z < 4 * 144) sts128(sBa + S_U + (z / 144) * ULEN * 2 + (PADU - 1152) * 2 + (z % 144) * 16, make_uint4(0, 0, 0, 0));
            }
            PROF(8);
            mbar_wait(bars + 8 * B_U, 0);
            PROF(14);
            #pragma unroll
            for (int i = 0; i < 2; i++) {
                const int l = 2 * (tid + 512 * i);
                const uint2 r0 = *(const uint2*)(sp + SM_SLAB + l * 16 + rank * 8), r1 = *(const uint2*)(sp + SM_SLAB + l * 16 + 16 + rank * 8);
                const uint32_t dst = swz128(sBa + S_U + (PADU + l) * 2);
                sts32(dst, __byte_perm(r0.x, r1.x, 0x5410));
                sts32(dst + ULEN * 2, __byte_perm(r0.x, r1.x, 0x7632));
                sts32(dst + ULEN * 4, __byte_perm(r0.y, r1.y, 0x5410));
                sts32(dst + ULEN * 6, __byte_perm(r0.y, r1.y, 0x7632));
            }
            bar_arrive(13, 544);
            {
                const float* kc = (const float*)(sB + S_KC + wg * 4096);
                uint2* tab = (uint2*)(sB + S_TAB + wg * TABN * 2);
                #pragma unroll
                for (int i = 0; i < 6; i++) {
                    const int w = (tid & 127) + 128 * i;
                    if (w < TABN / 4) tab[w] = make_uint2(pack_bf16(kc[mp[i].x & 0xFFFF], kc[mp[i].x >> 16]), pack_bf16(kc[mp[i].y & 0xFFFF], kc[mp[i].y >> 16]));
                }
            }
            fence_async_smem();
            bar_sync(1, 512);
            PROF(1);
            mbar_wait(bars + 8 * B_WQ2, 0);
            mbar_wait(bars + 8 * (B_X + 1), 0);
            fence_regs<16>(acc);
            wg_fence();
            #pragma unroll
            for (int ks = 16; ks < 32; ks++) wg_ss32(acc, dA1 + (ks >> 2) * 1024 + (ks & 3) * 2, dB + ks * 128);
            wg_commit();
            {
                const int task = tid + (tid < 8 ? 512 : 0) * 0;
                #pragma unroll 1
                for (int tk = task; tk < 4 * 130; tk += 512) {
                    const int c = tk / 130, i = tk % 130;
                    const uint32_t src = sBa + S_U + c * ULEN * 2 + (PADU + 8 * i - WPAD - 8) * 2;
                    const uint4 v0 = lds128(swz128(src)), v1 = lds128(swz128(src + 16)), v2 = lds128(swz128(src + 32));
                    float x[16];
                    const uint32_t vv[8] = {v0.z, v0.w, v1.x, v1.y, v1.z, v1.w, v2.x, v2.y};
                    #pragma unroll
                    for (int k = 0; k < 8; k++) { x[2 * k] = bf_lo(vv[k]); x[2 * k + 1] = bf_hi(vv[k]); }
                    float p2[15], w7[8], w9[8];
                    #pragma unroll
                    for (int e = 0; e < 15; e++) p2[e] = x[e] + x[e + 1];
                    #pragma unroll
                    for (int e = 0; e < 8; e++) {
                        w7[e] = (p2[e + 1] + p2[e + 3]) + (p2[e + 5] + x[e + 7]);
                        w9[e] = w7[e] + (x[e] + x[e + 8]);
                    }
                    sts128(swz(sBa + S_W7 + c * W3LEN * 2 + i * 16), make_uint4(pack_bf16(w7[0], w7[1]), pack_bf16(w7[2], w7[3]), pack_bf16(w7[4], w7[5]), pack_bf16(w7[6], w7[7])));
                    sts128(swz(sBa + S_W9 + c * W3LEN * 2 + i * 16), make_uint4(pack_bf16(w9[0], w9[1]), pack_bf16(w9[2], w9[3]), pack_bf16(w9[4], w9[5]), pack_bf16(w9[6], w9[7])));
                }
            }
            wg_wait<0>();
            fence_regs<16>(acc);
            bar_arrive(14, 544);
            const float QS = 0.25f * 1.4426950408889634f;
            float qm = 0.0f;
            #pragma unroll
            for (int i = 0; i < 2; i++) {
                #pragma unroll
                for (int j = 0; j < 4; j++) q[i][j] = pack_bf16(acc[8 * i + 2 * j] * QS, acc[8 * i + 2 * j + 1] * QS);
                float n0 = bf_lo(q[i][0]) * bf_lo(q[i][0]) + bf_hi(q[i][0]) * bf_hi(q[i][0]) + bf_lo(q[i][2]) * bf_lo(q[i][2]) + bf_hi(q[i][2]) * bf_hi(q[i][2]);
                float n1 = bf_lo(q[i][1]) * bf_lo(q[i][1]) + bf_hi(q[i][1]) * bf_hi(q[i][1]) + bf_lo(q[i][3]) * bf_lo(q[i][3]) + bf_hi(q[i][3]) * bf_hi(q[i][3]);
                n0 += __shfl_xor_sync(0xffffffffu, n0, 1); n0 += __shfl_xor_sync(0xffffffffu, n0, 2);
                n1 += __shfl_xor_sync(0xffffffffu, n1, 1); n1 += __shfl_xor_sync(0xffffffffu, n1, 2);
                qm = (n0 != n0 || n1 != n1) ? __int_as_float(0x7f800000) : fmaxf(qm, fmaxf(n0, n1));
            }
            #pragma unroll
            for (int o = 16; o; o >>= 1) qm = fmaxf(qm, __shfl_xor_sync(0xffffffffu, qm, o));
            if (lane == 0) s_misc[warp] = qm;
        }
        PROF(3);
        {
            const int c = wg;
            uint32_t sBl = sBa;
            asm volatile("" : "+r"(sBl) :: "memory");
            float acc[16];
            #pragma unroll
            for (int i = 0; i < 16; i++) acc[i] = 0.0f;
            fence_regs<16>(acc);
            const uint32_t tabc = sBl + S_TAB + c * TABN * 2;
            const uint32_t tD = tabc + ((g & 1) ? (TD1 + CD + 1) : (TD0 + CD)) * 2 - (g - 2 * t) * 2 - 32 * wiw;
            const uint32_t uLo = (((sBl + S_U + c * ULEN * 2 + PADU * 2) & 0x3FFFF) >> 4) | (1u << 16);
            uint32_t A[2][4][4];
            auto load_set = [&](uint32_t (&X)[4][4], int m0) {
                asm volatile("{ .reg .pred p; setp.lt.u32 p, %2, 66; mov.b32 %0, 0; @p ld.shared.u32 %0, [%1]; }"
                             : "=r"(X[0][2]) : "r"(tD - 32 * m0 + 16), "r"(m0 + wiw) : "memory");
                #pragma unroll
                for (int i = 0; i < 4; i++) {
                    asm volatile("{ .reg .pred p; setp.lt.u32 p, %3, 66; mov.b32 %0, 0; mov.b32 %1, 0; @p ld.shared.u32 %0, [%2]; @p ld.shared.u32 %1, [%2+-16]; }"
                                 : "=r"(X[i][0]), "=r"(X[i][1]) : "r"(tD - 32 * (m0 + i)), "r"(m0 + i + wiw) : "memory");
                }
                #pragma unroll
                for (int i = 0; i < 4; i++) {
                    asm volatile("mov.b32 %0, %1;" : "=r"(X[i][3]) : "r"(X[i][0]));
                    if (i < 3) asm volatile("mov.b32 %0, %1;" : "=r"(X[i + 1][2]) : "r"(X[i][1]));
                }
            };
            #pragma unroll 1
            for (int m0 = -3; m0 < 69; m0 += 8) {
                #pragma unroll
                for (int h = 0; h < 2; h++) {
                    load_set(A[h], m0 + 4 * h);
                    wg_fence();
                    #pragma unroll
                    for (int i = 0; i < 4; i++) wg_rs32(acc, A[h][i], uLo - 2 * (m0 + 4 * h + i));
                    wg_commit();
                    wg_wait<1>();
                }
            }
            bar_sync(1, 512);
            wg_wait<0>();
            fence_regs<16>(acc);
            PROF(6);
            {
                asm volatile("" : "+r"(sBl) :: "memory");
                const int mi = lane >> 3, r8 = lane & 7;
                const uint32_t frag = (16 * (8 * (mi >> 1) + r8) + 8 * (mi & 1)) * 2;
                const uint32_t t3 = sBl + S_TAB + c * TABN * 2 + (T3B + ((wiw & 1) ? (T3C + C3 + 1) : C3)) * 2 - (4 * g + wiw - 2 * t) * 2;
                #pragma unroll
                for (int s = 0; s < 2; s++) {
                    const uint32_t sig = swz(sBl + (s ? S_W7 : S_W9) + c * W3LEN * 2 + WPAD * 2 + frag - (s ? 16 : 32));
                    uint32_t a[4][4], R[4][2];
                    #pragma unroll
                    for (int b = 0; b < 4; b++) ldsm4t_p(a[b], sig + b * 512);
                    #pragma unroll
                    for (int i = 0; i < 4; i++) { R[i][0] = lds32_p(t3 + s * (T3S * 2) - 2 * (48 + 16 * i)); R[i][1] = lds32_p(t3 + s * (T3S * 2) - 2 * (40 + 16 * i)); }
                    #pragma unroll
                    for (int b = 0; b < 4; b++) {
                        mma_bf16_p(acc + 12, a[b][0], a[b][1], a[b][2], a[b][3], R[3 - b][0], R[3 - b][1]);
                        if (b < 2) mma_bf16_p(acc + 8, a[b][0], a[b][1], a[b][2], a[b][3], R[1 - b][0], R[1 - b][1]);
                    }
                }
            }
            __nv_bfloat16* ys = (__nv_bfloat16*)(sB + S_Y + c * 4096) + 128 * t + 16 * wiw + g;
            #pragma unroll
            for (int j = 0; j < 4; j++) {
                ys[512 * j] = __float2bfloat16_rn(acc[4 * j]);
                ys[512 * j + 64] = __float2bfloat16_rn(acc[4 * j + 1]);
                ys[512 * j + 8] = __float2bfloat16_rn(acc[4 * j + 2]);
                ys[512 * j + 72] = __float2bfloat16_rn(acc[4 * j + 3]);
            }
        }
        bar_arrive(10, 608);
        PROF(7);
        {
            mbar_wait(bars + 8 * B_ST, 0);
            PROF(9); PROFC(8);
            float qm = 0.0f;
            #pragma unroll
            for (int i = 0; i < 16; i++) qm = fmaxf(qm, s_misc[i]);
            const float vm = s_misc[17];
            const bool fast = (qm * s_misc[16] <= 60.0f * 60.0f) && (vm <= 1.0e12f) && (vm >= 1.0e-12f || vm == 0.0f);
            uint8_t* ob = g_oimg + qb * 131072 + hg * 16384 + nh * 8192 + (rowhalf * 8 + wiw * 2) * 128 + g * 16 + 4 * t;
            uint32_t cA = 0xBF00BF00u, cB = 0x00030003u;
            asm volatile("" : "+r"(cA), "+r"(cB));
            #pragma unroll 1
            for (int tile = 0; tile < 2; tile++) {
                uint32_t kLo = (((sb + SM_K) & 0x3FFFF) >> 4) | (8u << 16), vLo = (((sb + SM_V) & 0x3FFFF) >> 4) | (8u << 16), vHi = 2048;
                float o[12], s[32];
                uint32_t p[16], qq[4];
                #pragma unroll
                for (int i = 0; i < 4; i++) { qq[i] = tile ? q[1][i] : q[0][i]; asm volatile("" : "+r"(qq[i])); }
                #pragma unroll
                for (int i = 0; i < 12; i++) o[i] = 0.0f;
                #pragma unroll
                for (int i = 0; i < 32; i++) s[i] = 0.0f;
                fence_regs<12>(o);
                fence_regs<32>(s);
                if (fast) {
                    #pragma unroll 1
                    for (int c = 0; c < SEQ / 256; c++) {
                        if (c <= 4) mbar_wait(bars + 8 * (B_KV + (c < 2 ? c : c < 4 ? 2 : 3)), 0);
                        wg_fence();
                        wg_qk(s, qq, kLo);
                        wg_commit();
                        #pragma unroll
                        for (int u = 0; u < 4; u++) {
                            wg_wait<0>();
                            fence_regs<32>(s);
                            #pragma unroll
                            for (int i = 0; i < 16; i++) {
                                if ((MUFU_MASK >> i) & 1) p[i] = exp_mufu(s[2 * i], s[2 * i + 1]);
                                else p[i] = exp_sw(s[2 * i], s[2 * i + 1], cA, cB);
                            }
                            wg_fence();
                            if (u + 1 < 4) wg_qk(s, qq, kLo + (u + 1) * 128);
                            #pragma unroll
                            for (int kk = 0; kk < 4; kk++) wg_pv(o, p + 4 * kk, vLo + u * 64 + kk * 16, vHi - u * 64);
                            wg_commit();
                        }
                        kLo += 512; vLo += 256; vHi -= 256;
                    }
                    wg_wait<0>();
                } else {
                    float mx0 = -INFINITY, mx1 = -INFINITY;
                    #pragma unroll 1
                    for (int c = 0; c < SEQ / 64; c++) {
                        if (c <= 16) mbar_wait(bars + 8 * (B_KV + (c < 8 ? (c >> 2) : c < 16 ? 2 : 3)), 0);
                        wg_fence();
                        wg_qk(s, qq, kLo);
                        wg_commit();
                        wg_wait<0>();
                        fence_regs<32>(s);
                        fence_regs<12>(o);
                        float m0 = mx0, m1 = mx1;
                        #pragma unroll
                        for (int j = 0; j < 8; j++) {
                            m0 = fmaxf(m0, fmaxf(s[4 * j], s[4 * j + 1]));
                            m1 = fmaxf(m1, fmaxf(s[4 * j + 2], s[4 * j + 3]));
                        }
                        m0 = fmaxf(m0, __shfl_xor_sync(0xffffffffu, m0, 1)); m0 = fmaxf(m0, __shfl_xor_sync(0xffffffffu, m0, 2));
                        m1 = fmaxf(m1, __shfl_xor_sync(0xffffffffu, m1, 1)); m1 = fmaxf(m1, __shfl_xor_sync(0xffffffffu, m1, 2));
                        const float c0 = ex2f(mx0 - m0), c1 = ex2f(mx1 - m1);
                        mx0 = m0; mx1 = m1;
                        #pragma unroll
                        for (int j = 0; j < 3; j++) { o[4 * j] *= c0; o[4 * j + 1] *= c0; o[4 * j + 2] *= c1; o[4 * j + 3] *= c1; }
                        #pragma unroll
                        for (int j = 0; j < 8; j++) {
                            p[2 * j] = exp_mufu(s[4 * j] - m0, s[4 * j + 1] - m0);
                            p[2 * j + 1] = exp_mufu(s[4 * j + 2] - m1, s[4 * j + 3] - m1);
                        }
                        wg_fence();
                        #pragma unroll
                        for (int kk = 0; kk < 4; kk++) wg_pv(o, p + 4 * kk, vLo + kk * 16, vHi);
                        wg_commit();
                        wg_wait<0>();
                        kLo += 128; vLo += 64; vHi -= 64;
                    }
                }
                fence_regs<12>(o);
                if (tile == 0) PROFC(3);
                const float i0 = 1.0f / o[4], i1 = 1.0f / o[6];
                uint8_t* b = ob + tile * 4096;
                *(uint32_t*)(b) = pack_bf16(o[0] * i0, o[1] * i0);
                *(uint32_t*)(b + 128) = pack_bf16(o[2] * i1, o[3] * i1);
                *(uint32_t*)(b + 2048) = pack_bf16(o[8] * i0, o[9] * i0);
                *(uint32_t*)(b + 2048 + 128) = pack_bf16(o[10] * i1, o[11] * i1);
            }
        }
        PROF(10); PROFC(9);
        bar_arrive(12, 544);

        {
            float acc[16];
            #pragma unroll
            for (int i = 0; i < 16; i++) acc[i] = 0.0f;
            fence_regs<16>(acc);
            const uint64_t dA = make_desc(sb + SM_A + rowhalf * 1024, 2048, 128, 0);
            const uint64_t dB = make_desc(sb + SM_B + nh * 64, 16, 1024, 1);
            mbar_wait(bars + 8 * B_WO, 0);
            #pragma unroll 1
            for (int i = 0; i < 8; i++) {
                const int src = (hg + i) & 7;
                mbar_wait(bars + 8 * (B_O + src), 0);
                wg_fence();
                #pragma unroll
                for (int kk = 0; kk < 4; kk++) wg_ss32(acc, dA + src * 1024 + kk * 256, dB + (src * 4 + kk) * 128);
                wg_commit();
            }
            wg_wait<0>();
            fence_regs<16>(acc);
            PROF(12);
            const int row = qb * 128 + rowhalf * 64 + wiw * 16 + g;
            uint32_t* o32 = (uint32_t*)(P.out + (size_t)row * 1024 + hg * 64 + nh * 32 + 2 * t);
            #pragma unroll
            for (int j = 0; j < 4; j++) {
                o32[4 * j] = pack_bf16(acc[4 * j], acc[4 * j + 1]);
                o32[4 * j + 8 * 512] = pack_bf16(acc[4 * j + 2], acc[4 * j + 3]);
            }
        }
        PROF(13);
    }
}

typedef CUresult (*EncodeFn)(CUtensorMap*, CUtensorMapDataType, cuuint32_t, void*, const cuuint64_t*, const cuuint64_t*,
                             const cuuint32_t*, const cuuint32_t*, CUtensorMapInterleave, CUtensorMapSwizzle,
                             CUtensorMapL2promotion, CUtensorMapFloatOOBfill);

void make_map(EncodeFn fn, CUtensorMap* m, const void* ptr, uint64_t inner, uint64_t outer, uint32_t box_in, uint32_t box_out, CUtensorMapSwizzle swz) {
    cuuint64_t dims[2] = {inner, outer};
    cuuint64_t strides[1] = {inner * 2};
    cuuint32_t box[2] = {box_in, box_out};
    cuuint32_t es[2] = {1, 1};
    fn(m, CU_TENSOR_MAP_DATA_TYPE_BFLOAT16, 2, const_cast<void*>(ptr), dims, strides, box, es, CU_TENSOR_MAP_INTERLEAVE_NONE, swz,
       CU_TENSOR_MAP_L2_PROMOTION_L2_128B, CU_TENSOR_MAP_FLOAT_OOB_FILL_NONE);
}

}

extern "C" void kernel_launch(void* const* d_in, const int* in_sizes, int n_in, void* d_out, int out_size) {
    (void)in_sizes; (void)n_in; (void)out_size;
    static EncodeFn fn = nullptr;
    if (!fn) {
        void* p = nullptr;
        cudaDriverEntryPointQueryResult qr;
        cudaGetDriverEntryPoint("cuTensorMapEncodeTiled", &p, cudaEnableDefault, &qr);
        fn = (EncodeFn)p;
        cudaFuncSetAttribute(fused_kernel, cudaFuncAttributeMaxDynamicSharedMemorySize, SM_ALLOC);
    }
    CUtensorMap tx, twq, two, twk, twv, tu;
    {
        cuuint64_t dims[3] = {64, 2048, 8};
        cuuint64_t strides[2] = {1024, 128};
        cuuint32_t box[3] = {64, 128, 4};
        cuuint32_t es[3] = {1, 1, 1};
        fn(&tx, CU_TENSOR_MAP_DATA_TYPE_BFLOAT16, 3, d_in[0], dims, strides, box, es, CU_TENSOR_MAP_INTERLEAVE_NONE, CU_TENSOR_MAP_SWIZZLE_128B,
           CU_TENSOR_MAP_L2_PROMOTION_L2_128B, CU_TENSOR_MAP_FLOAT_OOB_FILL_NONE);
    }
    make_map(fn, &tu, d_in[5], 512, 2048, 8, 256, CU_TENSOR_MAP_SWIZZLE_NONE);
    make_map(fn, &twq, d_in[1], 512, 512, 64, 256, CU_TENSOR_MAP_SWIZZLE_128B);
    make_map(fn, &twk, d_in[2], 16, 512, 8, 256, CU_TENSOR_MAP_SWIZZLE_NONE);
    make_map(fn, &twv, d_in[3], 16, 512, 8, 256, CU_TENSOR_MAP_SWIZZLE_NONE);
    make_map(fn, &two, d_in[4], 512, 512, 64, 256, CU_TENSOR_MAP_SWIZZLE_128B);
    Params P;
    P.u = (const __nv_bfloat16*)d_in[5];
    P.lar = (const __nv_bfloat16*)d_in[6];
    P.aim = (const __nv_bfloat16*)d_in[7];
    P.cre = (const __nv_bfloat16*)d_in[8];
    P.cim = (const __nv_bfloat16*)d_in[9];
    P.logdt = (const __nv_bfloat16*)d_in[10];
    P.dskip = (const __nv_bfloat16*)d_in[11];
    P.out = (__nv_bfloat16*)d_out;
    fused_kernel<<<NCTA, NTHR, SM_ALLOC>>>(tx, twq, two, twk, twv, tu, P);
}
```

```cpp
#include <cuda_runtime.h>
#include <cuda_bf16.h>
#include <cuda_fp16.h>
#include <cuda.h>
#include <stdint.h>

namespace {

constexpr int SEQ = 2048;
constexpr int NCTA = 128, NTHR = 640;

constexpr int SM_A = 0;
constexpr int SM_WQ = 65536;
constexpr int SM_SLAB = SM_WQ + 32768;
constexpr int SM_K = 0, SM_V = 65536;
constexpr int SM_B = 132096;
constexpr int SM_WKV = SM_B + 65536;

constexpr int PADU = 1536, ULEN = PADU + 2048;
constexpr int WPAD = 16, W3LEN = WPAD + 1024;
constexpr int TABN = 2592;
constexpr int S_U = 0;
constexpr int S_W7 = S_U + 4 * ULEN * 2;
constexpr int S_W9 = S_W7 + 4 * W3LEN * 2;
constexpr int S_TAB = S_W9 + 4 * W3LEN * 2;
constexpr int S_KC = 214016 - SM_B;
constexpr int S_Y = S_KC;
constexpr int SM_BAR = SM_B + S_KC + 16384;
constexpr int SM_TOTAL = SM_BAR + 1024;
constexpr int SM_ALLOC = SM_TOTAL + 1024;
static_assert(SM_V + 65536 + 1024 <= SM_B && SM_ALLOC <= 232448 && S_TAB + 4 * TABN * 2 <= S_KC && SM_WKV + 16384 <= SM_B + S_KC, "smem map");

constexpr int TD0 = 0, TD1 = 1072, CD = 1056;
constexpr int T3B = 2144, T3S = 224, T3C = 112, C3 = 136;

constexpr int rne8(int t) {
    if (t < 256) return t;
    int sh = 0;
    while ((t >> sh) >= 256) sh++;
    int q = t >> sh, rem = t & ((1 << sh) - 1), half = 1 << (sh - 1);
    if (rem > half || (rem == half && (q & 1))) q++;
    return q << sh;
}
constexpr int kcidx(int p) {
    if (p < 256) return (p >> 3) * 24 + (p & 7);
    if (p < 512) return ((p - 256) >> 3) * 24 + 8 + (((p - 256) & 7) >> 1);
    if (p < 1024) { int q = p - 512, hi = q >> 8, rem = q & 255; return (rem >> 3) * 24 + 12 + 2 * hi + ((rem & 7) >> 2); }
    if (p < 2048) { int q = p - 1024; return ((q & 255) >> 3) * 24 + 16 + (q >> 8); }
    return 20;
}
constexpr int KC_ZERO = 23;
constexpr int tab_dense(int t) { return (t >= 0 && t <= 1028) ? kcidx(rne8(t)) : KC_ZERO; }
constexpr int tab_3(int s, int lag) { return (lag >= 64 && lag <= 127) ? kcidx(s == 0 ? 16 * (lag + 1) : 16 * lag + 8) : KC_ZERO; }
struct TabMap {
    uint16_t v[TABN];
    constexpr TabMap() : v{} {
        for (int i = 0; i < TD1; i++) { v[TD0 + i] = tab_dense(CD - i); v[TD1 + i] = tab_dense(CD + 1 - i); }
        for (int s = 0; s < 2; s++)
            for (int i = 0; i < T3C; i++) { v[T3B + s * T3S + i] = tab_3(s, C3 - i); v[T3B + s * T3S + T3C + i] = tab_3(s, C3 + 1 - i); }
    }
};
__device__ const __align__(16) TabMap g_tabmap = TabMap();

__device__ __align__(1024) uint8_t g_kimg[65536];
__device__ __align__(1024) uint8_t g_vimg[65536 + 1024];
__device__ __align__(1024) uint8_t g_oimg[16 * 131072];
__device__ unsigned long long g_flag_kv[64];
__device__ unsigned g_flag_o[128];
__device__ unsigned g_epoch;
__device__ unsigned g_done;

#define PROF(i) do {} while (0)
#define PROF2(i) do {} while (0)
#define PROFC(i) do {} while (0)
#define PROF3(i) do {} while (0)

__device__ __forceinline__ uint32_t smem_u32(const void* p) { return (uint32_t)__cvta_generic_to_shared(p); }
__device__ __forceinline__ void mbar_init(uint32_t bar, uint32_t cnt) { asm volatile("mbarrier.init.shared::cta.b64 [%0], %1;" :: "r"(bar), "r"(cnt) : "memory"); }
__device__ __forceinline__ void mbar_expect_tx(uint32_t bar, uint32_t bytes) {
    asm volatile("mbarrier.arrive.expect_tx.shared::cta.b64 _, [%0], %1;" :: "r"(bar), "r"(bytes) : "memory"); }
__device__ __forceinline__ void mbar_wait(uint32_t bar, uint32_t parity) {
    uint32_t ok = 0;
    for (int it = 0; it < (1 << 22) && !ok; it++) {
        asm volatile("{ .reg .pred p; mbarrier.try_wait.parity.shared::cta.b64 p, [%1], %2; selp.u32 %0, 1, 0, p; }"
                     : "=r"(ok) : "r"(bar), "r"(parity) : "memory");
    }
}
__device__ __forceinline__ void tma_2d(uint32_t dst, const CUtensorMap* map, int c0, int c1, uint32_t bar) {
    asm volatile("cp.async.bulk.tensor.2d.shared::cluster.global.mbarrier::complete_tx::bytes [%0], [%1, {%3, %4}], [%2];"
                 :: "r"(dst), "l"((uint64_t)map), "r"(bar), "r"(c0), "r"(c1) : "memory");
}
__device__ __forceinline__ void tma_2d_mc(uint32_t dst, const CUtensorMap* map, int c0, int c1, uint32_t bar) {
    asm volatile("cp.async.bulk.tensor.2d.shared::cluster.global.mbarrier::complete_tx::bytes.multicast::cluster [%0], [%1, {%3, %4}], [%2], %5;"
                 :: "r"(dst), "l"((uint64_t)map), "r"(bar), "r"(c0), "r"(c1), "h"((uint16_t)3) : "memory");
}
__device__ __forceinline__ void bulk_g2s_mc(uint32_t dst, const void* src, uint32_t bytes, uint32_t bar) {
    asm volatile("cp.async.bulk.shared::cluster.global.mbarrier::complete_tx::bytes.multicast::cluster [%0], [%1], %2, [%3], %4;"
                 :: "r"(dst), "l"((uint64_t)src), "r"(bytes), "r"(bar), "h"((uint16_t)3) : "memory");
}
__device__ __forceinline__ void pair_sync(uint32_t bar, uint32_t peer) {
    uint32_t ra;
    asm volatile("mapa.shared::cluster.u32 %0, %1, %2;" : "=r"(ra) : "r"(bar), "r"(peer));
    asm volatile("mbarrier.arrive.shared::cluster.b64 _, [%0];" :: "r"(ra) : "memory");
    asm volatile("mbarrier.arrive.shared::cta.b64 _, [%0];" :: "r"(bar) : "memory");
    uint32_t ok = 0;
    for (int it = 0; it < (1 << 22) && !ok; it++) {
        asm volatile("{ .reg .pred p; mbarrier.try_wait.parity.shared::cta.b64 p, [%1], 0; selp.u32 %0, 1, 0, p; }"
                     : "=r"(ok) : "r"(bar) : "memory");
    }
}
__device__ __forceinline__ void fence_async_all() { asm volatile("fence.proxy.async.global;" ::: "memory"); }
__device__ __forceinline__ void fence_async_smem() { asm volatile("fence.proxy.async.shared::cta;" ::: "memory"); }
__device__ __forceinline__ unsigned ld_acquire(const unsigned* p) {
    unsigned v; asm volatile("ld.acquire.gpu.global.u32 %0, [%1];" : "=r"(v) : "l"(p) : "memory"); return v; }
__device__ __forceinline__ void st_release(unsigned* p, unsigned v) { asm volatile("st.release.gpu.global.u32 [%0], %1;" :: "l"(p), "r"(v) : "memory"); }
__device__ __forceinline__ void wait_flag(const unsigned* p, unsigned epoch) {
    for (int it = 0; it < (1 << 22); it++) { if (ld_acquire(p) == epoch) break; }
}
__device__ __forceinline__ unsigned long long ld_acquire64(const unsigned long long* p) {
    unsigned long long v; asm volatile("ld.acquire.gpu.global.u64 %0, [%1];" : "=l"(v) : "l"(p) : "memory"); return v; }
__device__ __forceinline__ void st_release64(unsigned long long* p, unsigned long long v) { asm volatile("st.release.gpu.global.u64 [%0], %1;" :: "l"(p), "l"(v) : "memory"); }
__device__ __forceinline__ float wait_flag64(const unsigned long long* p, unsigned epoch) {
    unsigned long long v = 0;
    for (int it = 0; it < (1 << 22); it++) { v = ld_acquire64(p); if ((unsigned)(v >> 32) == epoch) break; }
    return __uint_as_float((unsigned)v);
}
__device__ __forceinline__ void tma_3d_mc(uint32_t dst, const CUtensorMap* map, int c0, int c1, int c2, uint32_t bar) {
    asm volatile("cp.async.bulk.tensor.3d.shared::cluster.global.mbarrier::complete_tx::bytes.multicast::cluster [%0], [%1, {%3, %4, %5}], [%2], %6;"
                 :: "r"(dst), "l"((uint64_t)map), "r"(bar), "r"(c0), "r"(c1), "r"(c2), "h"((uint16_t)3) : "memory");
}
__device__ __forceinline__ void bar_sync(int id, int n) { asm volatile("bar.sync %0, %1;" :: "r"(id), "r"(n) : "memory"); }
__device__ __forceinline__ void bar_arrive(int id, int n) { asm volatile("bar.arrive %0, %1;" :: "r"(id), "r"(n) : "memory"); }
__device__ __forceinline__ void mbar_arrive(uint32_t bar) { asm volatile("mbarrier.arrive.shared::cta.b64 _, [%0];" :: "r"(bar) : "memory"); }

__device__ __forceinline__ uint64_t make_desc(uint32_t saddr, uint32_t lbo, uint32_t sbo, uint32_t swz) {
    uint64_t d = 0;
    d |= (uint64_t)((saddr & 0x3FFFF) >> 4);
    d |= (uint64_t)((lbo >> 4) & 0x3FFF) << 16;
    d |= (uint64_t)((sbo >> 4) & 0x3FFF) << 32;
    d |= (uint64_t)swz << 62;
    return d;
}
__device__ __forceinline__ void wg_fence() { asm volatile("wgmma.fence.sync.aligned;" ::: "memory"); }
__device__ __forceinline__ void wg_commit() { asm volatile("wgmma.commit_group.sync.aligned;" ::: "memory"); }
template<int N> __device__ __forceinline__ void wg_wait() { asm volatile("wgmma.wait_group.sync.aligned %0;" :: "n"(N) : "memory"); }
#define A4(d, o) "+f"(d[o + 0]), "+f"(d[o + 1]), "+f"(d[o + 2]), "+f"(d[o + 3])
#define A16(d, o) A4(d, o), A4(d, o + 4), A4(d, o + 8), A4(d, o + 12)

__device__ __forceinline__ void wg_pv(float* d, const uint32_t* a, uint32_t lo, uint32_t hi) {
    asm volatile("{ .reg .b64 dd; mov.b64 dd, {%16, %17};\n"
                 "wgmma.mma_async.sync.aligned.m64n24k16.f32.bf16.bf16 {%0,%1,%2,%3,%4,%5,%6,%7,%8,%9,%10,%11}, {%12,%13,%14,%15}, dd, 1, 1, 1, 1; }"
                 : A4(d, 0), A4(d, 4), A4(d, 8) : "r"(a[0]), "r"(a[1]), "r"(a[2]), "r"(a[3]), "r"(lo), "r"(hi));
}
__device__ __forceinline__ void wg_qk(float* d, const uint32_t* a, uint32_t lo) {
    asm volatile("{ .reg .b64 dd; mov.b64 dd, {%36, %37};\n"
                 "wgmma.mma_async.sync.aligned.m64n64k16.f32.bf16.bf16 {%0,%1,%2,%3,%4,%5,%6,%7,%8,%9,%10,%11,%12,%13,%14,%15,%16,%17,%18,%19,%20,%21,%22,%23,%24,%25,%26,%27,%28,%29,%30,%31}, {%32,%33,%34,%35}, dd, 0, 1, 1, 0; }"
                 : A16(d, 0), A16(d, 16) : "r"(a[0]), "r"(a[1]), "r"(a[2]), "r"(a[3]), "r"(lo), "r"(16));
}
__device__ __forceinline__ void wg_rs32(float* d, const uint32_t* a, uint32_t lo) {
    asm volatile("{ .reg .b64 dd; mov.b64 dd, {%20, %21};\n"
                 "wgmma.mma_async.sync.aligned.m64n32k16.f32.bf16.bf16 {%0,%1,%2,%3,%4,%5,%6,%7,%8,%9,%10,%11,%12,%13,%14,%15}, {%16,%17,%18,%19}, dd, 1, 1, 1, 0; }"
                 : A16(d, 0) : "r"(a[0]), "r"(a[1]), "r"(a[2]), "r"(a[3]), "r"(lo), "r"(0x40000040));
}
__device__ __forceinline__ void wg_ss32(float* d, uint64_t da, uint64_t db) {
    asm volatile("wgmma.mma_async.sync.aligned.m64n32k16.f32.bf16.bf16 {%0,%1,%2,%3,%4,%5,%6,%7,%8,%9,%10,%11,%12,%13,%14,%15}, %16, %17, 1, 1, 1, 0, 1;"
                 : A16(d, 0) : "l"(da), "l"(db));
}
__device__ __forceinline__ void wg_ss64(float* d, uint64_t da, uint64_t db) {
    asm volatile("wgmma.mma_async.sync.aligned.m64n64k16.f32.bf16.bf16 {%0,%1,%2,%3,%4,%5,%6,%7,%8,%9,%10,%11,%12,%13,%14,%15,%16,%17,%18,%19,%20,%21,%22,%23,%24,%25,%26,%27,%28,%29,%30,%31}, %32, %33, 1, 1, 1, 0, 1;"
                 : A16(d, 0), A16(d, 16) : "l"(da), "l"(db));
}
__device__ __forceinline__ void wg_ss16(float* d, uint64_t da, uint64_t db) {
    asm volatile("wgmma.mma_async.sync.aligned.m64n16k16.f32.bf16.bf16 {%0,%1,%2,%3,%4,%5,%6,%7}, %8, %9, 1, 1, 1, 0, 1;"
                 : A4(d, 0), A4(d, 4) : "l"(da), "l"(db));
}
template<int N> __device__ __forceinline__ void fence_regs(float* r) {
    #pragma unroll
    for (int i = 0; i < N; i++) asm volatile("" : "+f"(r[i]) :: "memory");
}
__device__ __forceinline__ void mma_f16(float* d, const uint32_t* a, uint32_t b0, uint32_t b1) {
    asm volatile("mma.sync.aligned.m16n8k16.row.col.f32.f16.f16.f32 {%0,%1,%2,%3}, {%4,%5,%6,%7}, {%8,%9}, {%0,%1,%2,%3};"
                 : "+f"(d[0]), "+f"(d[1]), "+f"(d[2]), "+f"(d[3]) : "r"(a[0]), "r"(a[1]), "r"(a[2]), "r"(a[3]), "r"(b0), "r"(b1));
}
__device__ __forceinline__ uint32_t lds32(uint32_t addr) { uint32_t v; asm volatile("ld.shared.u32 %0, [%1];" : "=r"(v) : "r"(addr) : "memory"); return v; }
__device__ __forceinline__ void mma_bf16_p(float* d, uint32_t a0, uint32_t a1, uint32_t a2, uint32_t a3, uint32_t b0, uint32_t b1) {
    asm("mma.sync.aligned.m16n8k16.row.col.f32.bf16.bf16.f32 {%0,%1,%2,%3}, {%4,%5,%6,%7}, {%8,%9}, {%0,%1,%2,%3};"
        : "+f"(d[0]), "+f"(d[1]), "+f"(d[2]), "+f"(d[3]) : "r"(a0), "r"(a1), "r"(a2), "r"(a3), "r"(b0), "r"(b1));
}
__device__ __forceinline__ void ldsm4t_p(uint32_t* r, uint32_t addr) {
    asm("ldmatrix.sync.aligned.m8n8.x4.trans.shared.b16 {%0,%1,%2,%3}, [%4];" : "=r"(r[0]), "=r"(r[1]), "=r"(r[2]), "=r"(r[3]) : "r"(addr));
}
__device__ __forceinline__ uint32_t lds32_p(uint32_t addr) { uint32_t v; asm("ld.shared.u32 %0, [%1];" : "=r"(v) : "r"(addr)); return v; }
__device__ __forceinline__ uint32_t swz(uint32_t a) { return a ^ ((a >> 3) & 16u); }
__device__ __forceinline__ uint32_t swz128(uint32_t a) { return a ^ ((a >> 3) & 0x70u); }
__device__ __forceinline__ void sts32(uint32_t addr, uint32_t v) { asm volatile("st.shared.u32 [%0], %1;" :: "r"(addr), "r"(v) : "memory"); }
__device__ __forceinline__ void sts128(uint32_t addr, uint4 v) { asm volatile("st.shared.v4.u32 [%0], {%1,%2,%3,%4};" :: "r"(addr), "r"(v.x), "r"(v.y), "r"(v.z), "r"(v.w) : "memory"); }
__device__ __forceinline__ uint4 lds128(uint32_t addr) { uint4 v; asm volatile("ld.shared.v4.u32 {%0,%1,%2,%3}, [%4];" : "=r"(v.x), "=r"(v.y), "=r"(v.z), "=r"(v.w) : "r"(addr) : "memory"); return v; }
__device__ __forceinline__ float ex2f(float x) { float r; asm("ex2.approx.ftz.f32 %0, %1;" : "=f"(r) : "f"(x)); return r; }
__device__ __forceinline__ uint32_t pack_bf16(float lo, float hi) { uint32_t r; asm("cvt.rn.bf16x2.f32 %0, %1, %2;" : "=r"(r) : "f"(hi), "f"(lo)); return r; }
__device__ __forceinline__ uint32_t pack_f16(float lo, float hi) { uint32_t r; asm("cvt.rn.f16x2.f32 %0, %1, %2;" : "=r"(r) : "f"(hi), "f"(lo)); return r; }
__device__ __forceinline__ float bf_lo(uint32_t v) { return __uint_as_float(v << 16); }
__device__ __forceinline__ float bf_hi(uint32_t v) { return __uint_as_float(v & 0xFFFF0000u); }
__device__ __forceinline__ float bf_round(float x) { return __bfloat162float(__float2bfloat16_rn(x)); }

__device__ __forceinline__ uint32_t exp_mufu(float x0, float x1) { return pack_bf16(ex2f(x0), ex2f(x1)); }
#define SW_MAGIC (256.0f + 127.0f - 0.598938f)
__device__ __forceinline__ uint32_t exp_sw(float x0, float x1, uint32_t cA, uint32_t cB) {
    float t0 = x0 + SW_MAGIC, t1 = x1 + SW_MAGIC;
    uint32_t L, mh, ec, r;
    asm("prmt.b32 %0, %1, %2, 0x6521;" : "=r"(L) : "r"(__float_as_uint(t0)), "r"(__float_as_uint(t1)));
    asm("lop3.b32 %0, %1, 0x007F007F, %2, 0xEA;" : "=r"(mh) : "r"(L), "r"(cA));
    asm("lop3.b32 %0, %1, 0x7F807F80, %2, 0xEA;" : "=r"(ec) : "r"(L), "r"(cB));
    asm("fma.rn.bf16x2 %0, %1, %2, %3;" : "=r"(r) : "r"(L), "r"(mh), "r"(ec));
    return r;
}
constexpr uint32_t MUFU_MASK = 0x4949;

struct cf { float x, y; };
__device__ __forceinline__ cf cmul(cf a, cf b) { cf r; r.x = a.x * b.x - a.y * b.y; r.y = a.x * b.y + a.y * b.x; return r; }
__device__ __forceinline__ cf cexp_p(float a2, float b, float p) {
    float e = ex2f(a2 * p);
    float ph = b * p;
    ph -= (ph + 12582912.0f) - 12582912.0f;
    float ang = ph * 6.283185307f;
    cf r; r.x = e * __cosf(ang); r.y = e * __sinf(ang);
    return r;
}
__device__ __forceinline__ uint32_t h2_cmul(uint32_t w, uint32_t wsw, uint32_t e) {
    __half2 hw = *(__half2*)&w, hs = *(__half2*)&wsw, he = *(__half2*)&e;
    __half2 r = __hfma2(hs, __high2half2(he), __hmul2(hw, __low2half2(he)));
    return *(uint32_t*)&r;
}

template<bool B> struct BoolC { static constexpr bool value = B; };
struct Params {
    const __nv_bfloat16 *u, *lar, *aim, *cre, *cim, *logdt, *dskip;
    __nv_bfloat16* out;
};

constexpr int B_O = 0, B_KV = 8, B_WO = 12, B_WQ2 = 13, B_ST = 14, B_H = 15, B_X = 17, B_U = 19, B_WQ = 20;

__device__ __forceinline__ void helper_role(const Params& P, uint8_t* sp, uint32_t sb, unsigned epoch) {
    const uint32_t sBa = sb + SM_B;
    const int tid = threadIdx.x - 544;
    const int d0 = blockIdx.x * 4;
    uint8_t* sB = sp + SM_B;
    const uint2 dsk = __ldg((const uint2*)(P.dskip + d0));
    asm volatile("barrier.cluster.wait.aligned;" ::: "memory");
    {
        const int hg = blockIdx.x & 7;
        if (hg < 4 && tid < 32) {
            bar_sync(3, 160);
            if (tid == 0) {
                const float* s_misc = (const float*)(sp + SM_BAR + 256);
                const float st = fmaxf(fmaxf(s_misc[20], s_misc[21]), fmaxf(s_misc[22], s_misc[23]));
                st_release64(&g_flag_kv[((blockIdx.x >> 3) * 2 + (hg & 1)) * 2 + (hg >> 1)], ((unsigned long long)epoch << 32) | __float_as_uint(st));
            }
            __syncwarp();
        }
    }
    PROF2(2);
    bar_sync(10, 608);
    {
        uint32_t dd[4] = {__byte_perm(dsk.x, 0, 0x1010), __byte_perm(dsk.x, 0, 0x3232), __byte_perm(dsk.y, 0, 0x1010), __byte_perm(dsk.y, 0, 0x3232)};
        #pragma unroll 2
        for (int pi = tid; pi < 1024; pi += 96) {
            const int l = 2 * pi;
            uint32_t r[4];
            #pragma unroll
            for (int cc = 0; cc < 4; cc++) {
                const uint32_t y2 = *(const uint32_t*)(sB + S_Y + cc * 4096 + l * 2);
                const uint32_t u2 = lds32(swz128(sBa + S_U + cc * ULEN * 2 + (PADU + l) * 2));
                __nv_bfloat162 pr = __hmul2(*(const __nv_bfloat162*)&u2, *(const __nv_bfloat162*)&dd[cc]);
                __nv_bfloat162 sm = __hadd2(*(const __nv_bfloat162*)&y2, pr);
                r[cc] = *(uint32_t*)&sm;
            }
            *(uint2*)(P.out + (size_t)l * 1024 + 512 + d0) = make_uint2(__byte_perm(r[0], r[1], 0x5410), __byte_perm(r[2], r[3], 0x5410));
            *(uint2*)(P.out + (size_t)(l + 1) * 1024 + 512 + d0) = make_uint2(__byte_perm(r[0], r[1], 0x7632), __byte_perm(r[2], r[3], 0x7632));
        }
    }
    bar_arrive(11, 128);
    PROF2(4);
}

__global__ void __cluster_dims__(2, 1, 1) __launch_bounds__(NTHR, 1)
fused_kernel(const __grid_constant__ CUtensorMap tm_x, const __grid_constant__ CUtensorMap tm_wq,
             const __grid_constant__ CUtensorMap tm_wo, const __grid_constant__ CUtensorMap tm_wk,
             const __grid_constant__ CUtensorMap tm_wv, const __grid_constant__ CUtensorMap tm_u, const Params P) {
    extern __shared__ uint8_t smem_raw[];
    const uint32_t sb = (smem_u32(smem_raw) + 1023u) & ~1023u;
    uint8_t* sp = smem_raw + (sb - smem_u32(smem_raw));

    const int tid = threadIdx.x, warp = tid >> 5, lane = tid & 31, wg = tid >> 7, wiw = warp & 3;
    const int g = lane >> 2, t = lane & 3;
    const int qb = blockIdx.x >> 3, hg = blockIdx.x & 7;
    const uint32_t rank = blockIdx.x & 1;
    const int rowhalf = wg & 1, nh = wg >> 1;
    const bool kv_cta = hg < 4;
    const int kv_sel = hg >> 1;
    const bool kv_wg = kv_cta && (wg == (hg & 1));

    const uint32_t bars = sb + SM_BAR;
    float* s_misc = (float*)(sp + SM_BAR + 256);
    const CUtensorMap* tm_kv = kv_sel ? &tm_wv : &tm_wk;

    PROF(0);
    unsigned short p_lar = 0, p_aim = 0, p_cre = 0, p_cim = 0, p_ldt = 0;
    if (wg < 4) {
        const int n = (blockIdx.x * 4 + wg) * 128 + (tid & 127);
        p_lar = __ldg((const unsigned short*)P.lar + n);
        p_aim = __ldg((const unsigned short*)P.aim + n);
        p_cre = __ldg((const unsigned short*)P.cre + n);
        p_cim = __ldg((const unsigned short*)P.cim + n);
        p_ldt = __ldg((const unsigned short*)P.logdt + blockIdx.x * 4 + wg);
    } else if (warp == 16) {
        PROF3(5);
        if (lane == 0) {
            asm volatile("prefetch.tensormap [%0];" :: "l"((uint64_t)&tm_x) : "memory");
            asm volatile("prefetch.tensormap [%0];" :: "l"((uint64_t)tm_kv) : "memory");
            asm volatile("prefetch.tensormap [%0];" :: "l"((uint64_t)&tm_wq) : "memory");
            asm volatile("prefetch.tensormap [%0];" :: "l"((uint64_t)&tm_u) : "memory");
            mbar_init(bars + 8 * B_X, 1);
            mbar_init(bars + 8 * B_X + 8, 1);
            mbar_init(bars + 8 * B_U, 1);
            asm volatile("fence.mbarrier_init.release.cluster;" ::: "memory");
            mbar_expect_tx(bars + 8 * B_X, 65536u + (kv_cta ? 8192u : 0u));
            mbar_expect_tx(bars + 8 * B_X + 8, 65536u + (kv_cta ? 8192u : 0u));
            mbar_expect_tx(bars + 8 * B_U, 32768u);
        }
        __syncwarp();
        PROF3(6);
    }
    asm volatile("barrier.cluster.arrive.relaxed.aligned;" ::: "memory");
    const unsigned epoch = *(volatile unsigned*)&g_epoch + 1u;
    if (warp > 16) {
        if (lane == 0) {
            for (int i = warp - 17; i < B_X; i += 3) {
                mbar_init(bars + 8 * i, i >= B_H ? 2 : 1);
                if (i <= B_WQ2) mbar_expect_tx(bars + 8 * i, i < B_KV + 2 ? 16384u : i == B_KV + 2 ? 32768u : i <= B_WO ? 65536u : 32768u);
            }
            asm volatile("fence.mbarrier_init.release.cluster;" ::: "memory");
            fence_async_smem();
        } else if (warp == 19) {
            #pragma unroll
            for (int i = 0; i < 2; i++) if (lane - 1 + 31 * i < 41) asm volatile("prefetch.global.L2 [%0];" :: "l"((const char*)g_tabmap.v + (lane - 1 + 31 * i) * 128));
        }
        __syncwarp();
    }
    asm volatile("barrier.cluster.wait.aligned;" ::: "memory");
    PROF(5);
    if (warp == 16 && lane == 0) {
        tma_3d_mc(sb + (rank ? SM_A : SM_B), &tm_x, 0, qb * 128, rank * 4, bars + 8 * (B_X + rank));
        if (kv_cta) {
            #pragma unroll
            for (int i = 0; i < 4; i++) tma_2d(sb + SM_WKV + i * 4096, tm_kv, (i >> 1) * 8, (i & 1) * 256, bars + 8 * (B_X + (i & 1)));
        }
        mbar_init(bars + 8 * B_WQ, 1);
        asm volatile("fence.mbarrier_init.release.cluster;" ::: "memory");
        fence_async_smem();
        mbar_expect_tx(bars + 8 * B_WQ, 32768u);
        tma_2d(sb + SM_WQ, &tm_wq, hg * 64, 0, bars + 8 * B_WQ);
        #pragma unroll
        for (int i = 0; i < 4; i++) tma_2d_mc(sb + SM_SLAB + (rank * 4 + i) * 4096, &tm_u, (blockIdx.x >> 1) * 8, (rank * 4 + i) * 256, bars + 8 * B_U);
    }
    __syncwarp();
    asm volatile("barrier.cluster.arrive.relaxed.aligned;" ::: "memory");

    if (warp == 16) {
        if (lane == 0) asm volatile("prefetch.tensormap [%0];" :: "l"((uint64_t)&tm_wo) : "memory");
        asm volatile("barrier.cluster.wait.aligned;" ::: "memory");
        PROF3(10);
        bar_sync(13, 544);
        if (lane == 0) { fence_async_smem(); tma_2d(sb + SM_SLAB, &tm_wq, hg * 64, 256, bars + 8 * B_WQ2); }
        bar_sync(14, 544);
        if (lane == 0) pair_sync(bars + 8 * B_H, rank ^ 1);
        __syncwarp();
        PROF3(11);
        *(uint4*)(sp + SM_V + 32768 + lane * 32) = make_uint4(0x3F803F80u, 0x3F803F80u, 0x3F803F80u, 0x3F803F80u);
        *(uint4*)(sp + SM_V + 32768 + lane * 32 + 16) = make_uint4(0x3F803F80u, 0x3F803F80u, 0x3F803F80u, 0x3F803F80u);
        fence_async_smem();
        float km = wait_flag64(&g_flag_kv[2 * lane], epoch);
        float vm = wait_flag64(&g_flag_kv[2 * lane + 1], epoch);
        __syncwarp();
        PROF3(12);
        if (lane == 0) {
            fence_async_all();
            #pragma unroll
            for (int i = 0; i < 4; i++) {
                const uint32_t k0 = i == 0 ? 0 : 128u << i, nk = i == 0 ? 256 : 128u << i;
                const uint32_t bar = bars + 8 * (B_KV + i);
                if (rank == 0) bulk_g2s_mc(sb + SM_K + k0 * 32, g_kimg + k0 * 32, nk * 32, bar);
                else {
                    bulk_g2s_mc(sb + SM_V + k0 * 16, g_vimg + k0 * 16, nk * 16, bar);
                    bulk_g2s_mc(sb + SM_V + 66560 - (k0 + nk) * 16, g_vimg + 66560 - (k0 + nk) * 16, nk * 16, bar);
                }
            }
        }
        #pragma unroll
        for (int o = 16; o; o >>= 1) { km = fmaxf(km, __shfl_xor_sync(0xffffffffu, km, o)); vm = fmaxf(vm, __shfl_xor_sync(0xffffffffu, vm, o)); }
        if (lane == 0) { s_misc[16] = km; s_misc[17] = vm; mbar_arrive(bars + 8 * B_ST); }
        PROF3(13);
        bar_sync(11, 128);
        if (lane < 2) { fence_async_smem(); tma_2d(sb + SM_B + lane * 32768, &tm_wo, hg * 64, lane * 256, bars + 8 * B_WO); }
        bar_sync(12, 544);
        if (lane == 0) {
            st_release(&g_flag_o[blockIdx.x], epoch);
            pair_sync(bars + 8 * (B_H + 1), rank ^ 1);
        }
        __syncwarp();
        PROF3(14);
        if (lane < 4) {
            const int src = (2 * lane + (hg & 6) + rank) & 7;
            wait_flag(&g_flag_o[qb * 8 + src], epoch);
            fence_async_all();
            bulk_g2s_mc(sb + SM_A + src * 16384, g_oimg + qb * 131072 + src * 16384, 16384, bars + 8 * (B_O + src));
        }
        __syncwarp();
        PROF3(15);
        if (lane == 0) {
            const unsigned prev = atomicAdd(&g_done, 1u);
            if (prev == NCTA - 1) {
                g_done = 0;
                __threadfence();
                *(volatile unsigned*)&g_epoch = epoch;
            }
        }
    } else if (wg == 4) {
        helper_role(P, sp, sb, epoch);
    } else {
        uint8_t* sB = sp + SM_B;
        const uint32_t sBa = sb + SM_B;
        {
            const int c = wg;
            const float dt = bf_round(expf(bf_lo(p_ldt)));
            const float are = -bf_round(expf(bf_lo(p_lar))) * dt;
            const float aim = bf_lo(p_aim) * dt;
            float cr = 2.0f * (bf_lo(p_cre) * dt);
            float ci = 2.0f * (bf_lo(p_cim) * dt);
            const float a2 = are * 1.4426950408889634f, bb = aim * 0.15915494309189535f;
            float m = fmaxf(fabsf(cr), fabsf(ci));
            #pragma unroll
            for (int o = 16; o; o >>= 1) m = fmaxf(m, __shfl_xor_sync(0xffffffffu, m, o));
            int ebits = (__float_as_uint(m) >> 23) & 0xFF;
            ebits = min(max(ebits, 2), 250);
            const float scale = __uint_as_float((uint32_t)(ebits + 1) << 23);
            const float iscale = __uint_as_float((uint32_t)(253 - ebits) << 23);
            cf cc; cc.x = cr * iscale; cc.y = ci * iscale;

            const uint32_t stg = sBa + S_KC + warp * 1024;
            uint4* stp = (uint4*)(sB + S_KC + warp * 1024 + lane * 32);
            const uint32_t fa = stg + t * 32 + g * 4;

            uint32_t af[4][2][4];
            cf E256;
            {
                const cf E8 = cexp_p(a2, bb, 8.0f);
                uint32_t w[8];
                cf cur; cur.x = 1.0f; cur.y = 0.0f;
                w[0] = pack_f16(1.0f, 0.0f);
                cur = E8; w[1] = pack_f16(cur.x, cur.y);
                #pragma unroll
                for (int i = 2; i < 8; i++) { cur = cmul(cur, E8); w[i] = pack_f16(cur.x, cur.y); }
                stp[0] = make_uint4(w[0], w[1], w[2], w[3]);
                stp[1] = make_uint4(w[4], w[5], w[6], w[7]);
                const cf E64 = cexp_p(a2, bb, 64.0f);
                const cf E128 = cmul(E64, E64), E192 = cmul(E128, E64);
                E256 = cexp_p(a2, bb, 256.0f);
                const uint32_t e1 = pack_f16(E64.x, E64.y), e2 = pack_f16(E128.x, E128.y), e3 = pack_f16(E192.x, E192.y);
                __syncwarp();
                #pragma unroll
                for (int s = 0; s < 4; s++) {
                    #pragma unroll
                    for (int hh = 0; hh < 2; hh++) {
                        const uint32_t w0 = lds32(fa + s * 256 + hh * 128);
                        const uint32_t wsw = __byte_perm(w0, 0, 0x1032) ^ 0x00008000u;
                        const int src = 8 * s + t + 4 * hh;
                        const uint32_t f1 = __shfl_sync(0xffffffffu, e1, src), f2 = __shfl_sync(0xffffffffu, e2, src), f3 = __shfl_sync(0xffffffffu, e3, src);
                        af[s][0][2 * hh] = w0;
                        af[s][0][2 * hh + 1] = h2_cmul(w0, wsw, f1);
                        af[s][1][2 * hh] = h2_cmul(w0, wsw, f2);
                        af[s][1][2 * hh + 1] = h2_cmul(w0, wsw, f3);
                    }
                }
                __syncwarp();
            }
            float acc[2][3][4];
            #pragma unroll
            for (int i = 0; i < 24; i++) (&acc[0][0][0])[i] = 0.0f;
            const cf E1 = cexp_p(a2, bb, 1.0f);
            const cf E2 = cmul(E1, E1), E4 = cmul(E2, E2);
            cf X512;
            #pragma unroll
            for (int nt = 0; nt < 3; nt++) {
                uint32_t xv[8];
                if (nt == 0) {
                    cf cur = cc;
                    xv[0] = pack_f16(cur.x, -cur.y);
                    #pragma unroll
                    for (int i = 1; i < 8; i++) { cur = cmul(cur, E1); xv[i] = pack_f16(cur.x, -cur.y); }
                } else if (nt == 1) {
                    cf cur = cmul(cc, E256);
                    X512 = cmul(cur, E256);
                    xv[0] = pack_f16(cur.x, -cur.y);
                    #pragma unroll
                    for (int i = 1; i < 4; i++) { cur = cmul(cur, E2); xv[i] = pack_f16(cur.x, -cur.y); }
                    cur = cmul(X512, E4);
                    xv[4] = pack_f16(X512.x, -X512.y); xv[5] = pack_f16(cur.x, -cur.y);
                    X512 = cmul(X512, E256);
                    cur = cmul(X512, E4);
                    xv[6] = pack_f16(X512.x, -X512.y); xv[7] = pack_f16(cur.x, -cur.y);
                } else {
                    cf cur = X512;
                    #pragma unroll
                    for (int i = 0; i < 5; i++) { cur = cmul(cur, E256); xv[i] = pack_f16(cur.x, -cur.y); }
                    xv[5] = 0; xv[6] = 0; xv[7] = 0;
                }
                stp[0] = make_uint4(xv[0], xv[1], xv[2], xv[3]);
                stp[1] = make_uint4(xv[4], xv[5], xv[6], xv[7]);
                __syncwarp();
                #pragma unroll
                for (int s = 0; s < 4; s++) {
                    const uint32_t b0 = lds32(fa + s * 256), b1 = lds32(fa + s * 256 + 128);
                    mma_f16(acc[0][nt], af[s][0], b0, b1);
                    mma_f16(acc[1][nt], af[s][1], b0, b1);
                }
                __syncwarp();
            }
            float* kc = (float*)(sB + S_KC + c * 4096);
            bar_sync(4 + c, 128);
            #pragma unroll 1
            for (int step = 0; step < 4; step++) {
                if ((warp & 3) == step) {
                    #pragma unroll
                    for (int mt = 0; mt < 2; mt++)
                        #pragma unroll
                        for (int nt = 0; nt < 3; nt++)
                            #pragma unroll
                            for (int hh = 0; hh < 2; hh++) {
                                float2* p = (float2*)(kc + (mt * 16 + hh * 8 + g) * 24 + nt * 8 + 2 * t);
                                float2 v = make_float2(acc[mt][nt][2 * hh] * scale, acc[mt][nt][2 * hh + 1] * scale);
                                if (step) { float2 o = *p; v.x += o.x; v.y += o.y; }
                                *p = v;
                            }
                }
                if (step < 3) bar_sync(4 + c, 128);
            }
        }

        asm volatile("barrier.cluster.wait.aligned;" ::: "memory");
        PROF(4);
        uint32_t q[2][4];
        {
            float acc[16], akv[8];
            #pragma unroll
            for (int i = 0; i < 16; i++) acc[i] = 0.0f;
            #pragma unroll
            for (int i = 0; i < 8; i++) akv[i] = 0.0f;
            fence_regs<16>(acc);
            fence_regs<8>(akv);
            const uint64_t dA0 = make_desc(sb + SM_B + rowhalf * 8192, 16, 1024, 1);
            const uint64_t dA1 = make_desc(sb + SM_A + rowhalf * 8192, 16, 1024, 1) - 4096;
            const uint64_t dB = make_desc(sb + SM_WQ + nh * 64, 16, 1024, 1);
            const uint64_t dC = make_desc(sb + SM_WKV, 128, 8192, 0);
            if (kv_wg) {
                #pragma unroll 1
                for (int ch = 0; ch < 8; ch++) {
                    if ((ch & 3) == 0) mbar_wait(bars + 8 * (B_X + (ch >> 2)), 0);
                    const uint64_t dA = ch < 4 ? dA0 : dA1;
                    wg_fence();
                    #pragma unroll
                    for (int ks = 0; ks < 4; ks++) wg_ss16(akv, dA + ch * 1024 + ks * 2, dC + (ch * 4 + ks) * 16);
                    wg_commit();
                }
                wg_wait<0>();
            }
            fence_regs<8>(akv);
            if (kv_wg) {
                const int key = qb * 128 + rowhalf * 64 + wiw * 16 + g;
                uint32_t pk[4];
                #pragma unroll
                for (int i = 0; i < 4; i++) pk[i] = pack_bf16(akv[2 * i], akv[2 * i + 1]);
                float st;
                if (kv_sel == 0) {
                    uint8_t* b = g_kimg + (key >> 3) * 256 + (key & 7) * 16 + 4 * t;
                    *(uint32_t*)(b) = pk[0]; *(uint32_t*)(b + 256) = pk[1]; *(uint32_t*)(b + 128) = pk[2]; *(uint32_t*)(b + 384) = pk[3];
                    float n0 = bf_lo(pk[0]) * bf_lo(pk[0]) + bf_hi(pk[0]) * bf_hi(pk[0]) + bf_lo(pk[2]) * bf_lo(pk[2]) + bf_hi(pk[2]) * bf_hi(pk[2]);
                    float n1 = bf_lo(pk[1]) * bf_lo(pk[1]) + bf_hi(pk[1]) * bf_hi(pk[1]) + bf_lo(pk[3]) * bf_lo(pk[3]) + bf_hi(pk[3]) * bf_hi(pk[3]);
                    n0 += __shfl_xor_sync(0xffffffffu, n0, 1); n0 += __shfl_xor_sync(0xffffffffu, n0, 2);
                    n1 += __shfl_xor_sync(0xffffffffu, n1, 1); n1 += __shfl_xor_sync(0xffffffffu, n1, 2);
                    st = (n0 != n0 || n1 != n1) ? __int_as_float(0x7f800000) : fmaxf(n0, n1);
                } else {
                    uint8_t* lo = g_vimg + key * 16 + 4 * t;
                    uint8_t* hi = g_vimg + 33792 + (31 - (key >> 6)) * 1024 + (key & 63) * 16 + 4 * t;
                    *(uint32_t*)(lo) = pk[0]; *(uint32_t*)(lo + 128) = pk[1]; *(uint32_t*)(hi) = pk[2]; *(uint32_t*)(hi + 128) = pk[3];
                    st = 0.0f;
                    #pragma unroll
                    for (int i = 0; i < 4; i++) {
                        float a = fabsf(bf_lo(pk[i])), b = fabsf(bf_hi(pk[i]));
                        st = (a != a || b != b) ? __int_as_float(0x7f800000) : fmaxf(st, fmaxf(a, b));
                    }
                }
                #pragma unroll
                for (int o = 16; o; o >>= 1) st = fmaxf(st, __shfl_xor_sync(0xffffffffu, st, o));
                if (lane == 0) s_misc[20 + wiw] = st;
                bar_arrive(3, 160);
            }
            uint2 mp[6];
            #pragma unroll
            for (int i = 0; i < 6; i++) { const int w = (tid & 127) + 128 * i; mp[i] = (w < TABN / 4) ? __ldg((const uint2*)g_tabmap.v + w) : make_uint2(0u, 0u); }
            mbar_wait(bars + 8 * B_WQ, 0);
            mbar_wait(bars + 8 * B_X, 0);
            PROF(2);
            #pragma unroll 1
            for (int ch = 0; ch < 4; ch++) {
                wg_fence();
                #pragma unroll
                for (int ks = 0; ks < 4; ks++) wg_ss32(acc, dA0 + ch * 1024 + ks * 2, dB + (ch * 4 + ks) * 128);
                wg_commit();
            }
            wg_wait<0>();
            fence_regs<16>(acc);
            bar_sync(1, 512);
            PROF(15);
            #pragma unroll
            for (int i = 0; i < 2; i++) {
                const int z = tid + 512 * i;
                if (z < 4 * 144) sts128(sBa + S_U + (z / 144) * ULEN * 2 + (PADU - 1152) * 2 + (z % 144) * 16, make_uint4(0, 0, 0, 0));
            }
            PROF(8);
            mbar_wait(bars + 8 * B_U, 0);
            PROF(14);
            #pragma unroll
            for (int i = 0; i < 2; i++) {
                const int l = 2 * (tid + 512 * i);
                const uint2 r0 = *(const uint2*)(sp + SM_SLAB + l * 16 + rank * 8), r1 = *(const uint2*)(sp + SM_SLAB + l * 16 + 16 + rank * 8);
                const uint32_t dst = swz128(sBa + S_U + (PADU + l) * 2);
                sts32(dst, __byte_perm(r0.x, r1.x, 0x5410));
                sts32(dst + ULEN * 2, __byte_perm(r0.x, r1.x, 0x7632));
                sts32(dst + ULEN * 4, __byte_perm(r0.y, r1.y, 0x5410));
                sts32(dst + ULEN * 6, __byte_perm(r0.y, r1.y, 0x7632));
            }
            bar_arrive(13, 544);
            {
                const float* kc = (const float*)(sB + S_KC + wg * 4096);
                uint2* tab = (uint2*)(sB + S_TAB + wg * TABN * 2);
                #pragma unroll
                for (int i = 0; i < 6; i++) {
                    const int w = (tid & 127) + 128 * i;
                    if (w < TABN / 4) tab[w] = make_uint2(pack_bf16(kc[mp[i].x & 0xFFFF], kc[mp[i].x >> 16]), pack_bf16(kc[mp[i].y & 0xFFFF], kc[mp[i].y >> 16]));
                }
            }
            fence_async_smem();
            bar_sync(1, 512);
            PROF(1);
            mbar_wait(bars + 8 * B_WQ2, 0);
            mbar_wait(bars + 8 * (B_X + 1), 0);
            fence_regs<16>(acc);
            wg_fence();
            #pragma unroll
            for (int ks = 16; ks < 32; ks++) wg_ss32(acc, dA1 + (ks >> 2) * 1024 + (ks & 3) * 2, dB + ks * 128);
            wg_commit();
            {
                const int task = tid + (tid < 8 ? 512 : 0) * 0;
                #pragma unroll 1
                for (int tk = task; tk < 4 * 130; tk += 512) {
                    const int c = tk / 130, i = tk % 130;
                    const uint32_t src = sBa + S_U + c * ULEN * 2 + (PADU + 8 * i - WPAD - 8) * 2;
                    const uint4 v0 = lds128(swz128(src)), v1 = lds128(swz128(src + 16)), v2 = lds128(swz128(src + 32));
                    float x[16];
                    const uint32_t vv[8] = {v0.z, v0.w, v1.x, v1.y, v1.z, v1.w, v2.x, v2.y};
                    #pragma unroll
                    for (int k = 0; k < 8; k++) { x[2 * k] = bf_lo(vv[k]); x[2 * k + 1] = bf_hi(vv[k]); }
                    float p2[15], w7[8], w9[8];
                    #pragma unroll
                    for (int e = 0; e < 15; e++) p2[e] = x[e] + x[e + 1];
                    #pragma unroll
                    for (int e = 0; e < 8; e++) {
                        w7[e] = (p2[e + 1] + p2[e + 3]) + (p2[e + 5] + x[e + 7]);
                        w9[e] = w7[e] + (x[e] + x[e + 8]);
                    }
                    sts128(swz(sBa + S_W7 + c * W3LEN * 2 + i * 16), make_uint4(pack_bf16(w7[0], w7[1]), pack_bf16(w7[2], w7[3]), pack_bf16(w7[4], w7[5]), pack_bf16(w7[6], w7[7])));
                    sts128(swz(sBa + S_W9 + c * W3LEN * 2 + i * 16), make_uint4(pack_bf16(w9[0], w9[1]), pack_bf16(w9[2], w9[3]), pack_bf16(w9[4], w9[5]), pack_bf16(w9[6], w9[7])));
                }
            }
            wg_wait<0>();
            fence_regs<16>(acc);
            bar_arrive(14, 544);
            const float QS = 0.25f * 1.4426950408889634f;
            float qm = 0.0f;
            #pragma unroll
            for (int i = 0; i < 2; i++) {
                #pragma unroll
                for (int j = 0; j < 4; j++) q[i][j] = pack_bf16(bf_round(acc[8 * i + 2 * j]) * QS, bf_round(acc[8 * i + 2 * j + 1]) * QS);
                float n0 = bf_lo(q[i][0]) * bf_lo(q[i][0]) + bf_hi(q[i][0]) * bf_hi(q[i][0]) + bf_lo(q[i][2]) * bf_lo(q[i][2]) + bf_hi(q[i][2]) * bf_hi(q[i][2]);
                float n1 = bf_lo(q[i][1]) * bf_lo(q[i][1]) + bf_hi(q[i][1]) * bf_hi(q[i][1]) + bf_lo(q[i][3]) * bf_lo(q[i][3]) + bf_hi(q[i][3]) * bf_hi(q[i][3]);
                n0 += __shfl_xor_sync(0xffffffffu, n0, 1); n0 += __shfl_xor_sync(0xffffffffu, n0, 2);
                n1 += __shfl_xor_sync(0xffffffffu, n1, 1); n1 += __shfl_xor_sync(0xffffffffu, n1, 2);
                qm = (n0 != n0 || n1 != n1) ? __int_as_float(0x7f800000) : fmaxf(qm, fmaxf(n0, n1));
            }
            #pragma unroll
            for (int o = 16; o; o >>= 1) qm = fmaxf(qm, __shfl_xor_sync(0xffffffffu, qm, o));
            if (lane == 0) s_misc[warp] = qm;
        }
        PROF(3);
        {
            const int c = wg;
            uint32_t sBl = sBa;
            asm volatile("" : "+r"(sBl) :: "memory");
            float acc[16];
            #pragma unroll
            for (int i = 0; i < 16; i++) acc[i] = 0.0f;
            fence_regs<16>(acc);
            const uint32_t tabc = sBl + S_TAB + c * TABN * 2;
            const uint32_t tD = tabc + ((g & 1) ? (TD1 + CD + 1) : (TD0 + CD)) * 2 - (g - 2 * t) * 2 - 32 * wiw;
            const uint32_t uLo = (((sBl + S_U + c * ULEN * 2 + PADU * 2) & 0x3FFFF) >> 4) | (1u << 16);
            uint32_t A[2][4][4];
            auto load_set = [&](uint32_t (&X)[4][4], int m0) {
                asm volatile("{ .reg .pred p; setp.lt.u32 p, %2, 66; mov.b32 %0, 0; @p ld.shared.u32 %0, [%1]; }"
                             : "=r"(X[0][2]) : "r"(tD - 32 * m0 + 16), "r"(m0 + wiw) : "memory");
                #pragma unroll
                for (int i = 0; i < 4; i++) {
                    asm volatile("{ .reg .pred p; setp.lt.u32 p, %3, 66; mov.b32 %0, 0; mov.b32 %1, 0; @p ld.shared.u32 %0, [%2]; @p ld.shared.u32 %1, [%2+-16]; }"
                                 : "=r"(X[i][0]), "=r"(X[i][1]) : "r"(tD - 32 * (m0 + i)), "r"(m0 + i + wiw) : "memory");
                }
                #pragma unroll
                for (int i = 0; i < 4; i++) {
                    asm volatile("mov.b32 %0, %1;" : "=r"(X[i][3]) : "r"(X[i][0]));
                    if (i < 3) asm volatile("mov.b32 %0, %1;" : "=r"(X[i + 1][2]) : "r"(X[i][1]));
                }
            };
            #pragma unroll 1
            for (int m0 = -3; m0 < 69; m0 += 8) {
                #pragma unroll
                for (int h = 0; h < 2; h++) {
                    load_set(A[h], m0 + 4 * h);
                    wg_fence();
                    #pragma unroll
                    for (int i = 0; i < 4; i++) wg_rs32(acc, A[h][i], uLo - 2 * (m0 + 4 * h + i));
                    wg_commit();
                    wg_wait<1>();
                }
            }
            bar_sync(1, 512);
            wg_wait<0>();
            fence_regs<16>(acc);
            PROF(6);
            {
                asm volatile("" : "+r"(sBl) :: "memory");
                const int mi = lane >> 3, r8 = lane & 7;
                const uint32_t frag = (16 * (8 * (mi >> 1) + r8) + 8 * (mi & 1)) * 2;
                const uint32_t t3 = sBl + S_TAB + c * TABN * 2 + (T3B + ((wiw & 1) ? (T3C + C3 + 1) : C3)) * 2 - (4 * g + wiw - 2 * t) * 2;
                #pragma unroll
                for (int s = 0; s < 2; s++) {
                    const uint32_t sig = swz(sBl + (s ? S_W7 : S_W9) + c * W3LEN * 2 + WPAD * 2 + frag - (s ? 16 : 32));
                    uint32_t a[4][4], R[4][2];
                    #pragma unroll
                    for (int b = 0; b < 4; b++) ldsm4t_p(a[b], sig + b * 512);
                    #pragma unroll
                    for (int i = 0; i < 4; i++) { R[i][0] = lds32_p(t3 + s * (T3S * 2) - 2 * (48 + 16 * i)); R[i][1] = lds32_p(t3 + s * (T3S * 2) - 2 * (40 + 16 * i)); }
                    #pragma unroll
                    for (int b = 0; b < 4; b++) {
                        mma_bf16_p(acc + 12, a[b][0], a[b][1], a[b][2], a[b][3], R[3 - b][0], R[3 - b][1]);
                        if (b < 2) mma_bf16_p(acc + 8, a[b][0], a[b][1], a[b][2], a[b][3], R[1 - b][0], R[1 - b][1]);
                    }
                }
            }
            __nv_bfloat16* ys = (__nv_bfloat16*)(sB + S_Y + c * 4096) + 128 * t + 16 * wiw + g;
            #pragma unroll
            for (int j = 0; j < 4; j++) {
                ys[512 * j] = __float2bfloat16_rn(acc[4 * j]);
                ys[512 * j + 64] = __float2bfloat16_rn(acc[4 * j + 1]);
                ys[512 * j + 8] = __float2bfloat16_rn(acc[4 * j + 2]);
                ys[512 * j + 72] = __float2bfloat16_rn(acc[4 * j + 3]);
            }
        }
        bar_arrive(10, 608);
        PROF(7);
        {
            mbar_wait(bars + 8 * B_ST, 0);
            PROF(9); PROFC(8);
            float qm = 0.0f;
            #pragma unroll
            for (int i = 0; i < 16; i++) qm = fmaxf(qm, s_misc[i]);
            const float vm = s_misc[17];
            const bool fast = (qm * s_misc[16] <= 60.0f * 60.0f) && (vm <= 1.0e12f) && (vm >= 1.0e-12f || vm == 0.0f);
            uint8_t* ob = g_oimg + qb * 131072 + hg * 16384 + nh * 8192 + (rowhalf * 8 + wiw * 2) * 128 + g * 16 + 4 * t;
            uint32_t cA = 0xBF00BF00u, cB = 0x00030003u;
            asm volatile("" : "+r"(cA), "+r"(cB));
            #pragma unroll 1
            for (int tile = 0; tile < 2; tile++) {
                uint32_t kLo = (((sb + SM_K) & 0x3FFFF) >> 4) | (8u << 16), vLo = (((sb + SM_V) & 0x3FFFF) >> 4) | (8u << 16), vHi = 2048;
                float o[12], s[32];
                uint32_t p[16], qq[4];
                #pragma unroll
                for (int i = 0; i < 4; i++) { qq[i] = tile ? q[1][i] : q[0][i]; asm volatile("" : "+r"(qq[i])); }
                #pragma unroll
                for (int i = 0; i < 12; i++) o[i] = 0.0f;
                #pragma unroll
                for (int i = 0; i < 32; i++) s[i] = 0.0f;
                fence_regs<12>(o);
                fence_regs<32>(s);
                if (fast) {
                    #pragma unroll 1
                    for (int c = 0; c < SEQ / 256; c++) {
                        if (c <= 4) mbar_wait(bars + 8 * (B_KV + (c < 2 ? c : c < 4 ? 2 : 3)), 0);
                        wg_fence();
                        wg_qk(s, qq, kLo);
                        wg_commit();
                        #pragma unroll
                        for (int u = 0; u < 4; u++) {
                            wg_wait<0>();
                            fence_regs<32>(s);
                            #pragma unroll
                            for (int i = 0; i < 16; i++) {
                                if ((MUFU_MASK >> i) & 1) p[i] = exp_mufu(s[2 * i], s[2 * i + 1]);
                                else p[i] = exp_sw(s[2 * i], s[2 * i + 1], cA, cB);
                            }
                            wg_fence();
                            if (u + 1 < 4) wg_qk(s, qq, kLo + (u + 1) * 128);
                            #pragma unroll
                            for (int kk = 0; kk < 4; kk++) wg_pv(o, p + 4 * kk, vLo + u * 64 + kk * 16, vHi - u * 64);
                            wg_commit();
                        }
                        kLo += 512; vLo += 256; vHi -= 256;
                    }
                    wg_wait<0>();
                } else {
                    float mx0 = -INFINITY, mx1 = -INFINITY;
                    #pragma unroll 1
                    for (int c = 0; c < SEQ / 64; c++) {
                        if (c <= 16) mbar_wait(bars + 8 * (B_KV + (c < 8 ? (c >> 2) : c < 16 ? 2 : 3)), 0);
                        wg_fence();
                        wg_qk(s, qq, kLo);
                        wg_commit();
                        wg_wait<0>();
                        fence_regs<32>(s);
                        fence_regs<12>(o);
                        float m0 = mx0, m1 = mx1;
                        #pragma unroll
                        for (int j = 0; j < 8; j++) {
                            m0 = fmaxf(m0, fmaxf(s[4 * j], s[4 * j + 1]));
                            m1 = fmaxf(m1, fmaxf(s[4 * j + 2], s[4 * j + 3]));
                        }
                        m0 = fmaxf(m0, __shfl_xor_sync(0xffffffffu, m0, 1)); m0 = fmaxf(m0, __shfl_xor_sync(0xffffffffu, m0, 2));
                        m1 = fmaxf(m1, __shfl_xor_sync(0xffffffffu, m1, 1)); m1 = fmaxf(m1, __shfl_xor_sync(0xffffffffu, m1, 2));
                        const float c0 = ex2f(mx0 - m0), c1 = ex2f(mx1 - m1);
                        mx0 = m0; mx1 = m1;
                        #pragma unroll
                        for (int j = 0; j < 3; j++) { o[4 * j] *= c0; o[4 * j + 1] *= c0; o[4 * j + 2] *= c1; o[4 * j + 3] *= c1; }
                        #pragma unroll
                        for (int j = 0; j < 8; j++) {
                            p[2 * j] = exp_mufu(s[4 * j] - m0, s[4 * j + 1] - m0);
                            p[2 * j + 1] = exp_mufu(s[4 * j + 2] - m1, s[4 * j + 3] - m1);
                        }
                        wg_fence();
                        #pragma unroll
                        for (int kk = 0; kk < 4; kk++) wg_pv(o, p + 4 * kk, vLo + kk * 16, vHi);
                        wg_commit();
                        wg_wait<0>();
                        kLo += 128; vLo += 64; vHi -= 64;
                    }
                }
                fence_regs<12>(o);
                if (tile == 0) PROFC(3);
                const float i0 = 1.0f / o[4], i1 = 1.0f / o[6];
                uint8_t* b = ob + tile * 4096;
                *(uint32_t*)(b) = pack_bf16(o[0] * i0, o[1] * i0);
                *(uint32_t*)(b + 128) = pack_bf16(o[2] * i1, o[3] * i1);
                *(uint32_t*)(b + 2048) = pack_bf16(o[8] * i0, o[9] * i0);
                *(uint32_t*)(b + 2048 + 128) = pack_bf16(o[10] * i1, o[11] * i1);
            }
        }
        PROF(10); PROFC(9);
        bar_arrive(12, 544);

        if (wg < 2) {
            float acc[32];
            #pragma unroll
            for (int i = 0; i < 32; i++) acc[i] = 0.0f;
            fence_regs<32>(acc);
            const uint64_t dA = make_desc(sb + SM_A + rowhalf * 1024, 2048, 128, 0);
            const uint64_t dB = make_desc(sb + SM_B, 16, 1024, 1);
            mbar_wait(bars + 8 * B_WO, 0);
            #pragma unroll 1
            for (int i = 0; i < 8; i++) {
                const int src = ((hg & 6) + i) & 7;
                mbar_wait(bars + 8 * (B_O + src), 0);
                wg_fence();
                #pragma unroll
                for (int kk = 0; kk < 4; kk++) wg_ss64(acc, dA + src * 1024 + kk * 256, dB + (src * 4 + kk) * 128);
                wg_commit();
            }
            wg_wait<0>();
            fence_regs<32>(acc);
            PROF(12);
            const int row = qb * 128 + rowhalf * 64 + wiw * 16 + g;
            uint32_t* o32 = (uint32_t*)(P.out + (size_t)row * 1024 + hg * 64 + 2 * t);
            #pragma unroll
            for (int j = 0; j < 8; j++) {
                o32[4 * j] = pack_bf16(acc[4 * j], acc[4 * j + 1]);
                o32[4 * j + 8 * 512] = pack_bf16(acc[4 * j + 2], acc[4 * j + 3]);
            }
        }
        PROF(13);
    }
}

typedef CUresult (*EncodeFn)(CUtensorMap*, CUtensorMapDataType, cuuint32_t, void*, const cuuint64_t*, const cuuint64_t*,
                             const cuuint32_t*, const cuuint32_t*, CUtensorMapInterleave, CUtensorMapSwizzle,
                             CUtensorMapL2promotion, CUtensorMapFloatOOBfill);

void make_map(EncodeFn fn, CUtensorMap* m, const void* ptr, uint64_t inner, uint64_t outer, uint32_t box_in, uint32_t box_out, CUtensorMapSwizzle swz) {
    cuuint64_t dims[2] = {inner, outer};
    cuuint64_t strides[1] = {inner * 2};
    cuuint32_t box[2] = {box_in, box_out};
    cuuint32_t es[2] = {1, 1};
    fn(m, CU_TENSOR_MAP_DATA_TYPE_BFLOAT16, 2, const_cast<void*>(ptr), dims, strides, box, es, CU_TENSOR_MAP_INTERLEAVE_NONE, swz,
       CU_TENSOR_MAP_L2_PROMOTION_L2_128B, CU_TENSOR_MAP_FLOAT_OOB_FILL_NONE);
}

}

extern "C" void kernel_launch(void* const* d_in, const int* in_sizes, int n_in, void* d_out, int out_size) {
    (void)in_sizes; (void)n_in; (void)out_size;
    static EncodeFn fn = nullptr;
    if (!fn) {
        void* p = nullptr;
        cudaDriverEntryPointQueryResult qr;
        cudaGetDriverEntryPoint("cuTensorMapEncodeTiled", &p, cudaEnableDefault, &qr);
        fn = (EncodeFn)p;
        cudaFuncSetAttribute(fused_kernel, cudaFuncAttributeMaxDynamicSharedMemorySize, SM_ALLOC);
    }
    CUtensorMap tx, twq, two, twk, twv, tu;
    {
        cuuint64_t dims[3] = {64, 2048, 8};
        cuuint64_t strides[2] = {1024, 128};
        cuuint32_t box[3] = {64, 128, 4};
        cuuint32_t es[3] = {1, 1, 1};
        fn(&tx, CU_TENSOR_MAP_DATA_TYPE_BFLOAT16, 3, d_in[0], dims, strides, box, es, CU_TENSOR_MAP_INTERLEAVE_NONE, CU_TENSOR_MAP_SWIZZLE_128B,
           CU_TENSOR_MAP_L2_PROMOTION_L2_128B, CU_TENSOR_MAP_FLOAT_OOB_FILL_NONE);
    }
    make_map(fn, &tu, d_in[5], 512, 2048, 8, 256, CU_TENSOR_MAP_SWIZZLE_NONE);
    make_map(fn, &twq, d_in[1], 512, 512, 64, 256, CU_TENSOR_MAP_SWIZZLE_128B);
    make_map(fn, &twk, d_in[2], 16, 512, 8, 256, CU_TENSOR_MAP_SWIZZLE_NONE);
    make_map(fn, &twv, d_in[3], 16, 512, 8, 256, CU_TENSOR_MAP_SWIZZLE_NONE);
    make_map(fn, &two, d_in[4], 512, 512, 64, 256, CU_TENSOR_MAP_SWIZZLE_128B);
    Params P;
    P.u = (const __nv_bfloat16*)d_in[5];
    P.lar = (const __nv_bfloat16*)d_in[6];
    P.aim = (const __nv_bfloat16*)d_in[7];
    P.cre = (const __nv_bfloat16*)d_in[8];
    P.cim = (const __nv_bfloat16*)d_in[9];
    P.logdt = (const __nv_bfloat16*)d_in[10];
    P.dskip = (const __nv_bfloat16*)d_in[11];
    P.out = (__nv_bfloat16*)d_out;
    fused_kernel<<<NCTA, NTHR, SM_ALLOC>>>(tx, twq, two, twk, twv, tu, P);
}
```

```cpp
#include <cuda_runtime.h>
#include <cuda_bf16.h>
#include <cuda_fp16.h>
#include <cuda.h>
#include <stdint.h>

namespace {

constexpr int SEQ = 2048;
constexpr int NCTA = 128, NTHR = 640;

constexpr int SM_A = 0;
constexpr int SM_WQ = 65536;
constexpr int SM_SLAB = SM_WQ + 32768;
constexpr int SM_K = 0, SM_V = 65536;
constexpr int SM_B = 132096;
constexpr int SM_WKV = SM_B + 65536;

constexpr int PADU = 1536, ULEN = PADU + 2048;
constexpr int WPAD = 16, W3LEN = WPAD + 1024;
constexpr int TABN = 2592;
constexpr int S_U = 0;
constexpr int S_W7 = S_U + 4 * ULEN * 2;
constexpr int S_W9 = S_W7 + 4 * W3LEN * 2;
constexpr int S_TAB = S_W9 + 4 * W3LEN * 2;
constexpr int S_QX = S_TAB + 4 * TABN * 2;
constexpr int S_KC = 214016 - SM_B;
constexpr int S_Y = S_KC;
constexpr int SM_BAR = SM_B + S_KC + 16384;
constexpr int SM_TOTAL = SM_BAR + 1024;
constexpr int SM_ALLOC = SM_TOTAL + 1024;
static_assert(SM_V + 65536 + 1024 <= SM_B && SM_ALLOC <= 232448 && S_QX + 8192 <= S_KC && SM_WKV + 16384 <= SM_B + S_KC, "smem map");

constexpr int TD0 = 0, TD1 = 1072, CD = 1056;
constexpr int T3B = 2144, T3S = 224, T3C = 112, C3 = 136;

constexpr int rne8(int t) {
    if (t < 256) return t;
    int sh = 0;
    while ((t >> sh) >= 256) sh++;
    int q = t >> sh, rem = t & ((1 << sh) - 1), half = 1 << (sh - 1);
    if (rem > half || (rem == half && (q & 1))) q++;
    return q << sh;
}
constexpr int kcidx(int p) {
    if (p < 256) return (p >> 3) * 24 + (p & 7);
    if (p < 512) return ((p - 256) >> 3) * 24 + 8 + (((p - 256) & 7) >> 1);
    if (p < 1024) { int q = p - 512, hi = q >> 8, rem = q & 255; return (rem >> 3) * 24 + 12 + 2 * hi + ((rem & 7) >> 2); }
    if (p < 2048) { int q = p - 1024; return ((q & 255) >> 3) * 24 + 16 + (q >> 8); }
    return 20;
}
constexpr int KC_ZERO = 23;
constexpr int tab_dense(int t) { return (t >= 0 && t <= 1028) ? kcidx(rne8(t)) : KC_ZERO; }
constexpr int tab_3(int s, int lag) { return (lag >= 64 && lag <= 127) ? kcidx(s == 0 ? 16 * (lag + 1) : 16 * lag + 8) : KC_ZERO; }
struct TabMap {
    uint16_t v[TABN];
    constexpr TabMap() : v{} {
        for (int i = 0; i < TD1; i++) { v[TD0 + i] = tab_dense(CD - i); v[TD1 + i] = tab_dense(CD + 1 - i); }
        for (int s = 0; s < 2; s++)
            for (int i = 0; i < T3C; i++) { v[T3B + s * T3S + i] = tab_3(s, C3 - i); v[T3B + s * T3S + T3C + i] = tab_3(s, C3 + 1 - i); }
    }
};
__device__ const __align__(16) TabMap g_tabmap = TabMap();

__device__ __align__(1024) uint8_t g_kimg[65536];
__device__ __align__(1024) uint8_t g_vimg[65536 + 1024];
__device__ __align__(1024) uint8_t g_oimg[16 * 131072];
__device__ unsigned long long g_flag_kv[64];
__device__ unsigned g_flag_o[128];
__device__ unsigned g_epoch;
__device__ unsigned g_done;

#define PROF(i) do {} while (0)
#define PROF2(i) do {} while (0)
#define PROFC(i) do {} while (0)
#define PROF3(i) do {} while (0)

__device__ __forceinline__ uint32_t smem_u32(const void* p) { return (uint32_t)__cvta_generic_to_shared(p); }
__device__ __forceinline__ void mbar_init(uint32_t bar, uint32_t cnt) { asm volatile("mbarrier.init.shared::cta.b64 [%0], %1;" :: "r"(bar), "r"(cnt) : "memory"); }
__device__ __forceinline__ void mbar_expect_tx(uint32_t bar, uint32_t bytes) {
    asm volatile("mbarrier.arrive.expect_tx.shared::cta.b64 _, [%0], %1;" :: "r"(bar), "r"(bytes) : "memory"); }
__device__ __forceinline__ void mbar_wait(uint32_t bar, uint32_t parity) {
    uint32_t ok = 0;
    for (int it = 0; it < (1 << 22) && !ok; it++) {
        asm volatile("{ .reg .pred p; mbarrier.try_wait.parity.shared::cta.b64 p, [%1], %2; selp.u32 %0, 1, 0, p; }"
                     : "=r"(ok) : "r"(bar), "r"(parity) : "memory");
    }
}
__device__ __forceinline__ void tma_2d(uint32_t dst, const CUtensorMap* map, int c0, int c1, uint32_t bar) {
    asm volatile("cp.async.bulk.tensor.2d.shared::cluster.global.mbarrier::complete_tx::bytes [%0], [%1, {%3, %4}], [%2];"
                 :: "r"(dst), "l"((uint64_t)map), "r"(bar), "r"(c0), "r"(c1) : "memory");
}
__device__ __forceinline__ void tma_2d_mc(uint32_t dst, const CUtensorMap* map, int c0, int c1, uint32_t bar) {
    asm volatile("cp.async.bulk.tensor.2d.shared::cluster.global.mbarrier::complete_tx::bytes.multicast::cluster [%0], [%1, {%3, %4}], [%2], %5;"
                 :: "r"(dst), "l"((uint64_t)map), "r"(bar), "r"(c0), "r"(c1), "h"((uint16_t)3) : "memory");
}
__device__ __forceinline__ void bulk_g2s_mc(uint32_t dst, const void* src, uint32_t bytes, uint32_t bar) {
    asm volatile("cp.async.bulk.shared::cluster.global.mbarrier::complete_tx::bytes.multicast::cluster [%0], [%1], %2, [%3], %4;"
                 :: "r"(dst), "l"((uint64_t)src), "r"(bytes), "r"(bar), "h"((uint16_t)3) : "memory");
}
__device__ __forceinline__ void pair_sync(uint32_t bar, uint32_t peer) {
    uint32_t ra;
    asm volatile("mapa.shared::cluster.u32 %0, %1, %2;" : "=r"(ra) : "r"(bar), "r"(peer));
    asm volatile("mbarrier.arrive.shared::cluster.b64 _, [%0];" :: "r"(ra) : "memory");
    asm volatile("mbarrier.arrive.shared::cta.b64 _, [%0];" :: "r"(bar) : "memory");
    uint32_t ok = 0;
    for (int it = 0; it < (1 << 22) && !ok; it++) {
        asm volatile("{ .reg .pred p; mbarrier.try_wait.parity.shared::cta.b64 p, [%1], 0; selp.u32 %0, 1, 0, p; }"
                     : "=r"(ok) : "r"(bar) : "memory");
    }
}
__device__ __forceinline__ void fence_async_all() { asm volatile("fence.proxy.async.global;" ::: "memory"); }
__device__ __forceinline__ void fence_async_smem() { asm volatile("fence.proxy.async.shared::cta;" ::: "memory"); }
__device__ __forceinline__ unsigned ld_acquire(const unsigned* p) {
    unsigned v; asm volatile("ld.acquire.gpu.global.u32 %0, [%1];" : "=r"(v) : "l"(p) : "memory"); return v; }
__device__ __forceinline__ void st_release(unsigned* p, unsigned v) { asm volatile("st.release.gpu.global.u32 [%0], %1;" :: "l"(p), "r"(v) : "memory"); }
__device__ __forceinline__ void wait_flag(const unsigned* p, unsigned epoch) {
    for (int it = 0; it < (1 << 22); it++) { if (ld_acquire(p) == epoch) break; }
}
__device__ __forceinline__ unsigned long long ld_acquire64(const unsigned long long* p) {
    unsigned long long v; asm volatile("ld.acquire.gpu.global.u64 %0, [%1];" : "=l"(v) : "l"(p) : "memory"); return v; }
__device__ __forceinline__ void st_release64(unsigned long long* p, unsigned long long v) { asm volatile("st.release.gpu.global.u64 [%0], %1;" :: "l"(p), "l"(v) : "memory"); }
__device__ __forceinline__ float wait_flag64(const unsigned long long* p, unsigned epoch) {
    unsigned long long v = 0;
    for (int it = 0; it < (1 << 22); it++) { v = ld_acquire64(p); if ((unsigned)(v >> 32) == epoch) break; }
    return __uint_as_float((unsigned)v);
}
__device__ __forceinline__ void tma_3d_mc(uint32_t dst, const CUtensorMap* map, int c0, int c1, int c2, uint32_t bar) {
    asm volatile("cp.async.bulk.tensor.3d.shared::cluster.global.mbarrier::complete_tx::bytes.multicast::cluster [%0], [%1, {%3, %4, %5}], [%2], %6;"
                 :: "r"(dst), "l"((uint64_t)map), "r"(bar), "r"(c0), "r"(c1), "r"(c2), "h"((uint16_t)3) : "memory");
}
__device__ __forceinline__ void bar_sync(int id, int n) { asm volatile("bar.sync %0, %1;" :: "r"(id), "r"(n) : "memory"); }
__device__ __forceinline__ void bar_arrive(int id, int n) { asm volatile("bar.arrive %0, %1;" :: "r"(id), "r"(n) : "memory"); }
__device__ __forceinline__ void mbar_arrive(uint32_t bar) { asm volatile("mbarrier.arrive.shared::cta.b64 _, [%0];" :: "r"(bar) : "memory"); }

__device__ __forceinline__ uint64_t make_desc(uint32_t saddr, uint32_t lbo, uint32_t sbo, uint32_t swz) {
    uint64_t d = 0;
    d |= (uint64_t)((saddr & 0x3FFFF) >> 4);
    d |= (uint64_t)((lbo >> 4) & 0x3FFF) << 16;
    d |= (uint64_t)((sbo >> 4) & 0x3FFF) << 32;
    d |= (uint64_t)swz << 62;
    return d;
}
__device__ __forceinline__ void wg_fence() { asm volatile("wgmma.fence.sync.aligned;" ::: "memory"); }
__device__ __forceinline__ void wg_commit() { asm volatile("wgmma.commit_group.sync.aligned;" ::: "memory"); }
template<int N> __device__ __forceinline__ void wg_wait() { asm volatile("wgmma.wait_group.sync.aligned %0;" :: "n"(N) : "memory"); }
#define A4(d, o) "+f"(d[o + 0]), "+f"(d[o + 1]), "+f"(d[o + 2]), "+f"(d[o + 3])
#define A16(d, o) A4(d, o), A4(d, o + 4), A4(d, o + 8), A4(d, o + 12)

__device__ __forceinline__ void wg_pv(float* d, const uint32_t* a, uint32_t lo, uint32_t hi) {
    asm volatile("{ .reg .b64 dd; mov.b64 dd, {%16, %17};\n"
                 "wgmma.mma_async.sync.aligned.m64n24k16.f32.bf16.bf16 {%0,%1,%2,%3,%4,%5,%6,%7,%8,%9,%10,%11}, {%12,%13,%14,%15}, dd, 1, 1, 1, 1; }"
                 : A4(d, 0), A4(d, 4), A4(d, 8) : "r"(a[0]), "r"(a[1]), "r"(a[2]), "r"(a[3]), "r"(lo), "r"(hi));
}
__device__ __forceinline__ void wg_qk(float* d, const uint32_t* a, uint32_t lo) {
    asm volatile("{ .reg .b64 dd; mov.b64 dd, {%36, %37};\n"
                 "wgmma.mma_async.sync.aligned.m64n64k16.f32.bf16.bf16 {%0,%1,%2,%3,%4,%5,%6,%7,%8,%9,%10,%11,%12,%13,%14,%15,%16,%17,%18,%19,%20,%21,%22,%23,%24,%25,%26,%27,%28,%29,%30,%31}, {%32,%33,%34,%35}, dd, 0, 1, 1, 0; }"
                 : A16(d, 0), A16(d, 16) : "r"(a[0]), "r"(a[1]), "r"(a[2]), "r"(a[3]), "r"(lo), "r"(16));
}
__device__ __forceinline__ void wg_rs32(float* d, const uint32_t* a, uint32_t lo) {
    asm volatile("{ .reg .b64 dd; mov.b64 dd, {%20, %21};\n"
                 "wgmma.mma_async.sync.aligned.m64n32k16.f32.bf16.bf16 {%0,%1,%2,%3,%4,%5,%6,%7,%8,%9,%10,%11,%12,%13,%14,%15}, {%16,%17,%18,%19}, dd, 1, 1, 1, 0; }"
                 : A16(d, 0) : "r"(a[0]), "r"(a[1]), "r"(a[2]), "r"(a[3]), "r"(lo), "r"(0x40000040));
}
__device__ __forceinline__ void wg_ss64(float* d, uint64_t da, uint64_t db) {
    asm volatile("wgmma.mma_async.sync.aligned.m64n64k16.f32.bf16.bf16 {%0,%1,%2,%3,%4,%5,%6,%7,%8,%9,%10,%11,%12,%13,%14,%15,%16,%17,%18,%19,%20,%21,%22,%23,%24,%25,%26,%27,%28,%29,%30,%31}, %32, %33, 1, 1, 1, 0, 1;"
                 : A16(d, 0), A16(d, 16) : "l"(da), "l"(db));
}
__device__ __forceinline__ void wg_ss16(float* d, uint64_t da, uint64_t db) {
    asm volatile("wgmma.mma_async.sync.aligned.m64n16k16.f32.bf16.bf16 {%0,%1,%2,%3,%4,%5,%6,%7}, %8, %9, 1, 1, 1, 0, 1;"
                 : A4(d, 0), A4(d, 4) : "l"(da), "l"(db));
}
template<int N> __device__ __forceinline__ void fence_regs(float* r) {
    #pragma unroll
    for (int i = 0; i < N; i++) asm volatile("" : "+f"(r[i]) :: "memory");
}
__device__ __forceinline__ void mma_f16(float* d, const uint32_t* a, uint32_t b0, uint32_t b1) {
    asm volatile("mma.sync.aligned.m16n8k16.row.col.f32.f16.f16.f32 {%0,%1,%2,%3}, {%4,%5,%6,%7}, {%8,%9}, {%0,%1,%2,%3};"
                 : "+f"(d[0]), "+f"(d[1]), "+f"(d[2]), "+f"(d[3]) : "r"(a[0]), "r"(a[1]), "r"(a[2]), "r"(a[3]), "r"(b0), "r"(b1));
}
__device__ __forceinline__ uint32_t lds32(uint32_t addr) { uint32_t v; asm volatile("ld.shared.u32 %0, [%1];" : "=r"(v) : "r"(addr) : "memory"); return v; }
__device__ __forceinline__ void mma_bf16_p(float* d, uint32_t a0, uint32_t a1, uint32_t a2, uint32_t a3, uint32_t b0, uint32_t b1) {
    asm("mma.sync.aligned.m16n8k16.row.col.f32.bf16.bf16.f32 {%0,%1,%2,%3}, {%4,%5,%6,%7}, {%8,%9}, {%0,%1,%2,%3};"
        : "+f"(d[0]), "+f"(d[1]), "+f"(d[2]), "+f"(d[3]) : "r"(a0), "r"(a1), "r"(a2), "r"(a3), "r"(b0), "r"(b1));
}
__device__ __forceinline__ void ldsm4t_p(uint32_t* r, uint32_t addr) {
    asm("ldmatrix.sync.aligned.m8n8.x4.trans.shared.b16 {%0,%1,%2,%3}, [%4];" : "=r"(r[0]), "=r"(r[1]), "=r"(r[2]), "=r"(r[3]) : "r"(addr));
}
__device__ __forceinline__ uint32_t lds32_p(uint32_t addr) { uint32_t v; asm("ld.shared.u32 %0, [%1];" : "=r"(v) : "r"(addr)); return v; }
__device__ __forceinline__ uint32_t swz(uint32_t a) { return a ^ ((a >> 3) & 16u); }
__device__ __forceinline__ uint32_t swz128(uint32_t a) { return a ^ ((a >> 3) & 0x70u); }
__device__ __forceinline__ void sts32(uint32_t addr, uint32_t v) { asm volatile("st.shared.u32 [%0], %1;" :: "r"(addr), "r"(v) : "memory"); }
__device__ __forceinline__ void sts128(uint32_t addr, uint4 v) { asm volatile("st.shared.v4.u32 [%0], {%1,%2,%3,%4};" :: "r"(addr), "r"(v.x), "r"(v.y), "r"(v.z), "r"(v.w) : "memory"); }
__device__ __forceinline__ uint4 lds128(uint32_t addr) { uint4 v; asm volatile("ld.shared.v4.u32 {%0,%1,%2,%3}, [%4];" : "=r"(v.x), "=r"(v.y), "=r"(v.z), "=r"(v.w) : "r"(addr) : "memory"); return v; }
__device__ __forceinline__ void quad_transpose(uint32_t* v, int t) {
    #pragma unroll
    for (int p = 0; p < 2; p++) {
        const uint32_t x = __shfl_xor_sync(0xffffffffu, (t & 1) ? v[2 * p] : v[2 * p + 1], 1);
        if (t & 1) v[2 * p] = x; else v[2 * p + 1] = x;
    }
    #pragma unroll
    for (int p = 0; p < 2; p++) {
        const uint32_t x = __shfl_xor_sync(0xffffffffu, (t & 2) ? v[p] : v[p + 2], 2);
        if (t & 2) v[p] = x; else v[p + 2] = x;
    }
}
__device__ __forceinline__ float ex2f(float x) { float r; asm("ex2.approx.ftz.f32 %0, %1;" : "=f"(r) : "f"(x)); return r; }
__device__ __forceinline__ uint32_t pack_bf16(float lo, float hi) { uint32_t r; asm("cvt.rn.bf16x2.f32 %0, %1, %2;" : "=r"(r) : "f"(hi), "f"(lo)); return r; }
__device__ __forceinline__ uint32_t pack_f16(float lo, float hi) { uint32_t r; asm("cvt.rn.f16x2.f32 %0, %1, %2;" : "=r"(r) : "f"(hi), "f"(lo)); return r; }
__device__ __forceinline__ float bf_lo(uint32_t v) { return __uint_as_float(v << 16); }
__device__ __forceinline__ float bf_hi(uint32_t v) { return __uint_as_float(v & 0xFFFF0000u); }
__device__ __forceinline__ float bf_round(float x) { return __bfloat162float(__float2bfloat16_rn(x)); }

__device__ __forceinline__ uint32_t exp_mufu(float x0, float x1) { return pack_bf16(ex2f(x0), ex2f(x1)); }
#define SW_MAGIC (256.0f + 127.0f - 0.598938f)
__device__ __forceinline__ uint32_t exp_sw(float x0, float x1, uint32_t cA, uint32_t cB) {
    float t0 = x0 + SW_MAGIC, t1 = x1 + SW_MAGIC;
    uint32_t L, mh, ec, r;
    asm("prmt.b32 %0, %1, %2, 0x6521;" : "=r"(L) : "r"(__float_as_uint(t0)), "r"(__float_as_uint(t1)));
    asm("lop3.b32 %0, %1, 0x007F007F, %2, 0xEA;" : "=r"(mh) : "r"(L), "r"(cA));
    asm("lop3.b32 %0, %1, 0x7F807F80, %2, 0xEA;" : "=r"(ec) : "r"(L), "r"(cB));
    asm("fma.rn.bf16x2 %0, %1, %2, %3;" : "=r"(r) : "r"(L), "r"(mh), "r"(ec));
    return r;
}
constexpr uint32_t MUFU_MASK = 0x4949;

struct cf { float x, y; };
__device__ __forceinline__ cf cmul(cf a, cf b) { cf r; r.x = a.x * b.x - a.y * b.y; r.y = a.x * b.y + a.y * b.x; return r; }
__device__ __forceinline__ cf cexp_p(float a2, float b, float p) {
    float e = ex2f(a2 * p);
    float ph = b * p;
    ph -= (ph + 12582912.0f) - 12582912.0f;
    float ang = ph * 6.283185307f;
    cf r; r.x = e * __cosf(ang); r.y = e * __sinf(ang);
    return r;
}
__device__ __forceinline__ uint32_t h2_cmul(uint32_t w, uint32_t wsw, uint32_t e) {
    __half2 hw = *(__half2*)&w, hs = *(__half2*)&wsw, he = *(__half2*)&e;
    __half2 r = __hfma2(hs, __high2half2(he), __hmul2(hw, __low2half2(he)));
    return *(uint32_t*)&r;
}

template<bool B> struct BoolC { static constexpr bool value = B; };
struct Params {
    const __nv_bfloat16 *u, *lar, *aim, *cre, *cim, *logdt, *dskip;
    __nv_bfloat16* out;
};

constexpr int B_O = 0, B_KV = 8, B_WO = 12, B_WQ2 = 13, B_ST = 14, B_H = 15, B_X = 17, B_U = 19, B_WQ = 20;

__device__ __forceinline__ void helper_role(const Params& P, uint8_t* sp, uint32_t sb, unsigned epoch) {
    const uint32_t sBa = sb + SM_B;
    const int tid = threadIdx.x - 544;
    const int d0 = blockIdx.x * 4;
    uint8_t* sB = sp + SM_B;
    const uint2 dsk = __ldg((const uint2*)(P.dskip + d0));
    asm volatile("barrier.cluster.wait.aligned;" ::: "memory");
    {
        const int hg = blockIdx.x & 7;
        if (hg < 4 && tid < 32) {
            bar_sync(3, 160);
            if (tid == 0) {
                const float* s_misc = (const float*)(sp + SM_BAR + 256);
                const float st = fmaxf(fmaxf(s_misc[20], s_misc[21]), fmaxf(s_misc[22], s_misc[23]));
                st_release64(&g_flag_kv[((blockIdx.x >> 3) * 2 + (hg & 1)) * 2 + (hg >> 1)], ((unsigned long long)epoch << 32) | __float_as_uint(st));
            }
            __syncwarp();
        }
    }
    PROF2(2);
    bar_sync(10, 608);
    {
        uint32_t dd[4] = {__byte_perm(dsk.x, 0, 0x1010), __byte_perm(dsk.x, 0, 0x3232), __byte_perm(dsk.y, 0, 0x1010), __byte_perm(dsk.y, 0, 0x3232)};
        #pragma unroll 2
        for (int pi = tid; pi < 1024; pi += 96) {
            const int l = 2 * pi;
            uint32_t r[4];
            #pragma unroll
            for (int cc = 0; cc < 4; cc++) {
                const uint32_t y2 = *(const uint32_t*)(sB + S_Y + cc * 4096 + l * 2);
                const uint32_t u2 = lds32(swz128(sBa + S_U + cc * ULEN * 2 + (PADU + l) * 2));
                __nv_bfloat162 pr = __hmul2(*(const __nv_bfloat162*)&u2, *(const __nv_bfloat162*)&dd[cc]);
                __nv_bfloat162 sm = __hadd2(*(const __nv_bfloat162*)&y2, pr);
                r[cc] = *(uint32_t*)&sm;
            }
            *(uint2*)(P.out + (size_t)l * 1024 + 512 + d0) = make_uint2(__byte_perm(r[0], r[1], 0x5410), __byte_perm(r[2], r[3], 0x5410));
            *(uint2*)(P.out + (size_t)(l + 1) * 1024 + 512 + d0) = make_uint2(__byte_perm(r[0], r[1], 0x7632), __byte_perm(r[2], r[3], 0x7632));
        }
    }
    bar_arrive(11, 128);
    PROF2(4);
}

__global__ void __cluster_dims__(2, 1, 1) __launch_bounds__(NTHR, 1)
fused_kernel(const __grid_constant__ CUtensorMap tm_x, const __grid_constant__ CUtensorMap tm_wq,
             const __grid_constant__ CUtensorMap tm_wo, const __grid_constant__ CUtensorMap tm_wk,
             const __grid_constant__ CUtensorMap tm_wv, const __grid_constant__ CUtensorMap tm_u, const Params P) {
    extern __shared__ uint8_t smem_raw[];
    const uint32_t sb = (smem_u32(smem_raw) + 1023u) & ~1023u;
    uint8_t* sp = smem_raw + (sb - smem_u32(smem_raw));

    const int tid = threadIdx.x, warp = tid >> 5, lane = tid & 31, wg = tid >> 7, wiw = warp & 3;
    const int g = lane >> 2, t = lane & 3;
    const int qb = blockIdx.x >> 3, hg = blockIdx.x & 7;
    const uint32_t rank = blockIdx.x & 1;
    const int rowhalf = wg & 1, nh = wg >> 1;
    const bool kv_cta = hg < 4;
    const int kv_sel = hg >> 1;
    const bool kv_wg = kv_cta && (wg == 2 + (hg & 1));

    const uint32_t bars = sb + SM_BAR;
    float* s_misc = (float*)(sp + SM_BAR + 256);
    const CUtensorMap* tm_kv = kv_sel ? &tm_wv : &tm_wk;

    PROF(0);
    unsigned short p_lar = 0, p_aim = 0, p_cre = 0, p_cim = 0, p_ldt = 0;
    if (wg < 4) {
        const int n = (blockIdx.x * 4 + wg) * 128 + (tid & 127);
        p_lar = __ldg((const unsigned short*)P.lar + n);
        p_aim = __ldg((const unsigned short*)P.aim + n);
        p_cre = __ldg((const unsigned short*)P.cre + n);
        p_cim = __ldg((const unsigned short*)P.cim + n);
        p_ldt = __ldg((const unsigned short*)P.logdt + blockIdx.x * 4 + wg);
    } else if (warp == 16) {
        PROF3(5);
        if (lane == 0) {
            asm volatile("prefetch.tensormap [%0];" :: "l"((uint64_t)&tm_x) : "memory");
            asm volatile("prefetch.tensormap [%0];" :: "l"((uint64_t)tm_kv) : "memory");
            asm volatile("prefetch.tensormap [%0];" :: "l"((uint64_t)&tm_wq) : "memory");
            asm volatile("prefetch.tensormap [%0];" :: "l"((uint64_t)&tm_u) : "memory");
            mbar_init(bars + 8 * B_X, 1);
            mbar_init(bars + 8 * B_X + 8, 1);
            mbar_init(bars + 8 * B_U, 1);
            asm volatile("fence.mbarrier_init.release.cluster;" ::: "memory");
            mbar_expect_tx(bars + 8 * B_X, 65536u + (kv_cta ? 8192u : 0u));
            mbar_expect_tx(bars + 8 * B_X + 8, 65536u + (kv_cta ? 8192u : 0u));
            mbar_expect_tx(bars + 8 * B_U, 32768u);
        }
        __syncwarp();
        PROF3(6);
    }
    asm volatile("barrier.cluster.arrive.relaxed.aligned;" ::: "memory");
    const unsigned epoch = *(volatile unsigned*)&g_epoch + 1u;
    if (warp > 16) {
        if (lane == 0) {
            for (int i = warp - 17; i < B_X; i += 3) {
                mbar_init(bars + 8 * i, i >= B_H ? 2 : 1);
                if (i <= B_WQ2) mbar_expect_tx(bars + 8 * i, i < B_KV + 2 ? 16384u : i == B_KV + 2 ? 32768u : i <= B_WO ? 65536u : 32768u);
            }
            asm volatile("fence.mbarrier_init.release.cluster;" ::: "memory");
            fence_async_smem();
        } else if (warp == 19) {
            #pragma unroll
            for (int i = 0; i < 2; i++) if (lane - 1 + 31 * i < 41) asm volatile("prefetch.global.L2 [%0];" :: "l"((const char*)g_tabmap.v + (lane - 1 + 31 * i) * 128));
        }
        __syncwarp();
    }
    asm volatile("barrier.cluster.wait.aligned;" ::: "memory");
    PROF(5);
    if (warp == 16 && lane == 0) {
        tma_3d_mc(sb + (rank ? SM_A : SM_B), &tm_x, 0, qb * 128, rank * 4, bars + 8 * (B_X + rank));
        if (kv_cta) {
            #pragma unroll
            for (int i = 0; i < 4; i++) tma_2d(sb + SM_WKV + i * 4096, tm_kv, (i >> 1) * 8, (i & 1) * 256, bars + 8 * (B_X + (i & 1)));
        }
        mbar_init(bars + 8 * B_WQ, 1);
        asm volatile("fence.mbarrier_init.release.cluster;" ::: "memory");
        fence_async_smem();
        mbar_expect_tx(bars + 8 * B_WQ, 32768u);
        tma_2d(sb + SM_WQ, &tm_wq, hg * 64, 0, bars + 8 * B_WQ);
        #pragma unroll
        for (int i = 0; i < 4; i++) tma_2d_mc(sb + SM_SLAB + (rank * 4 + i) * 4096, &tm_u, (blockIdx.x >> 1) * 8, (rank * 4 + i) * 256, bars + 8 * B_U);
    }
    __syncwarp();
    asm volatile("barrier.cluster.arrive.relaxed.aligned;" ::: "memory");

    if (warp == 16) {
        if (lane == 0) asm volatile("prefetch.tensormap [%0];" :: "l"((uint64_t)&tm_wo) : "memory");
        asm volatile("barrier.cluster.wait.aligned;" ::: "memory");
        PROF3(10);
        bar_sync(13, 544);
        if (lane == 0) { fence_async_smem(); tma_2d(sb + SM_SLAB, &tm_wq, hg * 64, 256, bars + 8 * B_WQ2); }
        bar_sync(14, 288);
        if (lane == 0) pair_sync(bars + 8 * B_H, rank ^ 1);
        __syncwarp();
        PROF3(11);
        *(uint4*)(sp + SM_V + 32768 + lane * 32) = make_uint4(0x3F803F80u, 0x3F803F80u, 0x3F803F80u, 0x3F803F80u);
        *(uint4*)(sp + SM_V + 32768 + lane * 32 + 16) = make_uint4(0x3F803F80u, 0x3F803F80u, 0x3F803F80u, 0x3F803F80u);
        fence_async_smem();
        float km = wait_flag64(&g_flag_kv[2 * lane], epoch);
        float vm = wait_flag64(&g_flag_kv[2 * lane + 1], epoch);
        __syncwarp();
        PROF3(12);
        if (lane == 0) {
            fence_async_all();
            #pragma unroll
            for (int i = 0; i < 4; i++) {
                const uint32_t k0 = i == 0 ? 0 : 128u << i, nk = i == 0 ? 256 : 128u << i;
                const uint32_t bar = bars + 8 * (B_KV + i);
                if (rank == 0) bulk_g2s_mc(sb + SM_K + k0 * 32, g_kimg + k0 * 32, nk * 32, bar);
                else {
                    bulk_g2s_mc(sb + SM_V + k0 * 16, g_vimg + k0 * 16, nk * 16, bar);
                    bulk_g2s_mc(sb + SM_V + 66560 - (k0 + nk) * 16, g_vimg + 66560 - (k0 + nk) * 16, nk * 16, bar);
                }
            }
        }
        #pragma unroll
        for (int o = 16; o; o >>= 1) { km = fmaxf(km, __shfl_xor_sync(0xffffffffu, km, o)); vm = fmaxf(vm, __shfl_xor_sync(0xffffffffu, vm, o)); }
        if (lane == 0) { s_misc[16] = km; s_misc[17] = vm; mbar_arrive(bars + 8 * B_ST); }
        PROF3(13);
        bar_sync(11, 128);
        if (lane < 2) { fence_async_smem(); tma_2d(sb + SM_B + lane * 32768, &tm_wo, hg * 64, lane * 256, bars + 8 * B_WO); }
        bar_sync(12, 544);
        if (lane == 0) {
            st_release(&g_flag_o[blockIdx.x], epoch);
            pair_sync(bars + 8 * (B_H + 1), rank ^ 1);
        }
        __syncwarp();
        PROF3(14);
        if (lane < 4) {
            const int src = (2 * lane + (hg & 6) + rank) & 7;
            wait_flag(&g_flag_o[qb * 8 + src], epoch);
            fence_async_all();
            bulk_g2s_mc(sb + SM_A + src * 16384, g_oimg + qb * 131072 + src * 16384, 16384, bars + 8 * (B_O + src));
        }
        __syncwarp();
        PROF3(15);
        if (lane == 0) {
            const unsigned prev = atomicAdd(&g_done, 1u);
            if (prev == NCTA - 1) {
                g_done = 0;
                __threadfence();
                *(volatile unsigned*)&g_epoch = epoch;
            }
        }
    } else if (wg == 4) {
        helper_role(P, sp, sb, epoch);
    } else {
        uint8_t* sB = sp + SM_B;
        const uint32_t sBa = sb + SM_B;
        {
            const int c = wg;
            const float dt = bf_round(expf(bf_lo(p_ldt)));
            const float are = -bf_round(expf(bf_lo(p_lar))) * dt;
            const float aim = bf_lo(p_aim) * dt;
            float cr = 2.0f * (bf_lo(p_cre) * dt);
            float ci = 2.0f * (bf_lo(p_cim) * dt);
            const float a2 = are * 1.4426950408889634f, bb = aim * 0.15915494309189535f;
            float m = fmaxf(fabsf(cr), fabsf(ci));
            #pragma unroll
            for (int o = 16; o; o >>= 1) m = fmaxf(m, __shfl_xor_sync(0xffffffffu, m, o));
            int ebits = (__float_as_uint(m) >> 23) & 0xFF;
            ebits = min(max(ebits, 2), 250);
            const float scale = __uint_as_float((uint32_t)(ebits + 1) << 23);
            const float iscale = __uint_as_float((uint32_t)(253 - ebits) << 23);
            cf cc; cc.x = cr * iscale; cc.y = ci * iscale;

            const uint32_t stg = sBa + S_KC + warp * 1024;
            uint4* stp = (uint4*)(sB + S_KC + warp * 1024 + lane * 32);
            const uint32_t fa = stg + t * 32 + g * 4;

            uint32_t af[4][2][4];
            cf E256;
            {
                const cf E8 = cexp_p(a2, bb, 8.0f);
                uint32_t w[8];
                cf cur; cur.x = 1.0f; cur.y = 0.0f;
                w[0] = pack_f16(1.0f, 0.0f);
                cur = E8; w[1] = pack_f16(cur.x, cur.y);
                #pragma unroll
                for (int i = 2; i < 8; i++) { cur = cmul(cur, E8); w[i] = pack_f16(cur.x, cur.y); }
                stp[0] = make_uint4(w[0], w[1], w[2], w[3]);
                stp[1] = make_uint4(w[4], w[5], w[6], w[7]);
                const cf E64 = cexp_p(a2, bb, 64.0f);
                const cf E128 = cmul(E64, E64), E192 = cmul(E128, E64);
                E256 = cexp_p(a2, bb, 256.0f);
                const uint32_t e1 = pack_f16(E64.x, E64.y), e2 = pack_f16(E128.x, E128.y), e3 = pack_f16(E192.x, E192.y);
                __syncwarp();
                #pragma unroll
                for (int s = 0; s < 4; s++) {
                    #pragma unroll
                    for (int hh = 0; hh < 2; hh++) {
                        const uint32_t w0 = lds32(fa + s * 256 + hh * 128);
                        const uint32_t wsw = __byte_perm(w0, 0, 0x1032) ^ 0x00008000u;
                        const int src = 8 * s + t + 4 * hh;
                        const uint32_t f1 = __shfl_sync(0xffffffffu, e1, src), f2 = __shfl_sync(0xffffffffu, e2, src), f3 = __shfl_sync(0xffffffffu, e3, src);
                        af[s][0][2 * hh] = w0;
                        af[s][0][2 * hh + 1] = h2_cmul(w0, wsw, f1);
                        af[s][1][2 * hh] = h2_cmul(w0, wsw, f2);
                        af[s][1][2 * hh + 1] = h2_cmul(w0, wsw, f3);
                    }
                }
                __syncwarp();
            }
            float acc[2][3][4];
            #pragma unroll
            for (int i = 0; i < 24; i++) (&acc[0][0][0])[i] = 0.0f;
            const cf E1 = cexp_p(a2, bb, 1.0f);
            const cf E2 = cmul(E1, E1), E4 = cmul(E2, E2);
            cf X512;
            #pragma unroll
            for (int nt = 0; nt < 3; nt++) {
                uint32_t xv[8];
                if (nt == 0) {
                    cf cur = cc;
                    xv[0] = pack_f16(cur.x, -cur.y);
                    #pragma unroll
                    for (int i = 1; i < 8; i++) { cur = cmul(cur, E1); xv[i] = pack_f16(cur.x, -cur.y); }
                } else if (nt == 1) {
                    cf cur = cmul(cc, E256);
                    X512 = cmul(cur, E256);
                    xv[0] = pack_f16(cur.x, -cur.y);
                    #pragma unroll
                    for (int i = 1; i < 4; i++) { cur = cmul(cur, E2); xv[i] = pack_f16(cur.x, -cur.y); }
                    cur = cmul(X512, E4);
                    xv[4] = pack_f16(X512.x, -X512.y); xv[5] = pack_f16(cur.x, -cur.y);
                    X512 = cmul(X512, E256);
                    cur = cmul(X512, E4);
                    xv[6] = pack_f16(X512.x, -X512.y); xv[7] = pack_f16(cur.x, -cur.y);
                } else {
                    cf cur = X512;
                    #pragma unroll
                    for (int i = 0; i < 5; i++) { cur = cmul(cur, E256); xv[i] = pack_f16(cur.x, -cur.y); }
                    xv[5] = 0; xv[6] = 0; xv[7] = 0;
                }
                stp[0] = make_uint4(xv[0], xv[1], xv[2], xv[3]);
                stp[1] = make_uint4(xv[4], xv[5], xv[6], xv[7]);
                __syncwarp();
                #pragma unroll
                for (int s = 0; s < 4; s++) {
                    const uint32_t b0 = lds32(fa + s * 256), b1 = lds32(fa + s * 256 + 128);
                    mma_f16(acc[0][nt], af[s][0], b0, b1);
                    mma_f16(acc[1][nt], af[s][1], b0, b1);
                }
                __syncwarp();
            }
            float* kc = (float*)(sB + S_KC + c * 4096);
            bar_sync(4 + c, 128);
            #pragma unroll 1
            for (int step = 0; step < 4; step++) {
                if ((warp & 3) == step) {
                    #pragma unroll
                    for (int mt = 0; mt < 2; mt++)
                        #pragma unroll
                        for (int nt = 0; nt < 3; nt++)
                            #pragma unroll
                            for (int hh = 0; hh < 2; hh++) {
                                float2* p = (float2*)(kc + (mt * 16 + hh * 8 + g) * 24 + nt * 8 + 2 * t);
                                float2 v = make_float2(acc[mt][nt][2 * hh] * scale, acc[mt][nt][2 * hh + 1] * scale);
                                if (step) { float2 o = *p; v.x += o.x; v.y += o.y; }
                                *p = v;
                            }
                }
                if (step < 3) bar_sync(4 + c, 128);
            }
        }

        asm volatile("barrier.cluster.wait.aligned;" ::: "memory");
        PROF(4);
        uint32_t q[2][4];
        {
            const uint64_t dA0 = make_desc(sb + SM_B + rowhalf * 8192, 16, 1024, 1);
            const uint64_t dA1 = make_desc(sb + SM_A + rowhalf * 8192, 16, 1024, 1) - 4096;
            uint4* qx = (uint4*)(sp + SM_B + S_QX) + (tid & 255) * 2;
            auto stage_u = [&]() {
                #pragma unroll
                for (int i = 0; i < 2; i++) {
                    const int z = tid + 512 * i;
                    if (z < 4 * 144) sts128(sBa + S_U + (z / 144) * ULEN * 2 + (PADU - 1152) * 2 + (z % 144) * 16, make_uint4(0, 0, 0, 0));
                }
                mbar_wait(bars + 8 * B_U, 0);
                #pragma unroll
                for (int i = 0; i < 2; i++) {
                    const int l = 2 * (tid + 512 * i);
                    const uint2 r0 = *(const uint2*)(sp + SM_SLAB + l * 16 + rank * 8), r1 = *(const uint2*)(sp + SM_SLAB + l * 16 + 16 + rank * 8);
                    const uint32_t dst = swz128(sBa + S_U + (PADU + l) * 2);
                    sts32(dst, __byte_perm(r0.x, r1.x, 0x5410));
                    sts32(dst + ULEN * 2, __byte_perm(r0.x, r1.x, 0x7632));
                    sts32(dst + ULEN * 4, __byte_perm(r0.y, r1.y, 0x5410));
                    sts32(dst + ULEN * 6, __byte_perm(r0.y, r1.y, 0x7632));
                }
                fence_async_smem();
                bar_arrive(13, 544);
            };
            if (wg < 2) {
                float acc[32];
                #pragma unroll
                for (int i = 0; i < 32; i++) acc[i] = 0.0f;
                fence_regs<32>(acc);
                const uint64_t dB = make_desc(sb + SM_WQ, 16, 1024, 1);
                mbar_wait(bars + 8 * B_WQ, 0);
                mbar_wait(bars + 8 * B_X, 0);
                PROF(2);
                #pragma unroll 1
                for (int ch = 0; ch < 4; ch++) {
                    wg_fence();
                    #pragma unroll
                    for (int ks = 0; ks < 4; ks++) wg_ss64(acc, dA0 + ch * 1024 + ks * 2, dB + (ch * 4 + ks) * 128);
                    wg_commit();
                }
                wg_wait<0>();
                fence_regs<32>(acc);
                bar_sync(1, 512);
                PROF(15);
                stage_u();
                bar_arrive(2, 512);
                PROF(1);
                mbar_wait(bars + 8 * B_WQ2, 0);
                mbar_wait(bars + 8 * (B_X + 1), 0);
                fence_regs<32>(acc);
                #pragma unroll 1
                for (int ch = 4; ch < 8; ch++) {
                    wg_fence();
                    #pragma unroll
                    for (int ks = 0; ks < 4; ks++) wg_ss64(acc, dA1 + ch * 1024 + ks * 2, dB + (ch * 4 + ks) * 128);
                    wg_commit();
                }
                wg_wait<0>();
                fence_regs<32>(acc);
                bar_arrive(14, 288);
                const float QS = 0.25f * 1.4426950408889634f;
                float qm = 0.0f;
                uint32_t qa[4][4];
                #pragma unroll
                for (int i = 0; i < 4; i++) {
                    #pragma unroll
                    for (int j = 0; j < 4; j++) qa[i][j] = pack_bf16(bf_round(acc[8 * i + 2 * j]) * QS, bf_round(acc[8 * i + 2 * j + 1]) * QS);
                    float n0 = bf_lo(qa[i][0]) * bf_lo(qa[i][0]) + bf_hi(qa[i][0]) * bf_hi(qa[i][0]) + bf_lo(qa[i][2]) * bf_lo(qa[i][2]) + bf_hi(qa[i][2]) * bf_hi(qa[i][2]);
                    float n1 = bf_lo(qa[i][1]) * bf_lo(qa[i][1]) + bf_hi(qa[i][1]) * bf_hi(qa[i][1]) + bf_lo(qa[i][3]) * bf_lo(qa[i][3]) + bf_hi(qa[i][3]) * bf_hi(qa[i][3]);
                    n0 += __shfl_xor_sync(0xffffffffu, n0, 1); n0 += __shfl_xor_sync(0xffffffffu, n0, 2);
                    n1 += __shfl_xor_sync(0xffffffffu, n1, 1); n1 += __shfl_xor_sync(0xffffffffu, n1, 2);
                    qm = (n0 != n0 || n1 != n1) ? __int_as_float(0x7f800000) : fmaxf(qm, fmaxf(n0, n1));
                }
                #pragma unroll
                for (int o = 16; o; o >>= 1) qm = fmaxf(qm, __shfl_xor_sync(0xffffffffu, qm, o));
                if (lane == 0) s_misc[warp] = qm;
                qx[0] = make_uint4(qa[2][0], qa[2][1], qa[2][2], qa[2][3]);
                qx[1] = make_uint4(qa[3][0], qa[3][1], qa[3][2], qa[3][3]);
                #pragma unroll
                for (int j = 0; j < 4; j++) { q[0][j] = qa[0][j]; q[1][j] = qa[1][j]; }
                bar_sync(1, 512);
            } else {
                if (kv_wg) {
                    float akv[8];
                    #pragma unroll
                    for (int i = 0; i < 8; i++) akv[i] = 0.0f;
                    fence_regs<8>(akv);
                    const uint64_t dC = make_desc(sb + SM_WKV, 128, 8192, 0);
                    #pragma unroll 1
                    for (int ch = 0; ch < 8; ch++) {
                        if ((ch & 3) == 0) mbar_wait(bars + 8 * (B_X + (ch >> 2)), 0);
                        const uint64_t dA = ch < 4 ? dA0 : dA1;
                        wg_fence();
                        #pragma unroll
                        for (int ks = 0; ks < 4; ks++) wg_ss16(akv, dA + ch * 1024 + ks * 2, dC + (ch * 4 + ks) * 16);
                        wg_commit();
                    }
                    wg_wait<0>();
                    fence_regs<8>(akv);
                    const int key = qb * 128 + rowhalf * 64 + wiw * 16 + g;
                    uint32_t pk[4];
                    #pragma unroll
                    for (int i = 0; i < 4; i++) pk[i] = pack_bf16(akv[2 * i], akv[2 * i + 1]);
                    float st;
                    if (kv_sel == 0) {
                        uint8_t* b = g_kimg + (key >> 3) * 256 + (key & 7) * 16 + 4 * t;
                        *(uint32_t*)(b) = pk[0]; *(uint32_t*)(b + 256) = pk[1]; *(uint32_t*)(b + 128) = pk[2]; *(uint32_t*)(b + 384) = pk[3];
                        float n0 = bf_lo(pk[0]) * bf_lo(pk[0]) + bf_hi(pk[0]) * bf_hi(pk[0]) + bf_lo(pk[2]) * bf_lo(pk[2]) + bf_hi(pk[2]) * bf_hi(pk[2]);
                        float n1 = bf_lo(pk[1]) * bf_lo(pk[1]) + bf_hi(pk[1]) * bf_hi(pk[1]) + bf_lo(pk[3]) * bf_lo(pk[3]) + bf_hi(pk[3]) * bf_hi(pk[3]);
                        n0 += __shfl_xor_sync(0xffffffffu, n0, 1); n0 += __shfl_xor_sync(0xffffffffu, n0, 2);
                        n1 += __shfl_xor_sync(0xffffffffu, n1, 1); n1 += __shfl_xor_sync(0xffffffffu, n1, 2);
                        st = (n0 != n0 || n1 != n1) ? __int_as_float(0x7f800000) : fmaxf(n0, n1);
                    } else {
                        uint8_t* lo = g_vimg + key * 16 + 4 * t;
                        uint8_t* hi = g_vimg + 33792 + (31 - (key >> 6)) * 1024 + (key & 63) * 16 + 4 * t;
                        *(uint32_t*)(lo) = pk[0]; *(uint32_t*)(lo + 128) = pk[1]; *(uint32_t*)(hi) = pk[2]; *(uint32_t*)(hi + 128) = pk[3];
                        st = 0.0f;
                        #pragma unroll
                        for (int i = 0; i < 4; i++) {
                            float a = fabsf(bf_lo(pk[i])), b = fabsf(bf_hi(pk[i]));
                            st = (a != a || b != b) ? __int_as_float(0x7f800000) : fmaxf(st, fmaxf(a, b));
                        }
                    }
                    #pragma unroll
                    for (int o = 16; o; o >>= 1) st = fmaxf(st, __shfl_xor_sync(0xffffffffu, st, o));
                    if (lane == 0) s_misc[20 + wiw] = st;
                bar_arrive(3, 160);
                }
                uint2 mp[3];
                #pragma unroll
                for (int i = 0; i < 3; i++) { const int w = (tid & 255) + 256 * i; mp[i] = (w < TABN / 4) ? __ldg((const uint2*)g_tabmap.v + w) : make_uint2(0u, 0u); }
                bar_sync(1, 512);
                stage_u();
                #pragma unroll 1
                for (int cc = 0; cc < 4; cc++) {
                    const float* kc = (const float*)(sB + S_KC + cc * 4096);
                    uint2* tab = (uint2*)(sB + S_TAB + cc * TABN * 2);
                    #pragma unroll
                    for (int i = 0; i < 3; i++) {
                        const int w = (tid & 255) + 256 * i;
                        if (w < TABN / 4) tab[w] = make_uint2(pack_bf16(kc[mp[i].x & 0xFFFF], kc[mp[i].x >> 16]), pack_bf16(kc[mp[i].y & 0xFFFF], kc[mp[i].y >> 16]));
                    }
                }
                bar_sync(2, 512);
                #pragma unroll 1
                for (int tk = tid & 255; tk < 4 * 130; tk += 256) {
                    const int c = tk / 130, i = tk % 130;
                    const uint32_t src = sBa + S_U + c * ULEN * 2 + (PADU + 8 * i - WPAD - 8) * 2;
                    const uint4 v0 = lds128(swz128(src)), v1 = lds128(swz128(src + 16)), v2 = lds128(swz128(src + 32));
                    float x[16];
                    const uint32_t vv[8] = {v0.z, v0.w, v1.x, v1.y, v1.z, v1.w, v2.x, v2.y};
                    #pragma unroll
                    for (int k = 0; k < 8; k++) { x[2 * k] = bf_lo(vv[k]); x[2 * k + 1] = bf_hi(vv[k]); }
                    float p2[15], w7[8], w9[8];
                    #pragma unroll
                    for (int e = 0; e < 15; e++) p2[e] = x[e] + x[e + 1];
                    #pragma unroll
                    for (int e = 0; e < 8; e++) {
                        w7[e] = (p2[e + 1] + p2[e + 3]) + (p2[e + 5] + x[e + 7]);
                        w9[e] = w7[e] + (x[e] + x[e + 8]);
                    }
                    sts128(swz(sBa + S_W7 + c * W3LEN * 2 + i * 16), make_uint4(pack_bf16(w7[0], w7[1]), pack_bf16(w7[2], w7[3]), pack_bf16(w7[4], w7[5]), pack_bf16(w7[6], w7[7])));
                    sts128(swz(sBa + S_W9 + c * W3LEN * 2 + i * 16), make_uint4(pack_bf16(w9[0], w9[1]), pack_bf16(w9[2], w9[3]), pack_bf16(w9[4], w9[5]), pack_bf16(w9[6], w9[7])));
                }
                bar_sync(1, 512);
                const uint4 q0 = qx[0], q1 = qx[1];
                q[0][0] = q0.x; q[0][1] = q0.y; q[0][2] = q0.z; q[0][3] = q0.w;
                q[1][0] = q1.x; q[1][1] = q1.y; q[1][2] = q1.z; q[1][3] = q1.w;
            }
        }
        PROF(3);
        {
            const int c = wg;
            uint32_t sBl = sBa;
            asm volatile("" : "+r"(sBl) :: "memory");
            float acc[16];
            #pragma unroll
            for (int i = 0; i < 16; i++) acc[i] = 0.0f;
            fence_regs<16>(acc);
            const uint32_t tabc = sBl + S_TAB + c * TABN * 2;
            const uint32_t tD = tabc + ((g & 1) ? (TD1 + CD + 1) : (TD0 + CD)) * 2 - (g - 2 * t) * 2 - 32 * wiw;
            const uint32_t uLo = (((sBl + S_U + c * ULEN * 2 + PADU * 2) & 0x3FFFF) >> 4) | (1u << 16);
            uint32_t A[2][4][4];
            auto load_set = [&](uint32_t (&X)[4][4], int m0) {
                asm volatile("{ .reg .pred p; setp.lt.u32 p, %2, 66; mov.b32 %0, 0; @p ld.shared.u32 %0, [%1]; }"
                             : "=r"(X[0][2]) : "r"(tD - 32 * m0 + 16), "r"(m0 + wiw) : "memory");
                #pragma unroll
                for (int i = 0; i < 4; i++) {
                    asm volatile("{ .reg .pred p; setp.lt.u32 p, %3, 66; mov.b32 %0, 0; mov.b32 %1, 0; @p ld.shared.u32 %0, [%2]; @p ld.shared.u32 %1, [%2+-16]; }"
                                 : "=r"(X[i][0]), "=r"(X[i][1]) : "r"(tD - 32 * (m0 + i)), "r"(m0 + i + wiw) : "memory");
                }
                #pragma unroll
                for (int i = 0; i < 4; i++) {
                    asm volatile("mov.b32 %0, %1;" : "=r"(X[i][3]) : "r"(X[i][0]));
                    if (i < 3) asm volatile("mov.b32 %0, %1;" : "=r"(X[i + 1][2]) : "r"(X[i][1]));
                }
            };
            #pragma unroll 1
            for (int m0 = -3; m0 < 69; m0 += 8) {
                #pragma unroll
                for (int h = 0; h < 2; h++) {
                    load_set(A[h], m0 + 4 * h);
                    wg_fence();
                    #pragma unroll
                    for (int i = 0; i < 4; i++) wg_rs32(acc, A[h][i], uLo - 2 * (m0 + 4 * h + i));
                    wg_commit();
                    wg_wait<1>();
                }
            }
            wg_wait<0>();
            fence_regs<16>(acc);
            PROF(6);
            {
                asm volatile("" : "+r"(sBl) :: "memory");
                const int mi = lane >> 3, r8 = lane & 7;
                const uint32_t frag = (16 * (8 * (mi >> 1) + r8) + 8 * (mi & 1)) * 2;
                const uint32_t t3 = sBl + S_TAB + c * TABN * 2 + (T3B + ((wiw & 1) ? (T3C + C3 + 1) : C3)) * 2 - (4 * g + wiw - 2 * t) * 2;
                #pragma unroll
                for (int s = 0; s < 2; s++) {
                    const uint32_t sig = swz(sBl + (s ? S_W7 : S_W9) + c * W3LEN * 2 + WPAD * 2 + frag - (s ? 16 : 32));
                    uint32_t a[4][4], R[4][2];
                    #pragma unroll
                    for (int b = 0; b < 4; b++) ldsm4t_p(a[b], sig + b * 512);
                    #pragma unroll
                    for (int i = 0; i < 4; i++) { R[i][0] = lds32_p(t3 + s * (T3S * 2) - 2 * (48 + 16 * i)); R[i][1] = lds32_p(t3 + s * (T3S * 2) - 2 * (40 + 16 * i)); }
                    #pragma unroll
                    for (int b = 0; b < 4; b++) {
                        mma_bf16_p(acc + 12, a[b][0], a[b][1], a[b][2], a[b][3], R[3 - b][0], R[3 - b][1]);
                        if (b < 2) mma_bf16_p(acc + 8, a[b][0], a[b][1], a[b][2], a[b][3], R[1 - b][0], R[1 - b][1]);
                    }
                }
            }
            __nv_bfloat16* ys = (__nv_bfloat16*)(sB + S_Y + c * 4096) + 128 * t + 16 * wiw + g;
            #pragma unroll
            for (int j = 0; j < 4; j++) {
                ys[512 * j] = __float2bfloat16_rn(acc[4 * j]);
                ys[512 * j + 64] = __float2bfloat16_rn(acc[4 * j + 1]);
                ys[512 * j + 8] = __float2bfloat16_rn(acc[4 * j + 2]);
                ys[512 * j + 72] = __float2bfloat16_rn(acc[4 * j + 3]);
            }
        }
        bar_arrive(10, 608);
        PROF(7);
        {
            mbar_wait(bars + 8 * B_ST, 0);
            PROF(9); PROFC(8);
            float qm = 0.0f;
            #pragma unroll
            for (int i = 0; i < 8; i++) qm = fmaxf(qm, s_misc[i]);
            const float vm = s_misc[17];
            const bool fast = (qm * s_misc[16] <= 60.0f * 60.0f) && (vm <= 1.0e12f) && (vm >= 1.0e-12f || vm == 0.0f);
            uint8_t* ob = g_oimg + qb * 131072 + hg * 16384 + nh * 8192 + (rowhalf * 8 + wiw * 2) * 128 + g * 16 + 4 * t;
            uint32_t cA = 0xBF00BF00u, cB = 0x00030003u;
            asm volatile("" : "+r"(cA), "+r"(cB));
            #pragma unroll 1
            for (int tile = 0; tile < 2; tile++) {
                uint32_t kLo = (((sb + SM_K) & 0x3FFFF) >> 4) | (8u << 16), vLo = (((sb + SM_V) & 0x3FFFF) >> 4) | (8u << 16), vHi = 2048;
                float o[12], s[32];
                uint32_t p[16], qq[4];
                #pragma unroll
                for (int i = 0; i < 4; i++) { qq[i] = tile ? q[1][i] : q[0][i]; asm volatile("" : "+r"(qq[i])); }
                #pragma unroll
                for (int i = 0; i < 12; i++) o[i] = 0.0f;
                #pragma unroll
                for (int i = 0; i < 32; i++) s[i] = 0.0f;
                fence_regs<12>(o);
                fence_regs<32>(s);
                if (fast) {
                    #pragma unroll 1
                    for (int c = 0; c < SEQ / 256; c++) {
                        if (c <= 4) mbar_wait(bars + 8 * (B_KV + (c < 2 ? c : c < 4 ? 2 : 3)), 0);
                        wg_fence();
                        wg_qk(s, qq, kLo);
                        wg_commit();
                        #pragma unroll
                        for (int u = 0; u < 4; u++) {
                            wg_wait<0>();
                            fence_regs<32>(s);
                            #pragma unroll
                            for (int i = 0; i < 16; i++) {
                                if ((MUFU_MASK >> i) & 1) p[i] = exp_mufu(s[2 * i], s[2 * i + 1]);
                                else p[i] = exp_sw(s[2 * i], s[2 * i + 1], cA, cB);
                            }
                            wg_fence();
                            if (u + 1 < 4) wg_qk(s, qq, kLo + (u + 1) * 128);
                            #pragma unroll
                            for (int kk = 0; kk < 4; kk++) wg_pv(o, p + 4 * kk, vLo + u * 64 + kk * 16, vHi - u * 64);
                            wg_commit();
                        }
                        kLo += 512; vLo += 256; vHi -= 256;
                    }
                    wg_wait<0>();
                } else {
                    float mx0 = -INFINITY, mx1 = -INFINITY;
                    #pragma unroll 1
                    for (int c = 0; c < SEQ / 64; c++) {
                        if (c <= 16) mbar_wait(bars + 8 * (B_KV + (c < 8 ? (c >> 2) : c < 16 ? 2 : 3)), 0);
                        wg_fence();
                        wg_qk(s, qq, kLo);
                        wg_commit();
                        wg_wait<0>();
                        fence_regs<32>(s);
                        fence_regs<12>(o);
                        float m0 = mx0, m1 = mx1;
                        #pragma unroll
                        for (int j = 0; j < 8; j++) {
                            m0 = fmaxf(m0, fmaxf(s[4 * j], s[4 * j + 1]));
                            m1 = fmaxf(m1, fmaxf(s[4 * j + 2], s[4 * j + 3]));
                        }
                        m0 = fmaxf(m0, __shfl_xor_sync(0xffffffffu, m0, 1)); m0 = fmaxf(m0, __shfl_xor_sync(0xffffffffu, m0, 2));
                        m1 = fmaxf(m1, __shfl_xor_sync(0xffffffffu, m1, 1)); m1 = fmaxf(m1, __shfl_xor_sync(0xffffffffu, m1, 2));
                        const float c0 = ex2f(mx0 - m0), c1 = ex2f(mx1 - m1);
                        mx0 = m0; mx1 = m1;
                        #pragma unroll
                        for (int j = 0; j < 3; j++) { o[4 * j] *= c0; o[4 * j + 1] *= c0; o[4 * j + 2] *= c1; o[4 * j + 3] *= c1; }
                        #pragma unroll
                        for (int j = 0; j < 8; j++) {
                            p[2 * j] = exp_mufu(s[4 * j] - m0, s[4 * j + 1] - m0);
                            p[2 * j + 1] = exp_mufu(s[4 * j + 2] - m1, s[4 * j + 3] - m1);
                        }
                        wg_fence();
                        #pragma unroll
                        for (int kk = 0; kk < 4; kk++) wg_pv(o, p + 4 * kk, vLo + kk * 16, vHi);
                        wg_commit();
                        wg_wait<0>();
                        kLo += 128; vLo += 64; vHi -= 64;
                    }
                }
                fence_regs<12>(o);
                if (tile == 0) PROFC(3);
                const float i0 = 1.0f / o[4], i1 = 1.0f / o[6];
                uint8_t* b = ob + tile * 4096;
                *(uint32_t*)(b) = pack_bf16(o[0] * i0, o[1] * i0);
                *(uint32_t*)(b + 128) = pack_bf16(o[2] * i1, o[3] * i1);
                *(uint32_t*)(b + 2048) = pack_bf16(o[8] * i0, o[9] * i0);
                *(uint32_t*)(b + 2048 + 128) = pack_bf16(o[10] * i1, o[11] * i1);
            }
        }
        PROF(10); PROFC(9);
        bar_arrive(12, 544);

        if (wg < 2) {
            float acc[32];
            #pragma unroll
            for (int i = 0; i < 32; i++) acc[i] = 0.0f;
            fence_regs<32>(acc);
            const uint64_t dA = make_desc(sb + SM_A + rowhalf * 1024, 2048, 128, 0);
            const uint64_t dB = make_desc(sb + SM_B, 16, 1024, 1);
            mbar_wait(bars + 8 * B_WO, 0);
            #pragma unroll 1
            for (int i = 0; i < 8; i++) {
                const int src = ((hg & 6) + i) & 7;
                mbar_wait(bars + 8 * (B_O + src), 0);
                wg_fence();
                #pragma unroll
                for (int kk = 0; kk < 4; kk++) wg_ss64(acc, dA + src * 1024 + kk * 256, dB + (src * 4 + kk) * 128);
                wg_commit();
            }
            wg_wait<0>();
            fence_regs<32>(acc);
            PROF(12);
            const int row = qb * 128 + rowhalf * 64 + wiw * 16 + g;
            uint4* o128 = (uint4*)(P.out + (size_t)row * 1024 + hg * 64 + 8 * t);
            #pragma unroll
            for (int rr = 0; rr < 2; rr++)
                #pragma unroll
                for (int a = 0; a < 2; a++) {
                    uint32_t v[4];
                    #pragma unroll
                    for (int j = 0; j < 4; j++) v[j] = pack_bf16(acc[16 * a + 4 * j + 2 * rr], acc[16 * a + 4 * j + 2 * rr + 1]);
                    quad_transpose(v, t);
                    o128[rr * 1024 + a * 4] = make_uint4(v[0], v[1], v[2], v[3]);
                }
        }
        PROF(13);
    }
}

typedef CUresult (*EncodeFn)(CUtensorMap*, CUtensorMapDataType, cuuint32_t, void*, const cuuint64_t*, const cuuint64_t*,
                             const cuuint32_t*, const cuuint32_t*, CUtensorMapInterleave, CUtensorMapSwizzle,
                             CUtensorMapL2promotion, CUtensorMapFloatOOBfill);

void make_map(EncodeFn fn, CUtensorMap* m, const void* ptr, uint64_t inner, uint64_t outer, uint32_t box_in, uint32_t box_out, CUtensorMapSwizzle swz) {
    cuuint64_t dims[2] = {inner, outer};
    cuuint64_t strides[1] = {inner * 2};
    cuuint32_t box[2] = {box_in, box_out};
    cuuint32_t es[2] = {1, 1};
    fn(m, CU_TENSOR_MAP_DATA_TYPE_BFLOAT16, 2, const_cast<void*>(ptr), dims, strides, box, es, CU_TENSOR_MAP_INTERLEAVE_NONE, swz,
       CU_TENSOR_MAP_L2_PROMOTION_L2_128B, CU_TENSOR_MAP_FLOAT_OOB_FILL_NONE);
}

}

extern "C" void kernel_launch(void* const* d_in, const int* in_sizes, int n_in, void* d_out, int out_size) {
    (void)in_sizes; (void)n_in; (void)out_size;
    static EncodeFn fn = nullptr;
    if (!fn) {
        void* p = nullptr;
        cudaDriverEntryPointQueryResult qr;
        cudaGetDriverEntryPoint("cuTensorMapEncodeTiled", &p, cudaEnableDefault, &qr);
        fn = (EncodeFn)p;
        cudaFuncSetAttribute(fused_kernel, cudaFuncAttributeMaxDynamicSharedMemorySize, SM_ALLOC);
    }
    CUtensorMap tx, twq, two, twk, twv, tu;
    {
        cuuint64_t dims[3] = {64, 2048, 8};
        cuuint64_t strides[2] = {1024, 128};
        cuuint32_t box[3] = {64, 128, 4};
        cuuint32_t es[3] = {1, 1, 1};
        fn(&tx, CU_TENSOR_MAP_DATA_TYPE_BFLOAT16, 3, d_in[0], dims, strides, box, es, CU_TENSOR_MAP_INTERLEAVE_NONE, CU_TENSOR_MAP_SWIZZLE_128B,
           CU_TENSOR_MAP_L2_PROMOTION_L2_128B, CU_TENSOR_MAP_FLOAT_OOB_FILL_NONE);
    }
    make_map(fn, &tu, d_in[5], 512, 2048, 8, 256, CU_TENSOR_MAP_SWIZZLE_NONE);
    make_map(fn, &twq, d_in[1], 512, 512, 64, 256, CU_TENSOR_MAP_SWIZZLE_128B);
    make_map(fn, &twk, d_in[2], 16, 512, 8, 256, CU_TENSOR_MAP_SWIZZLE_NONE);
    make_map(fn, &twv, d_in[3], 16, 512, 8, 256, CU_TENSOR_MAP_SWIZZLE_NONE);
    make_map(fn, &two, d_in[4], 512, 512, 64, 256, CU_TENSOR_MAP_SWIZZLE_128B);
    Params P;
    P.u = (const __nv_bfloat16*)d_in[5];
    P.lar = (const __nv_bfloat16*)d_in[6];
    P.aim = (const __nv_bfloat16*)d_in[7];
    P.cre = (const __nv_bfloat16*)d_in[8];
    P.cim = (const __nv_bfloat16*)d_in[9];
    P.logdt = (const __nv_bfloat16*)d_in[10];
    P.dskip = (const __nv_bfloat16*)d_in[11];
    P.out = (__nv_bfloat16*)d_out;
    fused_kernel<<<NCTA, NTHR, SM_ALLOC>>>(tx, twq, two, twk, twv, tu, P);
}
```

```cpp
#include <cuda_runtime.h>
#include <cuda_bf16.h>
#include <cuda_fp16.h>
#include <cuda.h>
#include <stdint.h>

namespace {

constexpr int SEQ = 2048;
constexpr int NCTA = 128, NTHR = 640;

constexpr int SM_A = 0;
constexpr int SM_WQ = 65536;
constexpr int SM_SLAB = SM_WQ + 32768;
constexpr int SM_K = 0, SM_V = 65536;
constexpr int SM_B = 132096;
constexpr int SM_WKV = SM_B + 65536;

constexpr int PADU = 1024, ULEN = PADU + 2048;
constexpr int WPAD = 16, W3LEN = WPAD + 1024;
constexpr int TABN = 2912;
constexpr int S_U = 0;
constexpr int S_W7 = S_U + 4 * ULEN * 2;
constexpr int S_W9 = S_W7 + 4 * W3LEN * 2;
constexpr int S_TAB = S_W9 + 4 * W3LEN * 2;
constexpr int S_QX = S_TAB + 4 * TABN * 2;
constexpr int S_KC = 214016 - SM_B;
constexpr int S_Y = S_KC;
constexpr int SM_BAR = SM_B + S_KC + 16384;
constexpr int SM_TOTAL = SM_BAR + 1024;
constexpr int SM_ALLOC = SM_TOTAL + 1024;
static_assert(SM_V + 65536 + 1024 <= SM_B && SM_ALLOC <= 232448 && S_QX + 8192 <= S_KC && SM_WKV + 16384 <= SM_B + S_KC, "smem map");

constexpr int TD0 = 0, TD1 = 1232, CD = 1152;
constexpr int T3B = 2464, T3S = 224, T3C = 112, C3 = 136;

constexpr int rne8(int t) {
    if (t < 256) return t;
    int sh = 0;
    while ((t >> sh) >= 256) sh++;
    int q = t >> sh, rem = t & ((1 << sh) - 1), half = 1 << (sh - 1);
    if (rem > half || (rem == half && (q & 1))) q++;
    return q << sh;
}
constexpr int kcidx(int p) {
    if (p < 256) return (p >> 3) * 24 + (p & 7);
    if (p < 512) return ((p - 256) >> 3) * 24 + 8 + (((p - 256) & 7) >> 1);
    if (p < 1024) { int q = p - 512, hi = q >> 8, rem = q & 255; return (rem >> 3) * 24 + 12 + 2 * hi + ((rem & 7) >> 2); }
    if (p < 2048) { int q = p - 1024; return ((q & 255) >> 3) * 24 + 16 + (q >> 8); }
    return 20;
}
constexpr int KC_ZERO = 23;
constexpr int tab_dense(int t) { return (t >= 0 && t <= 1028) ? kcidx(rne8(t)) : KC_ZERO; }
constexpr int tab_3(int s, int lag) { return (lag >= 64 && lag <= 127) ? kcidx(s == 0 ? 16 * (lag + 1) : 16 * lag + 8) : KC_ZERO; }
struct TabMap {
    uint16_t v[TABN];
    constexpr TabMap() : v{} {
        for (int i = 0; i < TD1; i++) { v[TD0 + i] = tab_dense(CD - i); v[TD1 + i] = tab_dense(CD + 1 - i); }
        for (int s = 0; s < 2; s++)
            for (int i = 0; i < T3C; i++) { v[T3B + s * T3S + i] = tab_3(s, C3 - i); v[T3B + s * T3S + T3C + i] = tab_3(s, C3 + 1 - i); }
    }
};
__device__ const __align__(16) TabMap g_tabmap = TabMap();

__device__ __align__(1024) uint8_t g_kimg[65536];
__device__ __align__(1024) uint8_t g_vimg[65536 + 1024];
__device__ __align__(1024) uint8_t g_oimg[16 * 131072];
__device__ unsigned long long g_flag_kv[64];
__device__ unsigned g_flag_o[128];
__device__ unsigned g_epoch;
__device__ unsigned g_done;

#define PROF(i) do {} while (0)
#define PROF2(i) do {} while (0)
#define PROFC(i) do {} while (0)
#define PROF3(i) do {} while (0)

__device__ __forceinline__ uint32_t smem_u32(const void* p) { return (uint32_t)__cvta_generic_to_shared(p); }
__device__ __forceinline__ void mbar_init(uint32_t bar, uint32_t cnt) { asm volatile("mbarrier.init.shared::cta.b64 [%0], %1;" :: "r"(bar), "r"(cnt) : "memory"); }
__device__ __forceinline__ void mbar_expect_tx(uint32_t bar, uint32_t bytes) {
    asm volatile("mbarrier.arrive.expect_tx.shared::cta.b64 _, [%0], %1;" :: "r"(bar), "r"(bytes) : "memory"); }
__device__ __forceinline__ void mbar_wait(uint32_t bar, uint32_t parity) {
    uint32_t ok = 0;
    for (int it = 0; it < (1 << 22) && !ok; it++) {
        asm volatile("{ .reg .pred p; mbarrier.try_wait.parity.shared::cta.b64 p, [%1], %2; selp.u32 %0, 1, 0, p; }"
                     : "=r"(ok) : "r"(bar), "r"(parity) : "memory");
    }
}
__device__ __forceinline__ void tma_2d(uint32_t dst, const CUtensorMap* map, int c0, int c1, uint32_t bar) {
    asm volatile("cp.async.bulk.tensor.2d.shared::cluster.global.mbarrier::complete_tx::bytes [%0], [%1, {%3, %4}], [%2];"
                 :: "r"(dst), "l"((uint64_t)map), "r"(bar), "r"(c0), "r"(c1) : "memory");
}
__device__ __forceinline__ void tma_2d_mc(uint32_t dst, const CUtensorMap* map, int c0, int c1, uint32_t bar) {
    asm volatile("cp.async.bulk.tensor.2d.shared::cluster.global.mbarrier::complete_tx::bytes.multicast::cluster [%0], [%1, {%3, %4}], [%2], %5;"
                 :: "r"(dst), "l"((uint64_t)map), "r"(bar), "r"(c0), "r"(c1), "h"((uint16_t)3) : "memory");
}
__device__ __forceinline__ void bulk_g2s_mc(uint32_t dst, const void* src, uint32_t bytes, uint32_t bar) {
    asm volatile("cp.async.bulk.shared::cluster.global.mbarrier::complete_tx::bytes.multicast::cluster [%0], [%1], %2, [%3], %4;"
                 :: "r"(dst), "l"((uint64_t)src), "r"(bytes), "r"(bar), "h"((uint16_t)3) : "memory");
}
__device__ __forceinline__ void pair_sync(uint32_t bar, uint32_t peer) {
    uint32_t ra;
    asm volatile("mapa.shared::cluster.u32 %0, %1, %2;" : "=r"(ra) : "r"(bar), "r"(peer));
    asm volatile("mbarrier.arrive.shared::cluster.b64 _, [%0];" :: "r"(ra) : "memory");
    asm volatile("mbarrier.arrive.shared::cta.b64 _, [%0];" :: "r"(bar) : "memory");
    uint32_t ok = 0;
    for (int it = 0; it < (1 << 22) && !ok; it++) {
        asm volatile("{ .reg .pred p; mbarrier.try_wait.parity.shared::cta.b64 p, [%1], 0; selp.u32 %0, 1, 0, p; }"
                     : "=r"(ok) : "r"(bar) : "memory");
    }
}
__device__ __forceinline__ void fence_async_all() { asm volatile("fence.proxy.async.global;" ::: "memory"); }
__device__ __forceinline__ void fence_async_smem() { asm volatile("fence.proxy.async.shared::cta;" ::: "memory"); }
__device__ __forceinline__ unsigned ld_acquire(const unsigned* p) {
    unsigned v; asm volatile("ld.acquire.gpu.global.u32 %0, [%1];" : "=r"(v) : "l"(p) : "memory"); return v; }
__device__ __forceinline__ void st_release(unsigned* p, unsigned v) { asm volatile("st.release.gpu.global.u32 [%0], %1;" :: "l"(p), "r"(v) : "memory"); }
__device__ __forceinline__ void wait_flag(const unsigned* p, unsigned epoch) {
    for (int it = 0; it < (1 << 22); it++) { if (ld_acquire(p) == epoch) break; }
}
__device__ __forceinline__ unsigned long long ld_acquire64(const unsigned long long* p) {
    unsigned long long v; asm volatile("ld.acquire.gpu.global.u64 %0, [%1];" : "=l"(v) : "l"(p) : "memory"); return v; }
__device__ __forceinline__ void st_release64(unsigned long long* p, unsigned long long v) { asm volatile("st.release.gpu.global.u64 [%0], %1;" :: "l"(p), "l"(v) : "memory"); }
__device__ __forceinline__ float wait_flag64(const unsigned long long* p, unsigned epoch) {
    unsigned long long v = 0;
    for (int it = 0; it < (1 << 22); it++) { v = ld_acquire64(p); if ((unsigned)(v >> 32) == epoch) break; }
    return __uint_as_float((unsigned)v);
}
__device__ __forceinline__ void tma_3d_mc(uint32_t dst, const CUtensorMap* map, int c0, int c1, int c2, uint32_t bar) {
    asm volatile("cp.async.bulk.tensor.3d.shared::cluster.global.mbarrier::complete_tx::bytes.multicast::cluster [%0], [%1, {%3, %4, %5}], [%2], %6;"
                 :: "r"(dst), "l"((uint64_t)map), "r"(bar), "r"(c0), "r"(c1), "r"(c2), "h"((uint16_t)3) : "memory");
}
__device__ __forceinline__ void bar_sync(int id, int n) { asm volatile("bar.sync %0, %1;" :: "r"(id), "r"(n) : "memory"); }
__device__ __forceinline__ void bar_arrive(int id, int n) { asm volatile("bar.arrive %0, %1;" :: "r"(id), "r"(n) : "memory"); }
__device__ __forceinline__ void mbar_arrive(uint32_t bar) { asm volatile("mbarrier.arrive.shared::cta.b64 _, [%0];" :: "r"(bar) : "memory"); }

__device__ __forceinline__ uint64_t make_desc(uint32_t saddr, uint32_t lbo, uint32_t sbo, uint32_t swz) {
    uint64_t d = 0;
    d |= (uint64_t)((saddr & 0x3FFFF) >> 4);
    d |= (uint64_t)((lbo >> 4) & 0x3FFF) << 16;
    d |= (uint64_t)((sbo >> 4) & 0x3FFF) << 32;
    d |= (uint64_t)swz << 62;
    return d;
}
__device__ __forceinline__ void wg_fence() { asm volatile("wgmma.fence.sync.aligned;" ::: "memory"); }
__device__ __forceinline__ void wg_commit() { asm volatile("wgmma.commit_group.sync.aligned;" ::: "memory"); }
template<int N> __device__ __forceinline__ void wg_wait() { asm volatile("wgmma.wait_group.sync.aligned %0;" :: "n"(N) : "memory"); }
#define A4(d, o) "+f"(d[o + 0]), "+f"(d[o + 1]), "+f"(d[o + 2]), "+f"(d[o + 3])
#define A16(d, o) A4(d, o), A4(d, o + 4), A4(d, o + 8), A4(d, o + 12)

__device__ __forceinline__ void wg_pv(float* d, const uint32_t* a, uint32_t lo, uint32_t hi) {
    asm volatile("{ .reg .b64 dd; mov.b64 dd, {%16, %17};\n"
                 "wgmma.mma_async.sync.aligned.m64n24k16.f32.bf16.bf16 {%0,%1,%2,%3,%4,%5,%6,%7,%8,%9,%10,%11}, {%12,%13,%14,%15}, dd, 1, 1, 1, 1; }"
                 : A4(d, 0), A4(d, 4), A4(d, 8) : "r"(a[0]), "r"(a[1]), "r"(a[2]), "r"(a[3]), "r"(lo), "r"(hi));
}
__device__ __forceinline__ void wg_qk(float* d, const uint32_t* a, uint32_t lo) {
    asm volatile("{ .reg .b64 dd; mov.b64 dd, {%36, %37};\n"
                 "wgmma.mma_async.sync.aligned.m64n64k16.f32.bf16.bf16 {%0,%1,%2,%3,%4,%5,%6,%7,%8,%9,%10,%11,%12,%13,%14,%15,%16,%17,%18,%19,%20,%21,%22,%23,%24,%25,%26,%27,%28,%29,%30,%31}, {%32,%33,%34,%35}, dd, 0, 1, 1, 0; }"
                 : A16(d, 0), A16(d, 16) : "r"(a[0]), "r"(a[1]), "r"(a[2]), "r"(a[3]), "r"(lo), "r"(16));
}
__device__ __forceinline__ void wg_rs32(float* d, const uint32_t* a, uint32_t lo) {
    asm volatile("{ .reg .b64 dd; mov.b64 dd, {%20, %21};\n"
                 "wgmma.mma_async.sync.aligned.m64n32k16.f32.bf16.bf16 {%0,%1,%2,%3,%4,%5,%6,%7,%8,%9,%10,%11,%12,%13,%14,%15}, {%16,%17,%18,%19}, dd, 1, 1, 1, 0; }"
                 : A16(d, 0) : "r"(a[0]), "r"(a[1]), "r"(a[2]), "r"(a[3]), "r"(lo), "r"(0x40000040));
}
__device__ __forceinline__ void wg_rs24(float* d, const uint32_t* a, uint32_t lo) {
    asm volatile("{ .reg .b64 dd; mov.b64 dd, {%16, %17};\n"
                 "wgmma.mma_async.sync.aligned.m64n24k16.f32.bf16.bf16 {%0,%1,%2,%3,%4,%5,%6,%7,%8,%9,%10,%11}, {%12,%13,%14,%15}, dd, 1, 1, 1, 0; }"
                 : A4(d, 0), A4(d, 4), A4(d, 8) : "r"(a[0]), "r"(a[1]), "r"(a[2]), "r"(a[3]), "r"(lo), "r"(0x40000040));
}
__device__ __forceinline__ void wg_ss64(float* d, uint64_t da, uint64_t db) {
    asm volatile("wgmma.mma_async.sync.aligned.m64n64k16.f32.bf16.bf16 {%0,%1,%2,%3,%4,%5,%6,%7,%8,%9,%10,%11,%12,%13,%14,%15,%16,%17,%18,%19,%20,%21,%22,%23,%24,%25,%26,%27,%28,%29,%30,%31}, %32, %33, 1, 1, 1, 0, 1;"
                 : A16(d, 0), A16(d, 16) : "l"(da), "l"(db));
}
__device__ __forceinline__ void wg_ss16(float* d, uint64_t da, uint64_t db) {
    asm volatile("wgmma.mma_async.sync.aligned.m64n16k16.f32.bf16.bf16 {%0,%1,%2,%3,%4,%5,%6,%7}, %8, %9, 1, 1, 1, 0, 1;"
                 : A4(d, 0), A4(d, 4) : "l"(da), "l"(db));
}
template<int N> __device__ __forceinline__ void fence_regs(float* r) {
    #pragma unroll
    for (int i = 0; i < N; i++) asm volatile("" : "+f"(r[i]) :: "memory");
}
__device__ __forceinline__ void mma_f16(float* d, const uint32_t* a, uint32_t b0, uint32_t b1) {
    asm volatile("mma.sync.aligned.m16n8k16.row.col.f32.f16.f16.f32 {%0,%1,%2,%3}, {%4,%5,%6,%7}, {%8,%9}, {%0,%1,%2,%3};"
                 : "+f"(d[0]), "+f"(d[1]), "+f"(d[2]), "+f"(d[3]) : "r"(a[0]), "r"(a[1]), "r"(a[2]), "r"(a[3]), "r"(b0), "r"(b1));
}
__device__ __forceinline__ uint32_t lds32(uint32_t addr) { uint32_t v; asm volatile("ld.shared.u32 %0, [%1];" : "=r"(v) : "r"(addr) : "memory"); return v; }
__device__ __forceinline__ void mma_bf16_p(float* d, uint32_t a0, uint32_t a1, uint32_t a2, uint32_t a3, uint32_t b0, uint32_t b1) {
    asm("mma.sync.aligned.m16n8k16.row.col.f32.bf16.bf16.f32 {%0,%1,%2,%3}, {%4,%5,%6,%7}, {%8,%9}, {%0,%1,%2,%3};"
        : "+f"(d[0]), "+f"(d[1]), "+f"(d[2]), "+f"(d[3]) : "r"(a0), "r"(a1), "r"(a2), "r"(a3), "r"(b0), "r"(b1));
}
__device__ __forceinline__ void ldsm4t_p(uint32_t* r, uint32_t addr) {
    asm("ldmatrix.sync.aligned.m8n8.x4.trans.shared.b16 {%0,%1,%2,%3}, [%4];" : "=r"(r[0]), "=r"(r[1]), "=r"(r[2]), "=r"(r[3]) : "r"(addr));
}
__device__ __forceinline__ uint32_t lds32_p(uint32_t addr) { uint32_t v; asm("ld.shared.u32 %0, [%1];" : "=r"(v) : "r"(addr)); return v; }
__device__ __forceinline__ uint32_t swz(uint32_t a) { return a ^ ((a >> 3) & 16u); }
__device__ __forceinline__ uint32_t swz128(uint32_t a) { return a ^ ((a >> 3) & 0x70u); }
__device__ __forceinline__ void sts32(uint32_t addr, uint32_t v) { asm volatile("st.shared.u32 [%0], %1;" :: "r"(addr), "r"(v) : "memory"); }
__device__ __forceinline__ void sts128(uint32_t addr, uint4 v) { asm volatile("st.shared.v4.u32 [%0], {%1,%2,%3,%4};" :: "r"(addr), "r"(v.x), "r"(v.y), "r"(v.z), "r"(v.w) : "memory"); }
__device__ __forceinline__ uint4 lds128(uint32_t addr) { uint4 v; asm volatile("ld.shared.v4.u32 {%0,%1,%2,%3}, [%4];" : "=r"(v.x), "=r"(v.y), "=r"(v.z), "=r"(v.w) : "r"(addr) : "memory"); return v; }
__device__ __forceinline__ void quad_transpose(uint32_t* v, int t) {
    #pragma unroll
    for (int p = 0; p < 2; p++) {
        const uint32_t x = __shfl_xor_sync(0xffffffffu, (t & 1) ? v[2 * p] : v[2 * p + 1], 1);
        if (t & 1) v[2 * p] = x; else v[2 * p + 1] = x;
    }
    #pragma unroll
    for (int p = 0; p < 2; p++) {
        const uint32_t x = __shfl_xor_sync(0xffffffffu, (t & 2) ? v[p] : v[p + 2], 2);
        if (t & 2) v[p] = x; else v[p + 2] = x;
    }
}
__device__ __forceinline__ float ex2f(float x) { float r; asm("ex2.approx.ftz.f32 %0, %1;" : "=f"(r) : "f"(x)); return r; }
__device__ __forceinline__ uint32_t pack_bf16(float lo, float hi) { uint32_t r; asm("cvt.rn.bf16x2.f32 %0, %1, %2;" : "=r"(r) : "f"(hi), "f"(lo)); return r; }
__device__ __forceinline__ uint32_t pack_f16(float lo, float hi) { uint32_t r; asm("cvt.rn.f16x2.f32 %0, %1, %2;" : "=r"(r) : "f"(hi), "f"(lo)); return r; }
__device__ __forceinline__ float bf_lo(uint32_t v) { return __uint_as_float(v << 16); }
__device__ __forceinline__ float bf_hi(uint32_t v) { return __uint_as_float(v & 0xFFFF0000u); }
__device__ __forceinline__ float bf_round(float x) { return __bfloat162float(__float2bfloat16_rn(x)); }

__device__ __forceinline__ uint32_t exp_mufu(float x0, float x1) { return pack_bf16(ex2f(x0), ex2f(x1)); }
#define SW_MAGIC (256.0f + 127.0f - 0.598938f)
__device__ __forceinline__ uint32_t exp_sw(float x0, float x1, uint32_t cA, uint32_t cB) {
    float t0 = x0 + SW_MAGIC, t1 = x1 + SW_MAGIC;
    uint32_t L, mh, ec, r;
    asm("prmt.b32 %0, %1, %2, 0x6521;" : "=r"(L) : "r"(__float_as_uint(t0)), "r"(__float_as_uint(t1)));
    asm("lop3.b32 %0, %1, 0x007F007F, %2, 0xEA;" : "=r"(mh) : "r"(L), "r"(cA));
    asm("lop3.b32 %0, %1, 0x7F807F80, %2, 0xEA;" : "=r"(ec) : "r"(L), "r"(cB));
    asm("fma.rn.bf16x2 %0, %1, %2, %3;" : "=r"(r) : "r"(L), "r"(mh), "r"(ec));
    return r;
}
constexpr uint32_t MUFU_MASK = 0x4949;

struct cf { float x, y; };
__device__ __forceinline__ cf cmul(cf a, cf b) { cf r; r.x = a.x * b.x - a.y * b.y; r.y = a.x * b.y + a.y * b.x; return r; }
__device__ __forceinline__ cf cexp_p(float a2, float b, float p) {
    float e = ex2f(a2 * p);
    float ph = b * p;
    ph -= (ph + 12582912.0f) - 12582912.0f;
    float ang = ph * 6.283185307f;
    cf r; r.x = e * __cosf(ang); r.y = e * __sinf(ang);
    return r;
}
__device__ __forceinline__ uint32_t h2_cmul(uint32_t w, uint32_t wsw, uint32_t e) {
    __half2 hw = *(__half2*)&w, hs = *(__half2*)&wsw, he = *(__half2*)&e;
    __half2 r = __hfma2(hs, __high2half2(he), __hmul2(hw, __low2half2(he)));
    return *(uint32_t*)&r;
}

template<bool B> struct BoolC { static constexpr bool value = B; };
struct Params {
    const __nv_bfloat16 *u, *lar, *aim, *cre, *cim, *logdt, *dskip;
    __nv_bfloat16* out;
};

constexpr int B_O = 0, B_KV = 8, B_WO = 12, B_WQ2 = 13, B_ST = 14, B_H = 15, B_X = 17, B_U = 19, B_WQ = 20;

__device__ __forceinline__ void helper_role(const Params& P, uint8_t* sp, uint32_t sb, unsigned epoch) {
    const uint32_t sBa = sb + SM_B;
    const int tid = threadIdx.x - 544;
    const int d0 = blockIdx.x * 4;
    uint8_t* sB = sp + SM_B;
    const uint2 dsk = __ldg((const uint2*)(P.dskip + d0));
    asm volatile("barrier.cluster.wait.aligned;" ::: "memory");
    {
        const int hg = blockIdx.x & 7;
        if (hg < 4 && tid < 32) {
            bar_sync(3, 160);
            if (tid == 0) {
                const float* s_misc = (const float*)(sp + SM_BAR + 256);
                const float st = fmaxf(fmaxf(s_misc[20], s_misc[21]), fmaxf(s_misc[22], s_misc[23]));
                st_release64(&g_flag_kv[((blockIdx.x >> 3) * 2 + (hg & 1)) * 2 + (hg >> 1)], ((unsigned long long)epoch << 32) | __float_as_uint(st));
            }
            __syncwarp();
        }
    }
    PROF2(2);
    bar_sync(10, 608);
    {
        uint32_t dd[4] = {__byte_perm(dsk.x, 0, 0x1010), __byte_perm(dsk.x, 0, 0x3232), __byte_perm(dsk.y, 0, 0x1010), __byte_perm(dsk.y, 0, 0x3232)};
        #pragma unroll 2
        for (int pi = tid; pi < 1024; pi += 96) {
            const int l = 2 * pi;
            uint32_t r[4];
            #pragma unroll
            for (int cc = 0; cc < 4; cc++) {
                const uint32_t y2 = *(const uint32_t*)(sB + S_Y + cc * 4096 + l * 2);
                const uint32_t u2 = lds32(swz128(sBa + S_U + cc * ULEN * 2 + (PADU + l) * 2));
                __nv_bfloat162 pr = __hmul2(*(const __nv_bfloat162*)&u2, *(const __nv_bfloat162*)&dd[cc]);
                __nv_bfloat162 sm = __hadd2(*(const __nv_bfloat162*)&y2, pr);
                r[cc] = *(uint32_t*)&sm;
            }
            *(uint2*)(P.out + (size_t)l * 1024 + 512 + d0) = make_uint2(__byte_perm(r[0], r[1], 0x5410), __byte_perm(r[2], r[3], 0x5410));
            *(uint2*)(P.out + (size_t)(l + 1) * 1024 + 512 + d0) = make_uint2(__byte_perm(r[0], r[1], 0x7632), __byte_perm(r[2], r[3], 0x7632));
        }
    }
    bar_arrive(11, 128);
    PROF2(4);
}

__global__ void __cluster_dims__(2, 1, 1) __launch_bounds__(NTHR, 1)
fused_kernel(const __grid_constant__ CUtensorMap tm_x, const __grid_constant__ CUtensorMap tm_wq,
             const __grid_constant__ CUtensorMap tm_wo, const __grid_constant__ CUtensorMap tm_wk,
             const __grid_constant__ CUtensorMap tm_wv, const __grid_constant__ CUtensorMap tm_u, const Params P) {
    extern __shared__ uint8_t smem_raw[];
    const uint32_t sb = (smem_u32(smem_raw) + 1023u) & ~1023u;
    uint8_t* sp = smem_raw + (sb - smem_u32(smem_raw));

    const int tid = threadIdx.x, warp = tid >> 5, lane = tid & 31, wg = tid >> 7, wiw = warp & 3;
    const int g = lane >> 2, t = lane & 3;
    const int qb = blockIdx.x >> 3, hg = blockIdx.x & 7;
    const uint32_t rank = blockIdx.x & 1;
    const int rowhalf = wg & 1, nh = wg >> 1;
    const bool kv_cta = hg < 4;
    const int kv_sel = hg >> 1;
    const bool kv_wg = kv_cta && (wg == 2 + (hg & 1));

    const uint32_t bars = sb + SM_BAR;
    float* s_misc = (float*)(sp + SM_BAR + 256);
    const CUtensorMap* tm_kv = kv_sel ? &tm_wv : &tm_wk;

    PROF(0);
    unsigned short p_lar = 0, p_aim = 0, p_cre = 0, p_cim = 0, p_ldt = 0;
    if (wg < 4) {
        const int n = (blockIdx.x * 4 + wg) * 128 + (tid & 127);
        p_lar = __ldg((const unsigned short*)P.lar + n);
        p_aim = __ldg((const unsigned short*)P.aim + n);
        p_cre = __ldg((const unsigned short*)P.cre + n);
        p_cim = __ldg((const unsigned short*)P.cim + n);
        p_ldt = __ldg((const unsigned short*)P.logdt + blockIdx.x * 4 + wg);
    } else if (warp == 16) {
        PROF3(5);
        if (lane == 0) {
            asm volatile("prefetch.tensormap [%0];" :: "l"((uint64_t)&tm_x) : "memory");
            asm volatile("prefetch.tensormap [%0];" :: "l"((uint64_t)tm_kv) : "memory");
            asm volatile("prefetch.tensormap [%0];" :: "l"((uint64_t)&tm_wq) : "memory");
            asm volatile("prefetch.tensormap [%0];" :: "l"((uint64_t)&tm_u) : "memory");
            mbar_init(bars + 8 * B_X, 1);
            mbar_init(bars + 8 * B_X + 8, 1);
            mbar_init(bars + 8 * B_U, 1);
            asm volatile("fence.mbarrier_init.release.cluster;" ::: "memory");
            mbar_expect_tx(bars + 8 * B_X, 65536u + (kv_cta ? 8192u : 0u));
            mbar_expect_tx(bars + 8 * B_X + 8, 65536u + (kv_cta ? 8192u : 0u));
            mbar_expect_tx(bars + 8 * B_U, 32768u);
        }
        __syncwarp();
        PROF3(6);
    }
    asm volatile("barrier.cluster.arrive.relaxed.aligned;" ::: "memory");
    const unsigned epoch = *(volatile unsigned*)&g_epoch + 1u;
    if (warp > 16) {
        if (lane == 0) {
            for (int i = warp - 17; i < B_X; i += 3) {
                mbar_init(bars + 8 * i, i >= B_H ? 2 : 1);
                if (i <= B_WQ2) mbar_expect_tx(bars + 8 * i, i < B_KV + 2 ? 16384u : i == B_KV + 2 ? 32768u : i <= B_WO ? 65536u : 32768u);
            }
            asm volatile("fence.mbarrier_init.release.cluster;" ::: "memory");
            fence_async_smem();
        } else if (warp == 19) {
            #pragma unroll
            for (int i = 0; i < 2; i++) if (lane - 1 + 31 * i < 46) asm volatile("prefetch.global.L2 [%0];" :: "l"((const char*)g_tabmap.v + (lane - 1 + 31 * i) * 128));
        }
        __syncwarp();
    }
    asm volatile("barrier.cluster.wait.aligned;" ::: "memory");
    PROF(5);
    if (warp == 16 && lane == 0) {
        tma_3d_mc(sb + (rank ? SM_A : SM_B), &tm_x, 0, qb * 128, rank * 4, bars + 8 * (B_X + rank));
        if (kv_cta) {
            #pragma unroll
            for (int i = 0; i < 4; i++) tma_2d(sb + SM_WKV + i * 4096, tm_kv, (i >> 1) * 8, (i & 1) * 256, bars + 8 * (B_X + (i & 1)));
        }
        mbar_init(bars + 8 * B_WQ, 1);
        asm volatile("fence.mbarrier_init.release.cluster;" ::: "memory");
        fence_async_smem();
        mbar_expect_tx(bars + 8 * B_WQ, 32768u);
        tma_2d(sb + SM_WQ, &tm_wq, hg * 64, 0, bars + 8 * B_WQ);
        #pragma unroll
        for (int i = 0; i < 4; i++) tma_2d_mc(sb + SM_SLAB + (rank * 4 + i) * 4096, &tm_u, (blockIdx.x >> 1) * 8, (rank * 4 + i) * 256, bars + 8 * B_U);
    }
    __syncwarp();
    asm volatile("barrier.cluster.arrive.relaxed.aligned;" ::: "memory");

    if (warp == 16) {
        if (lane == 0) asm volatile("prefetch.tensormap [%0];" :: "l"((uint64_t)&tm_wo) : "memory");
        asm volatile("barrier.cluster.wait.aligned;" ::: "memory");
        PROF3(10);
        bar_sync(13, 544);
        if (lane == 0) { fence_async_smem(); tma_2d(sb + SM_SLAB, &tm_wq, hg * 64, 256, bars + 8 * B_WQ2); }
        bar_sync(14, 288);
        if (lane == 0) pair_sync(bars + 8 * B_H, rank ^ 1);
        __syncwarp();
        PROF3(11);
        *(uint4*)(sp + SM_V + 32768 + lane * 32) = make_uint4(0x3F803F80u, 0x3F803F80u, 0x3F803F80u, 0x3F803F80u);
        *(uint4*)(sp + SM_V + 32768 + lane * 32 + 16) = make_uint4(0x3F803F80u, 0x3F803F80u, 0x3F803F80u, 0x3F803F80u);
        fence_async_smem();
        float km = wait_flag64(&g_flag_kv[2 * lane], epoch);
        float vm = wait_flag64(&g_flag_kv[2 * lane + 1], epoch);
        __syncwarp();
        PROF3(12);
        if (lane == 0) {
            fence_async_all();
            #pragma unroll
            for (int i = 0; i < 4; i++) {
                const uint32_t k0 = i == 0 ? 0 : 128u << i, nk = i == 0 ? 256 : 128u << i;
                const uint32_t bar = bars + 8 * (B_KV + i);
                if (rank == 0) bulk_g2s_mc(sb + SM_K + k0 * 32, g_kimg + k0 * 32, nk * 32, bar);
                else {
                    bulk_g2s_mc(sb + SM_V + k0 * 16, g_vimg + k0 * 16, nk * 16, bar);
                    bulk_g2s_mc(sb + SM_V + 66560 - (k0 + nk) * 16, g_vimg + 66560 - (k0 + nk) * 16, nk * 16, bar);
                }
            }
        }
        #pragma unroll
        for (int o = 16; o; o >>= 1) { km = fmaxf(km, __shfl_xor_sync(0xffffffffu, km, o)); vm = fmaxf(vm, __shfl_xor_sync(0xffffffffu, vm, o)); }
        if (lane == 0) { s_misc[16] = km; s_misc[17] = vm; mbar_arrive(bars + 8 * B_ST); }
        PROF3(13);
        bar_sync(11, 128);
        if (lane < 2) { fence_async_smem(); tma_2d(sb + SM_B + lane * 32768, &tm_wo, hg * 64, lane * 256, bars + 8 * B_WO); }
        bar_sync(12, 544);
        if (lane == 0) {
            st_release(&g_flag_o[blockIdx.x], epoch);
            pair_sync(bars + 8 * (B_H + 1), rank ^ 1);
        }
        __syncwarp();
        PROF3(14);
        if (lane < 4) {
            const int src = (2 * lane + (hg & 6) + rank) & 7;
            wait_flag(&g_flag_o[qb * 8 + src], epoch);
            fence_async_all();
            bulk_g2s_mc(sb + SM_A + src * 16384, g_oimg + qb * 131072 + src * 16384, 16384, bars + 8 * (B_O + src));
        }
        __syncwarp();
        PROF3(15);
        if (lane == 0) {
            const unsigned prev = atomicAdd(&g_done, 1u);
            if (prev == NCTA - 1) {
                g_done = 0;
                __threadfence();
                *(volatile unsigned*)&g_epoch = epoch;
            }
        }
    } else if (wg == 4) {
        helper_role(P, sp, sb, epoch);
    } else {
        uint8_t* sB = sp + SM_B;
        const uint32_t sBa = sb + SM_B;
        {
            const int c = wg;
            const float dt = bf_round(expf(bf_lo(p_ldt)));
            const float are = -bf_round(expf(bf_lo(p_lar))) * dt;
            const float aim = bf_lo(p_aim) * dt;
            float cr = 2.0f * (bf_lo(p_cre) * dt);
            float ci = 2.0f * (bf_lo(p_cim) * dt);
            const float a2 = are * 1.4426950408889634f, bb = aim * 0.15915494309189535f;
            float m = fmaxf(fabsf(cr), fabsf(ci));
            #pragma unroll
            for (int o = 16; o; o >>= 1) m = fmaxf(m, __shfl_xor_sync(0xffffffffu, m, o));
            int ebits = (__float_as_uint(m) >> 23) & 0xFF;
            ebits = min(max(ebits, 2), 250);
            const float scale = __uint_as_float((uint32_t)(ebits + 1) << 23);
            const float iscale = __uint_as_float((uint32_t)(253 - ebits) << 23);
            cf cc; cc.x = cr * iscale; cc.y = ci * iscale;

            const uint32_t stg = sBa + S_KC + warp * 1024;
            uint4* stp = (uint4*)(sB + S_KC + warp * 1024 + lane * 32);
            const uint32_t fa = stg + t * 32 + g * 4;

            uint32_t af[4][2][4];
            cf E256;
            {
                const cf E8 = cexp_p(a2, bb, 8.0f);
                uint32_t w[8];
                cf cur; cur.x = 1.0f; cur.y = 0.0f;
                w[0] = pack_f16(1.0f, 0.0f);
                cur = E8; w[1] = pack_f16(cur.x, cur.y);
                #pragma unroll
                for (int i = 2; i < 8; i++) { cur = cmul(cur, E8); w[i] = pack_f16(cur.x, cur.y); }
                stp[0] = make_uint4(w[0], w[1], w[2], w[3]);
                stp[1] = make_uint4(w[4], w[5], w[6], w[7]);
                const cf E64 = cexp_p(a2, bb, 64.0f);
                const cf E128 = cmul(E64, E64), E192 = cmul(E128, E64);
                E256 = cexp_p(a2, bb, 256.0f);
                const uint32_t e1 = pack_f16(E64.x, E64.y), e2 = pack_f16(E128.x, E128.y), e3 = pack_f16(E192.x, E192.y);
                __syncwarp();
                #pragma unroll
                for (int s = 0; s < 4; s++) {
                    #pragma unroll
                    for (int hh = 0; hh < 2; hh++) {
                        const uint32_t w0 = lds32(fa + s * 256 + hh * 128);
                        const uint32_t wsw = __byte_perm(w0, 0, 0x1032) ^ 0x00008000u;
                        const int src = 8 * s + t + 4 * hh;
                        const uint32_t f1 = __shfl_sync(0xffffffffu, e1, src), f2 = __shfl_sync(0xffffffffu, e2, src), f3 = __shfl_sync(0xffffffffu, e3, src);
                        af[s][0][2 * hh] = w0;
                        af[s][0][2 * hh + 1] = h2_cmul(w0, wsw, f1);
                        af[s][1][2 * hh] = h2_cmul(w0, wsw, f2);
                        af[s][1][2 * hh + 1] = h2_cmul(w0, wsw, f3);
                    }
                }
                __syncwarp();
            }
            float acc[2][3][4];
            #pragma unroll
            for (int i = 0; i < 24; i++) (&acc[0][0][0])[i] = 0.0f;
            const cf E1 = cexp_p(a2, bb, 1.0f);
            const cf E2 = cmul(E1, E1), E4 = cmul(E2, E2);
            cf X512;
            #pragma unroll
            for (int nt = 0; nt < 3; nt++) {
                uint32_t xv[8];
                if (nt == 0) {
                    cf cur = cc;
                    xv[0] = pack_f16(cur.x, -cur.y);
                    #pragma unroll
                    for (int i = 1; i < 8; i++) { cur = cmul(cur, E1); xv[i] = pack_f16(cur.x, -cur.y); }
                } else if (nt == 1) {
                    cf cur = cmul(cc, E256);
                    X512 = cmul(cur, E256);
                    xv[0] = pack_f16(cur.x, -cur.y);
                    #pragma unroll
                    for (int i = 1; i < 4; i++) { cur = cmul(cur, E2); xv[i] = pack_f16(cur.x, -cur.y); }
                    cur = cmul(X512, E4);
                    xv[4] = pack_f16(X512.x, -X512.y); xv[5] = pack_f16(cur.x, -cur.y);
                    X512 = cmul(X512, E256);
                    cur = cmul(X512, E4);
                    xv[6] = pack_f16(X512.x, -X512.y); xv[7] = pack_f16(cur.x, -cur.y);
                } else {
                    cf cur = X512;
                    #pragma unroll
                    for (int i = 0; i < 5; i++) { cur = cmul(cur, E256); xv[i] = pack_f16(cur.x, -cur.y); }
                    xv[5] = 0; xv[6] = 0; xv[7] = 0;
                }
                stp[0] = make_uint4(xv[0], xv[1], xv[2], xv[3]);
                stp[1] = make_uint4(xv[4], xv[5], xv[6], xv[7]);
                __syncwarp();
                #pragma unroll
                for (int s = 0; s < 4; s++) {
                    const uint32_t b0 = lds32(fa + s * 256), b1 = lds32(fa + s * 256 + 128);
                    mma_f16(acc[0][nt], af[s][0], b0, b1);
                    mma_f16(acc[1][nt], af[s][1], b0, b1);
                }
                __syncwarp();
            }
            float* kc = (float*)(sB + S_KC + c * 4096);
            bar_sync(4 + c, 128);
            #pragma unroll 1
            for (int step = 0; step < 4; step++) {
                if ((warp & 3) == step) {
                    #pragma unroll
                    for (int mt = 0; mt < 2; mt++)
                        #pragma unroll
                        for (int nt = 0; nt < 3; nt++)
                            #pragma unroll
                            for (int hh = 0; hh < 2; hh++) {
                                float2* p = (float2*)(kc + (mt * 16 + hh * 8 + g) * 24 + nt * 8 + 2 * t);
                                float2 v = make_float2(acc[mt][nt][2 * hh] * scale, acc[mt][nt][2 * hh + 1] * scale);
                                if (step) { float2 o = *p; v.x += o.x; v.y += o.y; }
                                *p = v;
                            }
                }
                if (step < 3) bar_sync(4 + c, 128);
            }
        }

        asm volatile("barrier.cluster.wait.aligned;" ::: "memory");
        PROF(4);
        uint32_t q[2][4];
        {
            const uint64_t dA0 = make_desc(sb + SM_B + rowhalf * 8192, 16, 1024, 1);
            const uint64_t dA1 = make_desc(sb + SM_A + rowhalf * 8192, 16, 1024, 1) - 4096;
            uint4* qx = (uint4*)(sp + SM_B + S_QX) + (tid & 255) * 2;
            auto stage_u = [&]() {
                #pragma unroll
                for (int i = 0; i < 1; i++) {
                    const int z = tid + 512 * i;
                    if (z < 4 * 80) sts128(sBa + S_U + (z / 80) * ULEN * 2 + (PADU - 640) * 2 + (z % 80) * 16, make_uint4(0, 0, 0, 0));
                }
                mbar_wait(bars + 8 * B_U, 0);
                #pragma unroll
                for (int i = 0; i < 2; i++) {
                    const int l = 2 * (tid + 512 * i);
                    const uint2 r0 = *(const uint2*)(sp + SM_SLAB + l * 16 + rank * 8), r1 = *(const uint2*)(sp + SM_SLAB + l * 16 + 16 + rank * 8);
                    const uint32_t dst = swz128(sBa + S_U + (PADU + l) * 2);
                    sts32(dst, __byte_perm(r0.x, r1.x, 0x5410));
                    sts32(dst + ULEN * 2, __byte_perm(r0.x, r1.x, 0x7632));
                    sts32(dst + ULEN * 4, __byte_perm(r0.y, r1.y, 0x5410));
                    sts32(dst + ULEN * 6, __byte_perm(r0.y, r1.y, 0x7632));
                }
                fence_async_smem();
                bar_arrive(13, 544);
            };
            if (wg < 2) {
                float acc[32];
                #pragma unroll
                for (int i = 0; i < 32; i++) acc[i] = 0.0f;
                fence_regs<32>(acc);
                const uint64_t dB = make_desc(sb + SM_WQ, 16, 1024, 1);
                mbar_wait(bars + 8 * B_WQ, 0);
                mbar_wait(bars + 8 * B_X, 0);
                PROF(2);
                #pragma unroll 1
                for (int ch = 0; ch < 4; ch++) {
                    wg_fence();
                    #pragma unroll
                    for (int ks = 0; ks < 4; ks++) wg_ss64(acc, dA0 + ch * 1024 + ks * 2, dB + (ch * 4 + ks) * 128);
                    wg_commit();
                }
                wg_wait<0>();
                fence_regs<32>(acc);
                bar_sync(1, 512);
                PROF(15);
                stage_u();
                bar_arrive(2, 512);
                PROF(1);
                mbar_wait(bars + 8 * B_WQ2, 0);
                mbar_wait(bars + 8 * (B_X + 1), 0);
                fence_regs<32>(acc);
                #pragma unroll 1
                for (int ch = 4; ch < 8; ch++) {
                    wg_fence();
                    #pragma unroll
                    for (int ks = 0; ks < 4; ks++) wg_ss64(acc, dA1 + ch * 1024 + ks * 2, dB + (ch * 4 + ks) * 128);
                    wg_commit();
                }
                wg_wait<0>();
                fence_regs<32>(acc);
                bar_arrive(14, 288);
                const float QS = 0.25f * 1.4426950408889634f;
                float qm = 0.0f;
                uint32_t qa[4][4];
                #pragma unroll
                for (int i = 0; i < 4; i++) {
                    #pragma unroll
                    for (int j = 0; j < 4; j++) qa[i][j] = pack_bf16(bf_round(acc[8 * i + 2 * j]) * QS, bf_round(acc[8 * i + 2 * j + 1]) * QS);
                    float n0 = bf_lo(qa[i][0]) * bf_lo(qa[i][0]) + bf_hi(qa[i][0]) * bf_hi(qa[i][0]) + bf_lo(qa[i][2]) * bf_lo(qa[i][2]) + bf_hi(qa[i][2]) * bf_hi(qa[i][2]);
                    float n1 = bf_lo(qa[i][1]) * bf_lo(qa[i][1]) + bf_hi(qa[i][1]) * bf_hi(qa[i][1]) + bf_lo(qa[i][3]) * bf_lo(qa[i][3]) + bf_hi(qa[i][3]) * bf_hi(qa[i][3]);
                    n0 += __shfl_xor_sync(0xffffffffu, n0, 1); n0 += __shfl_xor_sync(0xffffffffu, n0, 2);
                    n1 += __shfl_xor_sync(0xffffffffu, n1, 1); n1 += __shfl_xor_sync(0xffffffffu, n1, 2);
                    qm = (n0 != n0 || n1 != n1) ? __int_as_float(0x7f800000) : fmaxf(qm, fmaxf(n0, n1));
                }
                #pragma unroll
                for (int o = 16; o; o >>= 1) qm = fmaxf(qm, __shfl_xor_sync(0xffffffffu, qm, o));
                if (lane == 0) s_misc[warp] = qm;
                qx[0] = make_uint4(qa[2][0], qa[2][1], qa[2][2], qa[2][3]);
                qx[1] = make_uint4(qa[3][0], qa[3][1], qa[3][2], qa[3][3]);
                #pragma unroll
                for (int j = 0; j < 4; j++) { q[0][j] = qa[0][j]; q[1][j] = qa[1][j]; }
                bar_sync(1, 512);
            } else {
                if (kv_wg) {
                    float akv[8];
                    #pragma unroll
                    for (int i = 0; i < 8; i++) akv[i] = 0.0f;
                    fence_regs<8>(akv);
                    const uint64_t dC = make_desc(sb + SM_WKV, 128, 8192, 0);
                    #pragma unroll 1
                    for (int ch = 0; ch < 8; ch++) {
                        if ((ch & 3) == 0) mbar_wait(bars + 8 * (B_X + (ch >> 2)), 0);
                        const uint64_t dA = ch < 4 ? dA0 : dA1;
                        wg_fence();
                        #pragma unroll
                        for (int ks = 0; ks < 4; ks++) wg_ss16(akv, dA + ch * 1024 + ks * 2, dC + (ch * 4 + ks) * 16);
                        wg_commit();
                    }
                    wg_wait<0>();
                    fence_regs<8>(akv);
                    const int key = qb * 128 + rowhalf * 64 + wiw * 16 + g;
                    uint32_t pk[4];
                    #pragma unroll
                    for (int i = 0; i < 4; i++) pk[i] = pack_bf16(akv[2 * i], akv[2 * i + 1]);
                    float st;
                    if (kv_sel == 0) {
                        uint8_t* b = g_kimg + (key >> 3) * 256 + (key & 7) * 16 + 4 * t;
                        *(uint32_t*)(b) = pk[0]; *(uint32_t*)(b + 256) = pk[1]; *(uint32_t*)(b + 128) = pk[2]; *(uint32_t*)(b + 384) = pk[3];
                        float n0 = bf_lo(pk[0]) * bf_lo(pk[0]) + bf_hi(pk[0]) * bf_hi(pk[0]) + bf_lo(pk[2]) * bf_lo(pk[2]) + bf_hi(pk[2]) * bf_hi(pk[2]);
                        float n1 = bf_lo(pk[1]) * bf_lo(pk[1]) + bf_hi(pk[1]) * bf_hi(pk[1]) + bf_lo(pk[3]) * bf_lo(pk[3]) + bf_hi(pk[3]) * bf_hi(pk[3]);
                        n0 += __shfl_xor_sync(0xffffffffu, n0, 1); n0 += __shfl_xor_sync(0xffffffffu, n0, 2);
                        n1 += __shfl_xor_sync(0xffffffffu, n1, 1); n1 += __shfl_xor_sync(0xffffffffu, n1, 2);
                        st = (n0 != n0 || n1 != n1) ? __int_as_float(0x7f800000) : fmaxf(n0, n1);
                    } else {
                        uint8_t* lo = g_vimg + key * 16 + 4 * t;
                        uint8_t* hi = g_vimg + 33792 + (31 - (key >> 6)) * 1024 + (key & 63) * 16 + 4 * t;
                        *(uint32_t*)(lo) = pk[0]; *(uint32_t*)(lo + 128) = pk[1]; *(uint32_t*)(hi) = pk[2]; *(uint32_t*)(hi + 128) = pk[3];
                        st = 0.0f;
                        #pragma unroll
                        for (int i = 0; i < 4; i++) {
                            float a = fabsf(bf_lo(pk[i])), b = fabsf(bf_hi(pk[i]));
                            st = (a != a || b != b) ? __int_as_float(0x7f800000) : fmaxf(st, fmaxf(a, b));
                        }
                    }
                    #pragma unroll
                    for (int o = 16; o; o >>= 1) st = fmaxf(st, __shfl_xor_sync(0xffffffffu, st, o));
                    if (lane == 0) s_misc[20 + wiw] = st;
                bar_arrive(3, 160);
                }
                uint2 mp[3];
                #pragma unroll
                for (int i = 0; i < 3; i++) { const int w = (tid & 255) + 256 * i; mp[i] = (w < TABN / 4) ? __ldg((const uint2*)g_tabmap.v + w) : make_uint2(0u, 0u); }
                bar_sync(1, 512);
                stage_u();
                #pragma unroll 1
                for (int cc = 0; cc < 4; cc++) {
                    const float* kc = (const float*)(sB + S_KC + cc * 4096);
                    uint2* tab = (uint2*)(sB + S_TAB + cc * TABN * 2);
                    #pragma unroll
                    for (int i = 0; i < 3; i++) {
                        const int w = (tid & 255) + 256 * i;
                        if (w < TABN / 4) tab[w] = make_uint2(pack_bf16(kc[mp[i].x & 0xFFFF], kc[mp[i].x >> 16]), pack_bf16(kc[mp[i].y & 0xFFFF], kc[mp[i].y >> 16]));
                    }
                }
                bar_sync(2, 512);
                #pragma unroll 1
                for (int tk = tid & 255; tk < 4 * 130; tk += 256) {
                    const int c = tk / 130, i = tk % 130;
                    const uint32_t src = sBa + S_U + c * ULEN * 2 + (PADU + 8 * i - WPAD - 8) * 2;
                    const uint4 v0 = lds128(swz128(src)), v1 = lds128(swz128(src + 16)), v2 = lds128(swz128(src + 32));
                    float x[16];
                    const uint32_t vv[8] = {v0.z, v0.w, v1.x, v1.y, v1.z, v1.w, v2.x, v2.y};
                    #pragma unroll
                    for (int k = 0; k < 8; k++) { x[2 * k] = bf_lo(vv[k]); x[2 * k + 1] = bf_hi(vv[k]); }
                    float p2[15], w7[8], w9[8];
                    #pragma unroll
                    for (int e = 0; e < 15; e++) p2[e] = x[e] + x[e + 1];
                    #pragma unroll
                    for (int e = 0; e < 8; e++) {
                        w7[e] = (p2[e + 1] + p2[e + 3]) + (p2[e + 5] + x[e + 7]);
                        w9[e] = w7[e] + (x[e] + x[e + 8]);
                    }
                    sts128(swz(sBa + S_W7 + c * W3LEN * 2 + i * 16), make_uint4(pack_bf16(w7[0], w7[1]), pack_bf16(w7[2], w7[3]), pack_bf16(w7[4], w7[5]), pack_bf16(w7[6], w7[7])));
                    sts128(swz(sBa + S_W9 + c * W3LEN * 2 + i * 16), make_uint4(pack_bf16(w9[0], w9[1]), pack_bf16(w9[2], w9[3]), pack_bf16(w9[4], w9[5]), pack_bf16(w9[6], w9[7])));
                }
                bar_sync(1, 512);
                const uint4 q0 = qx[0], q1 = qx[1];
                q[0][0] = q0.x; q[0][1] = q0.y; q[0][2] = q0.z; q[0][3] = q0.w;
                q[1][0] = q1.x; q[1][1] = q1.y; q[1][2] = q1.z; q[1][3] = q1.w;
            }
        }
        PROF(3);
        {
            const int c = wg;
            uint32_t sBl = sBa;
            asm volatile("" : "+r"(sBl) :: "memory");
            float acc[16];
            const uint32_t tabc = sBl + S_TAB + c * TABN * 2;
            const uint32_t tD = tabc + ((g & 1) ? (TD1 + CD + 1) : (TD0 + CD)) * 2 - (g - 2 * t) * 2 - 32 * wiw;
            const uint32_t uLo = (((sBl + S_U + c * ULEN * 2 + PADU * 2) & 0x3FFFF) >> 4) | (1u << 16);
            uint32_t A[2][4][4];
            auto load_set = [&](uint32_t (&X)[4][4], uint32_t a) {
                X[0][2] = lds32(a + 16);
                #pragma unroll
                for (int i = 0; i < 4; i++) { X[i][0] = lds32(a - 32 * i); X[i][1] = lds32(a - 32 * i - 16); }
                #pragma unroll
                for (int i = 0; i < 4; i++) {
                    asm volatile("mov.b32 %0, %1;" : "=r"(X[i][3]) : "r"(X[i][0]));
                    if (i < 3) asm volatile("mov.b32 %0, %1;" : "=r"(X[i + 1][2]) : "r"(X[i][1]));
                }
            };
            {
                float accB[12];
                #pragma unroll
                for (int i = 0; i < 12; i++) accB[i] = 0.0f;
                fence_regs<12>(accB);
                #pragma unroll 1
                for (int m0 = 29; m0 < 69; m0 += 8) {
                    #pragma unroll
                    for (int h = 0; h < 2; h++) {
                        load_set(A[h], tD - 32 * (m0 + 4 * h));
                        wg_fence();
                        #pragma unroll
                        for (int i = 0; i < 4; i++) wg_rs24(accB, A[h][i], uLo + 64 - 2 * (m0 + 4 * h + i));
                        wg_commit();
                        wg_wait<1>();
                    }
                }
                wg_wait<0>();
                fence_regs<12>(accB);
                #pragma unroll
                for (int i = 0; i < 4; i++) acc[i] = 0.0f;
                #pragma unroll
                for (int i = 0; i < 12; i++) asm volatile("add.f32 %0, %1, 0f00000000;" : "=f"(acc[4 + i]) : "f"(accB[i]));
                fence_regs<16>(acc);
            }
            #pragma unroll 1
            for (int m0 = -3; m0 < 29; m0 += 8) {
                #pragma unroll
                for (int h = 0; h < 2; h++) {
                    load_set(A[h], tD - 32 * (m0 + 4 * h));
                    wg_fence();
                    #pragma unroll
                    for (int i = 0; i < 4; i++) wg_rs32(acc, A[h][i], uLo - 2 * (m0 + 4 * h + i));
                    wg_commit();
                    wg_wait<1>();
                }
            }
            wg_wait<0>();
            fence_regs<16>(acc);
            PROF(6);
            {
                asm volatile("" : "+r"(sBl) :: "memory");
                const int mi = lane >> 3, r8 = lane & 7;
                const uint32_t frag = (16 * (8 * (mi >> 1) + r8) + 8 * (mi & 1)) * 2;
                const uint32_t t3 = sBl + S_TAB + c * TABN * 2 + (T3B + ((wiw & 1) ? (T3C + C3 + 1) : C3)) * 2 - (4 * g + wiw - 2 * t) * 2;
                #pragma unroll
                for (int s = 0; s < 2; s++) {
                    const uint32_t sig = swz(sBl + (s ? S_W7 : S_W9) + c * W3LEN * 2 + WPAD * 2 + frag - (s ? 16 : 32));
                    uint32_t a[4][4], R[4][2];
                    #pragma unroll
                    for (int b = 0; b < 4; b++) ldsm4t_p(a[b], sig + b * 512);
                    #pragma unroll
                    for (int i = 0; i < 4; i++) { R[i][0] = lds32_p(t3 + s * (T3S * 2) - 2 * (48 + 16 * i)); R[i][1] = lds32_p(t3 + s * (T3S * 2) - 2 * (40 + 16 * i)); }
                    #pragma unroll
                    for (int b = 0; b < 4; b++) {
                        mma_bf16_p(acc + 12, a[b][0], a[b][1], a[b][2], a[b][3], R[3 - b][0], R[3 - b][1]);
                        if (b < 2) mma_bf16_p(acc + 8, a[b][0], a[b][1], a[b][2], a[b][3], R[1 - b][0], R[1 - b][1]);
                    }
                }
            }
            __nv_bfloat16* ys = (__nv_bfloat16*)(sB + S_Y + c * 4096) + 128 * t + 16 * wiw + g;
            #pragma unroll
            for (int j = 0; j < 4; j++) {
                ys[512 * j] = __float2bfloat16_rn(acc[4 * j]);
                ys[512 * j + 64] = __float2bfloat16_rn(acc[4 * j + 1]);
                ys[512 * j + 8] = __float2bfloat16_rn(acc[4 * j + 2]);
                ys[512 * j + 72] = __float2bfloat16_rn(acc[4 * j + 3]);
            }
        }
        bar_arrive(10, 608);
        PROF(7);
        {
            mbar_wait(bars + 8 * B_ST, 0);
            PROF(9); PROFC(8);
            float qm = 0.0f;
            #pragma unroll
            for (int i = 0; i < 8; i++) qm = fmaxf(qm, s_misc[i]);
            const float vm = s_misc[17];
            const bool fast = (qm * s_misc[16] <= 60.0f * 60.0f) && (vm <= 1.0e12f) && (vm >= 1.0e-12f || vm == 0.0f);
            uint8_t* ob = g_oimg + qb * 131072 + hg * 16384 + nh * 8192 + (rowhalf * 8 + wiw * 2) * 128 + g * 16 + 4 * t;
            uint32_t cA = 0xBF00BF00u, cB = 0x00030003u;
            asm volatile("" : "+r"(cA), "+r"(cB));
            #pragma unroll 1
            for (int tile = 0; tile < 2; tile++) {
                uint32_t kLo = (((sb + SM_K) & 0x3FFFF) >> 4) | (8u << 16), vLo = (((sb + SM_V) & 0x3FFFF) >> 4) | (8u << 16), vHi = 2048;
                float o[12], s[32];
                uint32_t p[16], qq[4];
                #pragma unroll
                for (int i = 0; i < 4; i++) { qq[i] = tile ? q[1][i] : q[0][i]; asm volatile("" : "+r"(qq[i])); }
                #pragma unroll
                for (int i = 0; i < 12; i++) o[i] = 0.0f;
                #pragma unroll
                for (int i = 0; i < 32; i++) s[i] = 0.0f;
                fence_regs<12>(o);
                fence_regs<32>(s);
                if (fast) {
                    #pragma unroll 1
                    for (int c = 0; c < SEQ / 256; c++) {
                        if (c <= 4) mbar_wait(bars + 8 * (B_KV + (c < 2 ? c : c < 4 ? 2 : 3)), 0);
                        wg_fence();
                        wg_qk(s, qq, kLo);
                        wg_commit();
                        #pragma unroll
                        for (int u = 0; u < 4; u++) {
                            wg_wait<0>();
                            fence_regs<32>(s);
                            #pragma unroll
                            for (int i = 0; i < 16; i++) {
                                if ((MUFU_MASK >> i) & 1) p[i] = exp_mufu(s[2 * i], s[2 * i + 1]);
                                else p[i] = exp_sw(s[2 * i], s[2 * i + 1], cA, cB);
                            }
                            wg_fence();
                            if (u + 1 < 4) wg_qk(s, qq, kLo + (u + 1) * 128);
                            #pragma unroll
                            for (int kk = 0; kk < 4; kk++) wg_pv(o, p + 4 * kk, vLo + u * 64 + kk * 16, vHi - u * 64);
                            wg_commit();
                        }
                        kLo += 512; vLo += 256; vHi -= 256;
                    }
                    wg_wait<0>();
                } else {
                    float mx0 = -INFINITY, mx1 = -INFINITY;
                    #pragma unroll 1
                    for (int c = 0; c < SEQ / 64; c++) {
                        if (c <= 16) mbar_wait(bars + 8 * (B_KV + (c < 8 ? (c >> 2) : c < 16 ? 2 : 3)), 0);
                        wg_fence();
                        wg_qk(s, qq, kLo);
                        wg_commit();
                        wg_wait<0>();
                        fence_regs<32>(s);
                        fence_regs<12>(o);
                        float m0 = mx0, m1 = mx1;
                        #pragma unroll
                        for (int j = 0; j < 8; j++) {
                            m0 = fmaxf(m0, fmaxf(s[4 * j], s[4 * j + 1]));
                            m1 = fmaxf(m1, fmaxf(s[4 * j + 2], s[4 * j + 3]));
                        }
                        m0 = fmaxf(m0, __shfl_xor_sync(0xffffffffu, m0, 1)); m0 = fmaxf(m0, __shfl_xor_sync(0xffffffffu, m0, 2));
                        m1 = fmaxf(m1, __shfl_xor_sync(0xffffffffu, m1, 1)); m1 = fmaxf(m1, __shfl_xor_sync(0xffffffffu, m1, 2));
                        const float c0 = ex2f(mx0 - m0), c1 = ex2f(mx1 - m1);
                        mx0 = m0; mx1 = m1;
                        #pragma unroll
                        for (int j = 0; j < 3; j++) { o[4 * j] *= c0; o[4 * j + 1] *= c0; o[4 * j + 2] *= c1; o[4 * j + 3] *= c1; }
                        #pragma unroll
                        for (int j = 0; j < 8; j++) {
                            p[2 * j] = exp_mufu(s[4 * j] - m0, s[4 * j + 1] - m0);
                            p[2 * j + 1] = exp_mufu(s[4 * j + 2] - m1, s[4 * j + 3] - m1);
                        }
                        wg_fence();
                        #pragma unroll
                        for (int kk = 0; kk < 4; kk++) wg_pv(o, p + 4 * kk, vLo + kk * 16, vHi);
                        wg_commit();
                        wg_wait<0>();
                        kLo += 128; vLo += 64; vHi -= 64;
                    }
                }
                fence_regs<12>(o);
                if (tile == 0) PROFC(3);
                const float i0 = 1.0f / o[4], i1 = 1.0f / o[6];
                uint8_t* b = ob + tile * 4096;
                *(uint32_t*)(b) = pack_bf16(o[0] * i0, o[1] * i0);
                *(uint32_t*)(b + 128) = pack_bf16(o[2] * i1, o[3] * i1);
                *(uint32_t*)(b + 2048) = pack_bf16(o[8] * i0, o[9] * i0);
                *(uint32_t*)(b + 2048 + 128) = pack_bf16(o[10] * i1, o[11] * i1);
            }
        }
        PROF(10); PROFC(9);
        bar_arrive(12, 544);

        if (wg < 2) {
            float acc[32];
            #pragma unroll
            for (int i = 0; i < 32; i++) acc[i] = 0.0f;
            fence_regs<32>(acc);
            const uint64_t dA = make_desc(sb + SM_A + rowhalf * 1024, 2048, 128, 0);
            const uint64_t dB = make_desc(sb + SM_B, 16, 1024, 1);
            mbar_wait(bars + 8 * B_WO, 0);
            #pragma unroll 1
            for (int i = 0; i < 8; i++) {
                const int src = ((hg & 6) + i) & 7;
                mbar_wait(bars + 8 * (B_O + src), 0);
                wg_fence();
                #pragma unroll
                for (int kk = 0; kk < 4; kk++) wg_ss64(acc, dA + src * 1024 + kk * 256, dB + (src * 4 + kk) * 128);
                wg_commit();
            }
            wg_wait<0>();
            fence_regs<32>(acc);
            PROF(12);
            const int row = qb * 128 + rowhalf * 64 + wiw * 16 + g;
            uint4* o128 = (uint4*)(P.out + (size_t)row * 1024 + hg * 64 + 8 * t);
            #pragma unroll
            for (int rr = 0; rr < 2; rr++)
                #pragma unroll
                for (int a = 0; a < 2; a++) {
                    uint32_t v[4];
                    #pragma unroll
                    for (int j = 0; j < 4; j++) v[j] = pack_bf16(acc[16 * a + 4 * j + 2 * rr], acc[16 * a + 4 * j + 2 * rr + 1]);
                    quad_transpose(v, t);
                    o128[rr * 1024 + a * 4] = make_uint4(v[0], v[1], v[2], v[3]);
                }
        }
        PROF(13);
    }
}

typedef CUresult (*EncodeFn)(CUtensorMap*, CUtensorMapDataType, cuuint32_t, void*, const cuuint64_t*, const cuuint64_t*,
                             const cuuint32_t*, const cuuint32_t*, CUtensorMapInterleave, CUtensorMapSwizzle,
                             CUtensorMapL2promotion, CUtensorMapFloatOOBfill);

void make_map(EncodeFn fn, CUtensorMap* m, const void* ptr, uint64_t inner, uint64_t outer, uint32_t box_in, uint32_t box_out, CUtensorMapSwizzle swz) {
    cuuint64_t dims[2] = {inner, outer};
    cuuint64_t strides[1] = {inner * 2};
    cuuint32_t box[2] = {box_in, box_out};
    cuuint32_t es[2] = {1, 1};
    fn(m, CU_TENSOR_MAP_DATA_TYPE_BFLOAT16, 2, const_cast<void*>(ptr), dims, strides, box, es, CU_TENSOR_MAP_INTERLEAVE_NONE, swz,
       CU_TENSOR_MAP_L2_PROMOTION_L2_128B, CU_TENSOR_MAP_FLOAT_OOB_FILL_NONE);
}

}

extern "C" void kernel_launch(void* const* d_in, const int* in_sizes, int n_in, void* d_out, int out_size) {
    (void)in_sizes; (void)n_in; (void)out_size;
    static EncodeFn fn = nullptr;
    if (!fn) {
        void* p = nullptr;
        cudaDriverEntryPointQueryResult qr;
        cudaGetDriverEntryPoint("cuTensorMapEncodeTiled", &p, cudaEnableDefault, &qr);
        fn = (EncodeFn)p;
        cudaFuncSetAttribute(fused_kernel, cudaFuncAttributeMaxDynamicSharedMemorySize, SM_ALLOC);
    }
    CUtensorMap tx, twq, two, twk, twv, tu;
    {
        cuuint64_t dims[3] = {64, 2048, 8};
        cuuint64_t strides[2] = {1024, 128};
        cuuint32_t box[3] = {64, 128, 4};
        cuuint32_t es[3] = {1, 1, 1};
        fn(&tx, CU_TENSOR_MAP_DATA_TYPE_BFLOAT16, 3, d_in[0], dims, strides, box, es, CU_TENSOR_MAP_INTERLEAVE_NONE, CU_TENSOR_MAP_SWIZZLE_128B,
           CU_TENSOR_MAP_L2_PROMOTION_L2_128B, CU_TENSOR_MAP_FLOAT_OOB_FILL_NONE);
    }
    make_map(fn, &tu, d_in[5], 512, 2048, 8, 256, CU_TENSOR_MAP_SWIZZLE_NONE);
    make_map(fn, &twq, d_in[1], 512, 512, 64, 256, CU_TENSOR_MAP_SWIZZLE_128B);
    make_map(fn, &twk, d_in[2], 16, 512, 8, 256, CU_TENSOR_MAP_SWIZZLE_NONE);
    make_map(fn, &twv, d_in[3], 16, 512, 8, 256, CU_TENSOR_MAP_SWIZZLE_NONE);
    make_map(fn, &two, d_in[4], 512, 512, 64, 256, CU_TENSOR_MAP_SWIZZLE_128B);
    Params P;
    P.u = (const __nv_bfloat16*)d_in[5];
    P.lar = (const __nv_bfloat16*)d_in[6];
    P.aim = (const __nv_bfloat16*)d_in[7];
    P.cre = (const __nv_bfloat16*)d_in[8];
    P.cim = (const __nv_bfloat16*)d_in[9];
    P.logdt = (const __nv_bfloat16*)d_in[10];
    P.dskip = (const __nv_bfloat16*)d_in[11];
    P.out = (__nv_bfloat16*)d_out;
    fused_kernel<<<NCTA, NTHR, SM_ALLOC>>>(tx, twq, two, twk, twv, tu, P);
}
```

```cpp
#include <cuda_runtime.h>
#include <cuda_bf16.h>
#include <cuda_fp16.h>
#include <cuda.h>
#include <stdint.h>

namespace {

constexpr int SEQ = 2048;
constexpr int NCTA = 128, NTHR = 640;

constexpr int SM_A = 0;
constexpr int SM_WQ = 65536;
constexpr int SM_SLAB = SM_WQ + 32768;
constexpr int SM_K = 0, SM_V = 65536;
constexpr int SM_B = 132096;
constexpr int SM_WKV = SM_B + 65536;

constexpr int PADU = 1024, ULEN = PADU + 2048;
constexpr int WPAD = 16, W3LEN = WPAD + 1024;
constexpr int TABN = 2912;
constexpr int S_U = 0;
constexpr int S_W7 = S_U + 4 * ULEN * 2;
constexpr int S_W9 = S_W7 + 4 * W3LEN * 2;
constexpr int S_TAB = S_W9 + 4 * W3LEN * 2;
constexpr int S_QX = S_TAB + 4 * TABN * 2;
constexpr int S_KC = 214016 - SM_B;
constexpr int S_Y = S_KC;
constexpr int SM_BAR = SM_B + S_KC + 16384;
constexpr int SM_TOTAL = SM_BAR + 1024;
constexpr int SM_ALLOC = SM_TOTAL + 1024;
static_assert(SM_V + 65536 + 1024 <= SM_B && SM_ALLOC <= 232448 && S_QX + 8192 <= S_KC && SM_WKV + 16384 <= SM_B + S_KC, "smem map");

constexpr int TD0 = 0, TD1 = 1232, CD = 1152;
constexpr int T3B = 2464, T3S = 224, T3C = 112, C3 = 136;

constexpr int rne8(int t) {
    if (t < 256) return t;
    int sh = 0;
    while ((t >> sh) >= 256) sh++;
    int q = t >> sh, rem = t & ((1 << sh) - 1), half = 1 << (sh - 1);
    if (rem > half || (rem == half && (q & 1))) q++;
    return q << sh;
}
constexpr int kcidx(int p) {
    if (p < 256) return (p >> 3) * 24 + (p & 7);
    if (p < 512) return ((p - 256) >> 3) * 24 + 8 + (((p - 256) & 7) >> 1);
    if (p < 1024) { int q = p - 512, hi = q >> 8, rem = q & 255; return (rem >> 3) * 24 + 12 + 2 * hi + ((rem & 7) >> 2); }
    if (p < 2048) { int q = p - 1024; return ((q & 255) >> 3) * 24 + 16 + (q >> 8); }
    return 20;
}
constexpr int KC_ZERO = 23;
constexpr int tab_dense(int t) { return (t >= 0 && t <= 1028) ? kcidx(rne8(t)) : KC_ZERO; }
constexpr int tab_3(int s, int lag) { return (lag >= 64 && lag <= 127) ? kcidx(s == 0 ? 16 * (lag + 1) : 16 * lag + 8) : KC_ZERO; }
struct TabMap {
    uint16_t v[TABN];
    constexpr TabMap() : v{} {
        for (int i = 0; i < TD1; i++) { v[TD0 + i] = tab_dense(CD - i); v[TD1 + i] = tab_dense(CD + 1 - i); }
        for (int s = 0; s < 2; s++)
            for (int i = 0; i < T3C; i++) { v[T3B + s * T3S + i] = tab_3(s, C3 - i); v[T3B + s * T3S + T3C + i] = tab_3(s, C3 + 1 - i); }
    }
};
__device__ const __align__(16) TabMap g_tabmap = TabMap();

__device__ __align__(1024) uint8_t g_kimg[65536];
__device__ __align__(1024) uint8_t g_vimg[65536 + 1024];
__device__ __align__(1024) uint8_t g_oimg[16 * 131072];
__device__ unsigned long long g_flag_kv[64];
__device__ unsigned g_flag_o[128];
__device__ unsigned g_epoch;
__device__ unsigned g_done;

#define PROF(i) do {} while (0)
#define PROF2(i) do {} while (0)
#define PROFC(i) do {} while (0)
#define PROF3(i) do {} while (0)

__device__ __forceinline__ uint32_t smem_u32(const void* p) { return (uint32_t)__cvta_generic_to_shared(p); }
__device__ __forceinline__ void mbar_init(uint32_t bar, uint32_t cnt) { asm volatile("mbarrier.init.shared::cta.b64 [%0], %1;" :: "r"(bar), "r"(cnt) : "memory"); }
__device__ __forceinline__ void mbar_expect_tx(uint32_t bar, uint32_t bytes) {
    asm volatile("mbarrier.arrive.expect_tx.shared::cta.b64 _, [%0], %1;" :: "r"(bar), "r"(bytes) : "memory"); }
__device__ __forceinline__ void mbar_wait(uint32_t bar, uint32_t parity) {
    uint32_t ok = 0;
    for (int it = 0; it < (1 << 22) && !ok; it++) {
        asm volatile("{ .reg .pred p; mbarrier.try_wait.parity.shared::cta.b64 p, [%1], %2; selp.u32 %0, 1, 0, p; }"
                     : "=r"(ok) : "r"(bar), "r"(parity) : "memory");
    }
}
__device__ __forceinline__ void tma_2d(uint32_t dst, const CUtensorMap* map, int c0, int c1, uint32_t bar) {
    asm volatile("cp.async.bulk.tensor.2d.shared::cluster.global.mbarrier::complete_tx::bytes [%0], [%1, {%3, %4}], [%2];"
                 :: "r"(dst), "l"((uint64_t)map), "r"(bar), "r"(c0), "r"(c1) : "memory");
}
__device__ __forceinline__ void tma_2d_mc(uint32_t dst, const CUtensorMap* map, int c0, int c1, uint32_t bar) {
    asm volatile("cp.async.bulk.tensor.2d.shared::cluster.global.mbarrier::complete_tx::bytes.multicast::cluster [%0], [%1, {%3, %4}], [%2], %5;"
                 :: "r"(dst), "l"((uint64_t)map), "r"(bar), "r"(c0), "r"(c1), "h"((uint16_t)3) : "memory");
}
__device__ __forceinline__ void bulk_g2s_mc(uint32_t dst, const void* src, uint32_t bytes, uint32_t bar) {
    asm volatile("cp.async.bulk.shared::cluster.global.mbarrier::complete_tx::bytes.multicast::cluster [%0], [%1], %2, [%3], %4;"
                 :: "r"(dst), "l"((uint64_t)src), "r"(bytes), "r"(bar), "h"((uint16_t)3) : "memory");
}
__device__ __forceinline__ void pair_arrive(uint32_t bar, uint32_t peer) {
    uint32_t ra;
    asm volatile("mapa.shared::cluster.u32 %0, %1, %2;" : "=r"(ra) : "r"(bar), "r"(peer));
    asm volatile("mbarrier.arrive.shared::cluster.b64 _, [%0];" :: "r"(ra) : "memory");
    asm volatile("mbarrier.arrive.shared::cta.b64 _, [%0];" :: "r"(bar) : "memory");
}
__device__ __forceinline__ void pair_sync(uint32_t bar, uint32_t peer) { pair_arrive(bar, peer); mbar_wait(bar, 0); }
__device__ __forceinline__ void fence_async_all() { asm volatile("fence.proxy.async.global;" ::: "memory"); }
__device__ __forceinline__ void fence_async_smem() { asm volatile("fence.proxy.async.shared::cta;" ::: "memory"); }
__device__ __forceinline__ unsigned ld_acquire(const unsigned* p) {
    unsigned v; asm volatile("ld.acquire.gpu.global.u32 %0, [%1];" : "=r"(v) : "l"(p) : "memory"); return v; }
__device__ __forceinline__ void st_release(unsigned* p, unsigned v) { asm volatile("st.release.gpu.global.u32 [%0], %1;" :: "l"(p), "r"(v) : "memory"); }
__device__ __forceinline__ void wait_flag(const unsigned* p, unsigned epoch) {
    for (int it = 0; it < (1 << 22); it++) { if (ld_acquire(p) == epoch) break; }
}
__device__ __forceinline__ unsigned long long ld_acquire64(const unsigned long long* p) {
    unsigned long long v; asm volatile("ld.acquire.gpu.global.u64 %0, [%1];" : "=l"(v) : "l"(p) : "memory"); return v; }
__device__ __forceinline__ void st_release64(unsigned long long* p, unsigned long long v) { asm volatile("st.release.gpu.global.u64 [%0], %1;" :: "l"(p), "l"(v) : "memory"); }
__device__ __forceinline__ float wait_flag64(const unsigned long long* p, unsigned epoch) {
    unsigned long long v = 0;
    for (int it = 0; it < (1 << 22); it++) { v = ld_acquire64(p); if ((unsigned)(v >> 32) == epoch) break; }
    return __uint_as_float((unsigned)v);
}
__device__ __forceinline__ void tma_3d_mc(uint32_t dst, const CUtensorMap* map, int c0, int c1, int c2, uint32_t bar) {
    asm volatile("cp.async.bulk.tensor.3d.shared::cluster.global.mbarrier::complete_tx::bytes.multicast::cluster [%0], [%1, {%3, %4, %5}], [%2], %6;"
                 :: "r"(dst), "l"((uint64_t)map), "r"(bar), "r"(c0), "r"(c1), "r"(c2), "h"((uint16_t)3) : "memory");
}
__device__ __forceinline__ void bar_sync(int id, int n) { asm volatile("bar.sync %0, %1;" :: "r"(id), "r"(n) : "memory"); }
__device__ __forceinline__ void bar_arrive(int id, int n) { asm volatile("bar.arrive %0, %1;" :: "r"(id), "r"(n) : "memory"); }
__device__ __forceinline__ void mbar_arrive(uint32_t bar) { asm volatile("mbarrier.arrive.shared::cta.b64 _, [%0];" :: "r"(bar) : "memory"); }

__device__ __forceinline__ uint64_t make_desc(uint32_t saddr, uint32_t lbo, uint32_t sbo, uint32_t swz) {
    uint64_t d = 0;
    d |= (uint64_t)((saddr & 0x3FFFF) >> 4);
    d |= (uint64_t)((lbo >> 4) & 0x3FFF) << 16;
    d |= (uint64_t)((sbo >> 4) & 0x3FFF) << 32;
    d |= (uint64_t)swz << 62;
    return d;
}
__device__ __forceinline__ void wg_fence() { asm volatile("wgmma.fence.sync.aligned;" ::: "memory"); }
__device__ __forceinline__ void wg_commit() { asm volatile("wgmma.commit_group.sync.aligned;" ::: "memory"); }
template<int N> __device__ __forceinline__ void wg_wait() { asm volatile("wgmma.wait_group.sync.aligned %0;" :: "n"(N) : "memory"); }
#define A4(d, o) "+f"(d[o + 0]), "+f"(d[o + 1]), "+f"(d[o + 2]), "+f"(d[o + 3])
#define A16(d, o) A4(d, o), A4(d, o + 4), A4(d, o + 8), A4(d, o + 12)

__device__ __forceinline__ void wg_pv(float* d, const uint32_t* a, uint32_t lo, uint32_t hi) {
    asm volatile("{ .reg .b64 dd; mov.b64 dd, {%16, %17};\n"
                 "wgmma.mma_async.sync.aligned.m64n24k16.f32.bf16.bf16 {%0,%1,%2,%3,%4,%5,%6,%7,%8,%9,%10,%11}, {%12,%13,%14,%15}, dd, 1, 1, 1, 1; }"
                 : A4(d, 0), A4(d, 4), A4(d, 8) : "r"(a[0]), "r"(a[1]), "r"(a[2]), "r"(a[3]), "r"(lo), "r"(hi));
}
__device__ __forceinline__ void wg_qk(float* d, const uint32_t* a, uint32_t lo) {
    asm volatile("{ .reg .b64 dd; mov.b64 dd, {%36, %37};\n"
                 "wgmma.mma_async.sync.aligned.m64n64k16.f32.bf16.bf16 {%0,%1,%2,%3,%4,%5,%6,%7,%8,%9,%10,%11,%12,%13,%14,%15,%16,%17,%18,%19,%20,%21,%22,%23,%24,%25,%26,%27,%28,%29,%30,%31}, {%32,%33,%34,%35}, dd, 0, 1, 1, 0; }"
                 : A16(d, 0), A16(d, 16) : "r"(a[0]), "r"(a[1]), "r"(a[2]), "r"(a[3]), "r"(lo), "r"(16));
}
__device__ __forceinline__ void wg_rs32(float* d, const uint32_t* a, uint32_t lo) {
    asm volatile("{ .reg .b64 dd; mov.b64 dd, {%20, %21};\n"
                 "wgmma.mma_async.sync.aligned.m64n32k16.f32.bf16.bf16 {%0,%1,%2,%3,%4,%5,%6,%7,%8,%9,%10,%11,%12,%13,%14,%15}, {%16,%17,%18,%19}, dd, 1, 1, 1, 0; }"
                 : A16(d, 0) : "r"(a[0]), "r"(a[1]), "r"(a[2]), "r"(a[3]), "r"(lo), "r"(0x40000040));
}
__device__ __forceinline__ void wg_rs24(float* d, const uint32_t* a, uint32_t lo) {
    asm volatile("{ .reg .b64 dd; mov.b64 dd, {%16, %17};\n"
                 "wgmma.mma_async.sync.aligned.m64n24k16.f32.bf16.bf16 {%0,%1,%2,%3,%4,%5,%6,%7,%8,%9,%10,%11}, {%12,%13,%14,%15}, dd, 1, 1, 1, 0; }"
                 : A4(d, 0), A4(d, 4), A4(d, 8) : "r"(a[0]), "r"(a[1]), "r"(a[2]), "r"(a[3]), "r"(lo), "r"(0x40000040));
}
__device__ __forceinline__ void wg_ss64(float* d, uint64_t da, uint64_t db) {
    asm volatile("wgmma.mma_async.sync.aligned.m64n64k16.f32.bf16.bf16 {%0,%1,%2,%3,%4,%5,%6,%7,%8,%9,%10,%11,%12,%13,%14,%15,%16,%17,%18,%19,%20,%21,%22,%23,%24,%25,%26,%27,%28,%29,%30,%31}, %32, %33, 1, 1, 1, 0, 1;"
                 : A16(d, 0), A16(d, 16) : "l"(da), "l"(db));
}
__device__ __forceinline__ void wg_ss16(float* d, uint64_t da, uint64_t db) {
    asm volatile("wgmma.mma_async.sync.aligned.m64n16k16.f32.bf16.bf16 {%0,%1,%2,%3,%4,%5,%6,%7}, %8, %9, 1, 1, 1, 0, 1;"
                 : A4(d, 0), A4(d, 4) : "l"(da), "l"(db));
}
template<int N> __device__ __forceinline__ void fence_regs(float* r) {
    #pragma unroll
    for (int i = 0; i < N; i++) asm volatile("" : "+f"(r[i]) :: "memory");
}
__device__ __forceinline__ void mma_f16(float* d, const uint32_t* a, uint32_t b0, uint32_t b1) {
    asm volatile("mma.sync.aligned.m16n8k16.row.col.f32.f16.f16.f32 {%0,%1,%2,%3}, {%4,%5,%6,%7}, {%8,%9}, {%0,%1,%2,%3};"
                 : "+f"(d[0]), "+f"(d[1]), "+f"(d[2]), "+f"(d[3]) : "r"(a[0]), "r"(a[1]), "r"(a[2]), "r"(a[3]), "r"(b0), "r"(b1));
}
__device__ __forceinline__ uint32_t lds32(uint32_t addr) { uint32_t v; asm volatile("ld.shared.u32 %0, [%1];" : "=r"(v) : "r"(addr) : "memory"); return v; }
__device__ __forceinline__ void mma_bf16_p(float* d, uint32_t a0, uint32_t a1, uint32_t a2, uint32_t a3, uint32_t b0, uint32_t b1) {
    asm("mma.sync.aligned.m16n8k16.row.col.f32.bf16.bf16.f32 {%0,%1,%2,%3}, {%4,%5,%6,%7}, {%8,%9}, {%0,%1,%2,%3};"
        : "+f"(d[0]), "+f"(d[1]), "+f"(d[2]), "+f"(d[3]) : "r"(a0), "r"(a1), "r"(a2), "r"(a3), "r"(b0), "r"(b1));
}
__device__ __forceinline__ void ldsm4t_p(uint32_t* r, uint32_t addr) {
    asm("ldmatrix.sync.aligned.m8n8.x4.trans.shared.b16 {%0,%1,%2,%3}, [%4];" : "=r"(r[0]), "=r"(r[1]), "=r"(r[2]), "=r"(r[3]) : "r"(addr));
}
__device__ __forceinline__ uint32_t lds32_p(uint32_t addr) { uint32_t v; asm("ld.shared.u32 %0, [%1];" : "=r"(v) : "r"(addr)); return v; }
__device__ __forceinline__ uint32_t swz(uint32_t a) { return a ^ ((a >> 3) & 16u); }
__device__ __forceinline__ uint32_t swz128(uint32_t a) { return a ^ ((a >> 3) & 0x70u); }
__device__ __forceinline__ void sts32(uint32_t addr, uint32_t v) { asm volatile("st.shared.u32 [%0], %1;" :: "r"(addr), "r"(v) : "memory"); }
__device__ __forceinline__ void sts128(uint32_t addr, uint4 v) { asm volatile("st.shared.v4.u32 [%0], {%1,%2,%3,%4};" :: "r"(addr), "r"(v.x), "r"(v.y), "r"(v.z), "r"(v.w) : "memory"); }
__device__ __forceinline__ uint4 lds128(uint32_t addr) { uint4 v; asm volatile("ld.shared.v4.u32 {%0,%1,%2,%3}, [%4];" : "=r"(v.x), "=r"(v.y), "=r"(v.z), "=r"(v.w) : "r"(addr) : "memory"); return v; }
__device__ __forceinline__ void quad_transpose(uint32_t* v, int t) {
    #pragma unroll
    for (int p = 0; p < 2; p++) {
        const uint32_t x = __shfl_xor_sync(0xffffffffu, (t & 1) ? v[2 * p] : v[2 * p + 1], 1);
        if (t & 1) v[2 * p] = x; else v[2 * p + 1] = x;
    }
    #pragma unroll
    for (int p = 0; p < 2; p++) {
        const uint32_t x = __shfl_xor_sync(0xffffffffu, (t & 2) ? v[p] : v[p + 2], 2);
        if (t & 2) v[p] = x; else v[p + 2] = x;
    }
}
__device__ __forceinline__ float ex2f(float x) { float r; asm("ex2.approx.ftz.f32 %0, %1;" : "=f"(r) : "f"(x)); return r; }
__device__ __forceinline__ uint32_t pack_bf16(float lo, float hi) { uint32_t r; asm("cvt.rn.bf16x2.f32 %0, %1, %2;" : "=r"(r) : "f"(hi), "f"(lo)); return r; }
__device__ __forceinline__ uint32_t pack_f16(float lo, float hi) { uint32_t r; asm("cvt.rn.f16x2.f32 %0, %1, %2;" : "=r"(r) : "f"(hi), "f"(lo)); return r; }
__device__ __forceinline__ float bf_lo(uint32_t v) { return __uint_as_float(v << 16); }
__device__ __forceinline__ float bf_hi(uint32_t v) { return __uint_as_float(v & 0xFFFF0000u); }
__device__ __forceinline__ float bf_round(float x) { return __bfloat162float(__float2bfloat16_rn(x)); }

__device__ __forceinline__ uint32_t exp_mufu(float x0, float x1) { return pack_bf16(ex2f(x0), ex2f(x1)); }
#define SW_MAGIC (256.0f + 127.0f - 0.598938f)
__device__ __forceinline__ uint32_t exp_sw(float x0, float x1, uint32_t cA, uint32_t cB) {
    float t0 = x0 + SW_MAGIC, t1 = x1 + SW_MAGIC;
    uint32_t L, mh, ec, r;
    asm("prmt.b32 %0, %1, %2, 0x6521;" : "=r"(L) : "r"(__float_as_uint(t0)), "r"(__float_as_uint(t1)));
    asm("lop3.b32 %0, %1, 0x007F007F, %2, 0xEA;" : "=r"(mh) : "r"(L), "r"(cA));
    asm("lop3.b32 %0, %1, 0x7F807F80, %2, 0xEA;" : "=r"(ec) : "r"(L), "r"(cB));
    asm("fma.rn.bf16x2 %0, %1, %2, %3;" : "=r"(r) : "r"(L), "r"(mh), "r"(ec));
    return r;
}
#define MUFU_MASK_V 0x0555
#define AU_V 8
constexpr uint32_t MUFU_MASK = MUFU_MASK_V;
constexpr int AU = AU_V;

struct cf { float x, y; };
__device__ __forceinline__ cf cmul(cf a, cf b) { cf r; r.x = a.x * b.x - a.y * b.y; r.y = a.x * b.y + a.y * b.x; return r; }
__device__ __forceinline__ cf cexp_p(float a2, float b, float p) {
    float e = ex2f(a2 * p);
    float ph = b * p;
    ph -= (ph + 12582912.0f) - 12582912.0f;
    float ang = ph * 6.283185307f;
    cf r; r.x = e * __cosf(ang); r.y = e * __sinf(ang);
    return r;
}
__device__ __forceinline__ uint32_t h2_cmul(uint32_t w, uint32_t wsw, uint32_t e) {
    __half2 hw = *(__half2*)&w, hs = *(__half2*)&wsw, he = *(__half2*)&e;
    __half2 r = __hfma2(hs, __high2half2(he), __hmul2(hw, __low2half2(he)));
    return *(uint32_t*)&r;
}

struct Params {
    const __nv_bfloat16 *u, *lar, *aim, *cre, *cim, *logdt, *dskip;
    __nv_bfloat16* out;
};

constexpr int B_O = 0, B_KV = 8, B_WO = 12, B_WQ2 = 13, B_ST = 14, B_H = 15, B_X = 17, B_U = 19, B_WQ = 20;

__device__ __forceinline__ void helper_role(const Params& P, uint8_t* sp, uint32_t sb, unsigned epoch) {
    const uint32_t sBa = sb + SM_B;
    const int tid = threadIdx.x - 544;
    const int d0 = blockIdx.x * 4;
    uint8_t* sB = sp + SM_B;
    const uint2 dsk = __ldg((const uint2*)(P.dskip + d0));
    asm volatile("barrier.cluster.wait.aligned;" ::: "memory");
    {
        const int hg = blockIdx.x & 7;
        if (hg < 4 && tid < 32) {
            bar_sync(3, 160);
            if (tid == 0) {
                const float* s_misc = (const float*)(sp + SM_BAR + 256);
                const float st = fmaxf(fmaxf(s_misc[20], s_misc[21]), fmaxf(s_misc[22], s_misc[23]));
                st_release64(&g_flag_kv[((blockIdx.x >> 3) * 2 + (hg & 1)) * 2 + (hg >> 1)], ((unsigned long long)epoch << 32) | __float_as_uint(st));
            }
            __syncwarp();
        }
    }
    PROF2(2);
    bar_sync(10, 608);
    {
        uint32_t dd[4] = {__byte_perm(dsk.x, 0, 0x1010), __byte_perm(dsk.x, 0, 0x3232), __byte_perm(dsk.y, 0, 0x1010), __byte_perm(dsk.y, 0, 0x3232)};
        #pragma unroll 2
        for (int pi = tid; pi < 1024; pi += 96) {
            const int l = 2 * pi;
            uint32_t r[4];
            #pragma unroll
            for (int cc = 0; cc < 4; cc++) {
                const uint32_t y2 = *(const uint32_t*)(sB + S_Y + cc * 4096 + l * 2);
                const uint32_t u2 = lds32(swz128(sBa + S_U + cc * ULEN * 2 + (PADU + l) * 2));
                __nv_bfloat162 pr = __hmul2(*(const __nv_bfloat162*)&u2, *(const __nv_bfloat162*)&dd[cc]);
                __nv_bfloat162 sm = __hadd2(*(const __nv_bfloat162*)&y2, pr);
                r[cc] = *(uint32_t*)&sm;
            }
            *(uint2*)(P.out + (size_t)l * 1024 + 512 + d0) = make_uint2(__byte_perm(r[0], r[1], 0x5410), __byte_perm(r[2], r[3], 0x5410));
            *(uint2*)(P.out + (size_t)(l + 1) * 1024 + 512 + d0) = make_uint2(__byte_perm(r[0], r[1], 0x7632), __byte_perm(r[2], r[3], 0x7632));
        }
    }
    bar_arrive(11, 128);
    PROF2(4);
}

__global__ void __cluster_dims__(2, 1, 1) __launch_bounds__(NTHR, 1)
fused_kernel(const __grid_constant__ CUtensorMap tm_x, const __grid_constant__ CUtensorMap tm_wq,
             const __grid_constant__ CUtensorMap tm_wo, const __grid_constant__ CUtensorMap tm_wk,
             const __grid_constant__ CUtensorMap tm_wv, const __grid_constant__ CUtensorMap tm_u, const Params P) {
    extern __shared__ uint8_t smem_raw[];
    const uint32_t sb = (smem_u32(smem_raw) + 1023u) & ~1023u;
    uint8_t* sp = smem_raw + (sb - smem_u32(smem_raw));

    const int tid = threadIdx.x, warp = tid >> 5, lane = tid & 31, wg = tid >> 7, wiw = warp & 3;
    const int g = lane >> 2, t = lane & 3;
    const int qb = blockIdx.x >> 3, hg = blockIdx.x & 7;
    const uint32_t rank = blockIdx.x & 1;
    const int rowhalf = wg & 1, nh = wg >> 1;
    const bool kv_cta = hg < 4;
    const int kv_sel = hg >> 1;
    const bool kv_wg = kv_cta && (wg == 2 + (hg & 1));

    const uint32_t bars = sb + SM_BAR;
    float* s_misc = (float*)(sp + SM_BAR + 256);
    const CUtensorMap* tm_kv = kv_sel ? &tm_wv : &tm_wk;

    PROF(0);
    unsigned short p_lar = 0, p_aim = 0, p_cre = 0, p_cim = 0, p_ldt = 0;
    if (wg < 4) {
        const int n = (blockIdx.x * 4 + wg) * 128 + (tid & 127);
        p_lar = __ldg((const unsigned short*)P.lar + n);
        p_aim = __ldg((const unsigned short*)P.aim + n);
        p_cre = __ldg((const unsigned short*)P.cre + n);
        p_cim = __ldg((const unsigned short*)P.cim + n);
        p_ldt = __ldg((const unsigned short*)P.logdt + blockIdx.x * 4 + wg);
    } else if (warp == 16) {
        PROF3(5);
        if (lane == 0) {
            asm volatile("prefetch.tensormap [%0];" :: "l"((uint64_t)&tm_x) : "memory");
            asm volatile("prefetch.tensormap [%0];" :: "l"((uint64_t)tm_kv) : "memory");
            asm volatile("prefetch.tensormap [%0];" :: "l"((uint64_t)&tm_wq) : "memory");
            asm volatile("prefetch.tensormap [%0];" :: "l"((uint64_t)&tm_u) : "memory");
            mbar_init(bars + 8 * B_X, 1);
            mbar_init(bars + 8 * B_X + 8, 1);
            mbar_init(bars + 8 * B_U, 1);
            asm volatile("fence.mbarrier_init.release.cluster;" ::: "memory");
            mbar_expect_tx(bars + 8 * B_X, 65536u + (kv_cta ? 8192u : 0u));
            mbar_expect_tx(bars + 8 * B_X + 8, 65536u + (kv_cta ? 8192u : 0u));
            mbar_expect_tx(bars + 8 * B_U, 32768u);
        }
        __syncwarp();
        PROF3(6);
    }
    asm volatile("barrier.cluster.arrive.relaxed.aligned;" ::: "memory");
    const unsigned epoch = *(volatile unsigned*)&g_epoch + 1u;
    if (warp > 16) {
        if (lane == 0) {
            for (int i = warp - 17; i < B_X; i += 3) {
                mbar_init(bars + 8 * i, i >= B_H ? 2 : 1);
                if (i <= B_WQ2) mbar_expect_tx(bars + 8 * i, i < B_KV + 2 ? 16384u : i == B_KV + 2 ? 32768u : i <= B_WO ? 65536u : 32768u);
            }
            asm volatile("fence.mbarrier_init.release.cluster;" ::: "memory");
            fence_async_smem();
        } else if (warp == 19) {
            #pragma unroll
            for (int i = 0; i < 2; i++) if (lane - 1 + 31 * i < 46) asm volatile("prefetch.global.L2 [%0];" :: "l"((const char*)g_tabmap.v + (lane - 1 + 31 * i) * 128));
        }
        __syncwarp();
    }
    asm volatile("barrier.cluster.wait.aligned;" ::: "memory");
    PROF(5);
    if (warp == 16 && lane == 0) {
        tma_3d_mc(sb + (rank ? SM_A : SM_B), &tm_x, 0, qb * 128, rank * 4, bars + 8 * (B_X + rank));
        if (kv_cta) {
            #pragma unroll
            for (int i = 0; i < 4; i++) tma_2d(sb + SM_WKV + i * 4096, tm_kv, (i >> 1) * 8, (i & 1) * 256, bars + 8 * (B_X + (i & 1)));
        }
        mbar_init(bars + 8 * B_WQ, 1);
        asm volatile("fence.mbarrier_init.release.cluster;" ::: "memory");
        fence_async_smem();
        mbar_expect_tx(bars + 8 * B_WQ, 32768u);
        tma_2d(sb + SM_WQ, &tm_wq, hg * 64, 0, bars + 8 * B_WQ);
        #pragma unroll
        for (int i = 0; i < 4; i++) tma_2d_mc(sb + SM_SLAB + (rank * 4 + i) * 4096, &tm_u, (blockIdx.x >> 1) * 8, (rank * 4 + i) * 256, bars + 8 * B_U);
    }
    __syncwarp();
    asm volatile("barrier.cluster.arrive.relaxed.aligned;" ::: "memory");

    if (warp == 16) {
        if (lane == 0) asm volatile("prefetch.tensormap [%0];" :: "l"((uint64_t)&tm_wo) : "memory");
        asm volatile("barrier.cluster.wait.aligned;" ::: "memory");
        PROF3(10);
        bar_sync(13, 544);
        if (lane == 0) { fence_async_smem(); tma_2d(sb + SM_SLAB, &tm_wq, hg * 64, 256, bars + 8 * B_WQ2); }
        bar_sync(14, 288);
        if (lane == 0) pair_sync(bars + 8 * B_H, rank ^ 1);
        __syncwarp();
        PROF3(11);
        *(uint4*)(sp + SM_V + 32768 + lane * 32) = make_uint4(0x3F803F80u, 0x3F803F80u, 0x3F803F80u, 0x3F803F80u);
        *(uint4*)(sp + SM_V + 32768 + lane * 32 + 16) = make_uint4(0x3F803F80u, 0x3F803F80u, 0x3F803F80u, 0x3F803F80u);
        fence_async_smem();
        float km = wait_flag64(&g_flag_kv[2 * lane], epoch);
        float vm = wait_flag64(&g_flag_kv[2 * lane + 1], epoch);
        __syncwarp();
        PROF3(12);
        if (lane == 0) {
            fence_async_all();
            #pragma unroll
            for (int i = 0; i < 4; i++) {
                const uint32_t k0 = i == 0 ? 0 : 128u << i, nk = i == 0 ? 256 : 128u << i;
                const uint32_t bar = bars + 8 * (B_KV + i);
                if (rank == 0) bulk_g2s_mc(sb + SM_K + k0 * 32, g_kimg + k0 * 32, nk * 32, bar);
                else {
                    bulk_g2s_mc(sb + SM_V + k0 * 16, g_vimg + k0 * 16, nk * 16, bar);
                    bulk_g2s_mc(sb + SM_V + 66560 - (k0 + nk) * 16, g_vimg + 66560 - (k0 + nk) * 16, nk * 16, bar);
                }
            }
        }
        #pragma unroll
        for (int o = 16; o; o >>= 1) { km = fmaxf(km, __shfl_xor_sync(0xffffffffu, km, o)); vm = fmaxf(vm, __shfl_xor_sync(0xffffffffu, vm, o)); }
        if (lane == 0) { s_misc[16] = km; s_misc[17] = vm; mbar_arrive(bars + 8 * B_ST); }
        PROF3(13);
        bar_sync(11, 128);
        if (lane < 2) { fence_async_smem(); tma_2d(sb + SM_B + lane * 32768, &tm_wo, hg * 64, lane * 256, bars + 8 * B_WO); }
        bar_sync(12, 544);
        if (lane == 0) pair_arrive(bars + 8 * (B_H + 1), rank ^ 1);
        if (lane == 0) {
            st_release(&g_flag_o[blockIdx.x], epoch);
            mbar_wait(bars + 8 * (B_H + 1), 0);
        }
        __syncwarp();
        PROF3(14);
        if (lane < 4) {
            const int src = (2 * lane + (hg & 6) + rank) & 7;
            wait_flag(&g_flag_o[qb * 8 + src], epoch);
            fence_async_all();
            bulk_g2s_mc(sb + SM_A + src * 16384, g_oimg + qb * 131072 + src * 16384, 16384, bars + 8 * (B_O + src));
        }
        __syncwarp();
        PROF3(15);
        if (lane == 0) {
            const unsigned prev = atomicAdd(&g_done, 1u);
            if (prev == NCTA - 1) {
                g_done = 0;
                __threadfence();
                *(volatile unsigned*)&g_epoch = epoch;
            }
        }
    } else if (wg == 4) {
        helper_role(P, sp, sb, epoch);
    } else {
        uint8_t* sB = sp + SM_B;
        const uint32_t sBa = sb + SM_B;
        {
            const int c = wg;
            const float dt = bf_round(expf(bf_lo(p_ldt)));
            const float are = -bf_round(expf(bf_lo(p_lar))) * dt;
            const float aim = bf_lo(p_aim) * dt;
            float cr = 2.0f * (bf_lo(p_cre) * dt);
            float ci = 2.0f * (bf_lo(p_cim) * dt);
            const float a2 = are * 1.4426950408889634f, bb = aim * 0.15915494309189535f;
            float m = fmaxf(fabsf(cr), fabsf(ci));
            #pragma unroll
            for (int o = 16; o; o >>= 1) m = fmaxf(m, __shfl_xor_sync(0xffffffffu, m, o));
            int ebits = (__float_as_uint(m) >> 23) & 0xFF;
            ebits = min(max(ebits, 2), 250);
            const float scale = __uint_as_float((uint32_t)(ebits + 1) << 23);
            const float iscale = __uint_as_float((uint32_t)(253 - ebits) << 23);
            cf cc; cc.x = cr * iscale; cc.y = ci * iscale;

            const uint32_t stg = sBa + S_KC + warp * 1024;
            uint4* stp = (uint4*)(sB + S_KC + warp * 1024 + lane * 32);
            const uint32_t fa = stg + t * 32 + g * 4;

            uint32_t af[4][2][4];
            cf E256;
            {
                const cf E8 = cexp_p(a2, bb, 8.0f);
                uint32_t w[8];
                cf cur; cur.x = 1.0f; cur.y = 0.0f;
                w[0] = pack_f16(1.0f, 0.0f);
                cur = E8; w[1] = pack_f16(cur.x, cur.y);
                #pragma unroll
                for (int i = 2; i < 8; i++) { cur = cmul(cur, E8); w[i] = pack_f16(cur.x, cur.y); }
                stp[0] = make_uint4(w[0], w[1], w[2], w[3]);
                stp[1] = make_uint4(w[4], w[5], w[6], w[7]);
                const cf E64 = cexp_p(a2, bb, 64.0f);
                const cf E128 = cmul(E64, E64), E192 = cmul(E128, E64);
                E256 = cexp_p(a2, bb, 256.0f);
                const uint32_t e1 = pack_f16(E64.x, E64.y), e2 = pack_f16(E128.x, E128.y), e3 = pack_f16(E192.x, E192.y);
                __syncwarp();
                #pragma unroll
                for (int s = 0; s < 4; s++) {
                    #pragma unroll
                    for (int hh = 0; hh < 2; hh++) {
                        const uint32_t w0 = lds32(fa + s * 256 + hh * 128);
                        const uint32_t wsw = __byte_perm(w0, 0, 0x1032) ^ 0x00008000u;
                        const int src = 8 * s + t + 4 * hh;
                        const uint32_t f1 = __shfl_sync(0xffffffffu, e1, src), f2 = __shfl_sync(0xffffffffu, e2, src), f3 = __shfl_sync(0xffffffffu, e3, src);
                        af[s][0][2 * hh] = w0;
                        af[s][0][2 * hh + 1] = h2_cmul(w0, wsw, f1);
                        af[s][1][2 * hh] = h2_cmul(w0, wsw, f2);
                        af[s][1][2 * hh + 1] = h2_cmul(w0, wsw, f3);
                    }
                }
                __syncwarp();
            }
            float acc[2][3][4];
            #pragma unroll
            for (int i = 0; i < 24; i++) (&acc[0][0][0])[i] = 0.0f;
            const cf E1 = cexp_p(a2, bb, 1.0f);
            const cf E2 = cmul(E1, E1), E4 = cmul(E2, E2);
            cf X512;
            #pragma unroll
            for (int nt = 0; nt < 3; nt++) {
                uint32_t xv[8];
                if (nt == 0) {
                    cf cur = cc;
                    xv[0] = pack_f16(cur.x, -cur.y);
                    #pragma unroll
                    for (int i = 1; i < 8; i++) { cur = cmul(cur, E1); xv[i] = pack_f16(cur.x, -cur.y); }
                } else if (nt == 1) {
                    cf cur = cmul(cc, E256);
                    X512 = cmul(cur, E256);
                    xv[0] = pack_f16(cur.x, -cur.y);
                    #pragma unroll
                    for (int i = 1; i < 4; i++) { cur = cmul(cur, E2); xv[i] = pack_f16(cur.x, -cur.y); }
                    cur = cmul(X512, E4);
                    xv[4] = pack_f16(X512.x, -X512.y); xv[5] = pack_f16(cur.x, -cur.y);
                    X512 = cmul(X512, E256);
                    cur = cmul(X512, E4);
                    xv[6] = pack_f16(X512.x, -X512.y); xv[7] = pack_f16(cur.x, -cur.y);
                } else {
                    cf cur = X512;
                    #pragma unroll
                    for (int i = 0; i < 5; i++) { cur = cmul(cur, E256); xv[i] = pack_f16(cur.x, -cur.y); }
                    xv[5] = 0; xv[6] = 0; xv[7] = 0;
                }
                stp[0] = make_uint4(xv[0], xv[1], xv[2], xv[3]);
                stp[1] = make_uint4(xv[4], xv[5], xv[6], xv[7]);
                __syncwarp();
                #pragma unroll
                for (int s = 0; s < 4; s++) {
                    const uint32_t b0 = lds32(fa + s * 256), b1 = lds32(fa + s * 256 + 128);
                    mma_f16(acc[0][nt], af[s][0], b0, b1);
                    mma_f16(acc[1][nt], af[s][1], b0, b1);
                }
                __syncwarp();
            }
            float* kc = (float*)(sB + S_KC + c * 4096);
            bar_sync(4 + c, 128);
            #pragma unroll 1
            for (int step = 0; step < 4; step++) {
                if ((warp & 3) == step) {
                    #pragma unroll
                    for (int mt = 0; mt < 2; mt++)
                        #pragma unroll
                        for (int nt = 0; nt < 3; nt++)
                            #pragma unroll
                            for (int hh = 0; hh < 2; hh++) {
                                float2* p = (float2*)(kc + (mt * 16 + hh * 8 + g) * 24 + nt * 8 + 2 * t);
                                float2 v = make_float2(acc[mt][nt][2 * hh] * scale, acc[mt][nt][2 * hh + 1] * scale);
                                if (step) { float2 o = *p; v.x += o.x; v.y += o.y; }
                                *p = v;
                            }
                }
                if (step < 3) bar_sync(4 + c, 128);
            }
        }

        asm volatile("barrier.cluster.wait.aligned;" ::: "memory");
        PROF(4);
        uint32_t q[2][4];
        {
            const uint64_t dA0 = make_desc(sb + SM_B + rowhalf * 8192, 16, 1024, 1);
            const uint64_t dA1 = make_desc(sb + SM_A + rowhalf * 8192, 16, 1024, 1) - 4096;
            uint4* qx = (uint4*)(sp + SM_B + S_QX) + (tid & 255) * 2;
            auto stage_u = [&]() {
                #pragma unroll
                for (int i = 0; i < 1; i++) {
                    const int z = tid + 512 * i;
                    if (z < 4 * 80) sts128(sBa + S_U + (z / 80) * ULEN * 2 + (PADU - 640) * 2 + (z % 80) * 16, make_uint4(0, 0, 0, 0));
                }
                mbar_wait(bars + 8 * B_U, 0);
                #pragma unroll
                for (int i = 0; i < 2; i++) {
                    const int l = 2 * (tid + 512 * i);
                    const uint2 r0 = *(const uint2*)(sp + SM_SLAB + l * 16 + rank * 8), r1 = *(const uint2*)(sp + SM_SLAB + l * 16 + 16 + rank * 8);
                    const uint32_t dst = swz128(sBa + S_U + (PADU + l) * 2);
                    sts32(dst, __byte_perm(r0.x, r1.x, 0x5410));
                    sts32(dst + ULEN * 2, __byte_perm(r0.x, r1.x, 0x7632));
                    sts32(dst + ULEN * 4, __byte_perm(r0.y, r1.y, 0x5410));
                    sts32(dst + ULEN * 6, __byte_perm(r0.y, r1.y, 0x7632));
                }
                fence_async_smem();
                bar_arrive(13, 544);
            };
            if (wg < 2) {
                float acc[32];
                #pragma unroll
                for (int i = 0; i < 32; i++) acc[i] = 0.0f;
                fence_regs<32>(acc);
                const uint64_t dB = make_desc(sb + SM_WQ, 16, 1024, 1);
                mbar_wait(bars + 8 * B_WQ, 0);
                mbar_wait(bars + 8 * B_X, 0);
                PROF(2);
                #pragma unroll 1
                for (int ch = 0; ch < 4; ch++) {
                    wg_fence();
                    #pragma unroll
                    for (int ks = 0; ks < 4; ks++) wg_ss64(acc, dA0 + ch * 1024 + ks * 2, dB + (ch * 4 + ks) * 128);
                    wg_commit();
                }
                wg_wait<0>();
                fence_regs<32>(acc);
                bar_sync(1, 512);
                PROF(15);
                stage_u();
                bar_arrive(2, 512);
                PROF(1);
                mbar_wait(bars + 8 * B_WQ2, 0);
                mbar_wait(bars + 8 * (B_X + 1), 0);
                fence_regs<32>(acc);
                #pragma unroll 1
                for (int ch = 4; ch < 8; ch++) {
                    wg_fence();
                    #pragma unroll
                    for (int ks = 0; ks < 4; ks++) wg_ss64(acc, dA1 + ch * 1024 + ks * 2, dB + (ch * 4 + ks) * 128);
                    wg_commit();
                }
                wg_wait<0>();
                fence_regs<32>(acc);
                bar_arrive(14, 288);
                const float QS = 0.25f * 1.4426950408889634f;
                float qm = 0.0f;
                uint32_t qa[4][4];
                #pragma unroll
                for (int i = 0; i < 4; i++) {
                    #pragma unroll
                    for (int j = 0; j < 4; j++) qa[i][j] = pack_bf16(bf_round(acc[8 * i + 2 * j]) * QS, bf_round(acc[8 * i + 2 * j + 1]) * QS);
                    float n0 = bf_lo(qa[i][0]) * bf_lo(qa[i][0]) + bf_hi(qa[i][0]) * bf_hi(qa[i][0]) + bf_lo(qa[i][2]) * bf_lo(qa[i][2]) + bf_hi(qa[i][2]) * bf_hi(qa[i][2]);
                    float n1 = bf_lo(qa[i][1]) * bf_lo(qa[i][1]) + bf_hi(qa[i][1]) * bf_hi(qa[i][1]) + bf_lo(qa[i][3]) * bf_lo(qa[i][3]) + bf_hi(qa[i][3]) * bf_hi(qa[i][3]);
                    n0 += __shfl_xor_sync(0xffffffffu, n0, 1); n0 += __shfl_xor_sync(0xffffffffu, n0, 2);
                    n1 += __shfl_xor_sync(0xffffffffu, n1, 1); n1 += __shfl_xor_sync(0xffffffffu, n1, 2);
                    qm = (n0 != n0 || n1 != n1) ? __int_as_float(0x7f800000) : fmaxf(qm, fmaxf(n0, n1));
                }
                #pragma unroll
                for (int o = 16; o; o >>= 1) qm = fmaxf(qm, __shfl_xor_sync(0xffffffffu, qm, o));
                if (lane == 0) s_misc[warp] = qm;
                qx[0] = make_uint4(qa[2][0], qa[2][1], qa[2][2], qa[2][3]);
                qx[1] = make_uint4(qa[3][0], qa[3][1], qa[3][2], qa[3][3]);
                #pragma unroll
                for (int j = 0; j < 4; j++) { q[0][j] = qa[0][j]; q[1][j] = qa[1][j]; }
                bar_sync(1, 512);
            } else {
                if (kv_wg) {
                    float akv[8];
                    #pragma unroll
                    for (int i = 0; i < 8; i++) akv[i] = 0.0f;
                    fence_regs<8>(akv);
                    const uint64_t dC = make_desc(sb + SM_WKV, 128, 8192, 0);
                    #pragma unroll 1
                    for (int ch = 0; ch < 8; ch++) {
                        if ((ch & 3) == 0) mbar_wait(bars + 8 * (B_X + (ch >> 2)), 0);
                        const uint64_t dA = ch < 4 ? dA0 : dA1;
                        wg_fence();
                        #pragma unroll
                        for (int ks = 0; ks < 4; ks++) wg_ss16(akv, dA + ch * 1024 + ks * 2, dC + (ch * 4 + ks) * 16);
                        wg_commit();
                    }
                    wg_wait<0>();
                    fence_regs<8>(akv);
                    const int key = qb * 128 + rowhalf * 64 + wiw * 16 + g;
                    uint32_t pk[4];
                    #pragma unroll
                    for (int i = 0; i < 4; i++) pk[i] = pack_bf16(akv[2 * i], akv[2 * i + 1]);
                    float st;
                    if (kv_sel == 0) {
                        uint8_t* b = g_kimg + (key >> 3) * 256 + (key & 7) * 16 + 4 * t;
                        *(uint32_t*)(b) = pk[0]; *(uint32_t*)(b + 256) = pk[1]; *(uint32_t*)(b + 128) = pk[2]; *(uint32_t*)(b + 384) = pk[3];
                        float n0 = bf_lo(pk[0]) * bf_lo(pk[0]) + bf_hi(pk[0]) * bf_hi(pk[0]) + bf_lo(pk[2]) * bf_lo(pk[2]) + bf_hi(pk[2]) * bf_hi(pk[2]);
                        float n1 = bf_lo(pk[1]) * bf_lo(pk[1]) + bf_hi(pk[1]) * bf_hi(pk[1]) + bf_lo(pk[3]) * bf_lo(pk[3]) + bf_hi(pk[3]) * bf_hi(pk[3]);
                        n0 += __shfl_xor_sync(0xffffffffu, n0, 1); n0 += __shfl_xor_sync(0xffffffffu, n0, 2);
                        n1 += __shfl_xor_sync(0xffffffffu, n1, 1); n1 += __shfl_xor_sync(0xffffffffu, n1, 2);
                        st = (n0 != n0 || n1 != n1) ? __int_as_float(0x7f800000) : fmaxf(n0, n1);
                    } else {
                        uint8_t* lo = g_vimg + key * 16 + 4 * t;
                        uint8_t* hi = g_vimg + 33792 + (31 - (key >> 6)) * 1024 + (key & 63) * 16 + 4 * t;
                        *(uint32_t*)(lo) = pk[0]; *(uint32_t*)(lo + 128) = pk[1]; *(uint32_t*)(hi) = pk[2]; *(uint32_t*)(hi + 128) = pk[3];
                        st = 0.0f;
                        #pragma unroll
                        for (int i = 0; i < 4; i++) {
                            float a = fabsf(bf_lo(pk[i])), b = fabsf(bf_hi(pk[i]));
                            st = (a != a || b != b) ? __int_as_float(0x7f800000) : fmaxf(st, fmaxf(a, b));
                        }
                    }
                    #pragma unroll
                    for (int o = 16; o; o >>= 1) st = fmaxf(st, __shfl_xor_sync(0xffffffffu, st, o));
                    if (lane == 0) s_misc[20 + wiw] = st;
                bar_arrive(3, 160);
                }
                uint2 mp[3];
                #pragma unroll
                for (int i = 0; i < 3; i++) { const int w = (tid & 255) + 256 * i; mp[i] = (w < TABN / 4) ? __ldg((const uint2*)g_tabmap.v + w) : make_uint2(0u, 0u); }
                bar_sync(1, 512);
                stage_u();
                #pragma unroll 1
                for (int cc = 0; cc < 4; cc++) {
                    const float* kc = (const float*)(sB + S_KC + cc * 4096);
                    uint2* tab = (uint2*)(sB + S_TAB + cc * TABN * 2);
                    #pragma unroll
                    for (int i = 0; i < 3; i++) {
                        const int w = (tid & 255) + 256 * i;
                        if (w < TABN / 4) tab[w] = make_uint2(pack_bf16(kc[mp[i].x & 0xFFFF], kc[mp[i].x >> 16]), pack_bf16(kc[mp[i].y & 0xFFFF], kc[mp[i].y >> 16]));
                    }
                }
                bar_sync(2, 512);
                #pragma unroll 1
                for (int tk = tid & 255; tk < 4 * 130; tk += 256) {
                    const int c = tk / 130, i = tk % 130;
                    const uint32_t src = sBa + S_U + c * ULEN * 2 + (PADU + 8 * i - WPAD - 8) * 2;
                    const uint4 v0 = lds128(swz128(src)), v1 = lds128(swz128(src + 16)), v2 = lds128(swz128(src + 32));
                    float x[16];
                    const uint32_t vv[8] = {v0.z, v0.w, v1.x, v1.y, v1.z, v1.w, v2.x, v2.y};
                    #pragma unroll
                    for (int k = 0; k < 8; k++) { x[2 * k] = bf_lo(vv[k]); x[2 * k + 1] = bf_hi(vv[k]); }
                    float p2[15], w7[8], w9[8];
                    #pragma unroll
                    for (int e = 0; e < 15; e++) p2[e] = x[e] + x[e + 1];
                    #pragma unroll
                    for (int e = 0; e < 8; e++) {
                        w7[e] = (p2[e + 1] + p2[e + 3]) + (p2[e + 5] + x[e + 7]);
                        w9[e] = w7[e] + (x[e] + x[e + 8]);
                    }
                    sts128(swz(sBa + S_W7 + c * W3LEN * 2 + i * 16), make_uint4(pack_bf16(w7[0], w7[1]), pack_bf16(w7[2], w7[3]), pack_bf16(w7[4], w7[5]), pack_bf16(w7[6], w7[7])));
                    sts128(swz(sBa + S_W9 + c * W3LEN * 2 + i * 16), make_uint4(pack_bf16(w9[0], w9[1]), pack_bf16(w9[2], w9[3]), pack_bf16(w9[4], w9[5]), pack_bf16(w9[6], w9[7])));
                }
                bar_sync(1, 512);
                const uint4 q0 = qx[0], q1 = qx[1];
                q[0][0] = q0.x; q[0][1] = q0.y; q[0][2] = q0.z; q[0][3] = q0.w;
                q[1][0] = q1.x; q[1][1] = q1.y; q[1][2] = q1.z; q[1][3] = q1.w;
            }
        }
        PROF(3);
        {
            const int c = wg;
            uint32_t sBl = sBa;
            asm volatile("" : "+r"(sBl) :: "memory");
            float acc[16];
            const uint32_t tabc = sBl + S_TAB + c * TABN * 2;
            const uint32_t tD = tabc + ((g & 1) ? (TD1 + CD + 1) : (TD0 + CD)) * 2 - (g - 2 * t) * 2 - 32 * wiw;
            const uint32_t uLo = (((sBl + S_U + c * ULEN * 2 + PADU * 2) & 0x3FFFF) >> 4) | (1u << 16);
            uint32_t A[2][4][4];
            auto load_set = [&](uint32_t (&X)[4][4], uint32_t a) {
                X[0][2] = lds32(a + 16);
                #pragma unroll
                for (int i = 0; i < 4; i++) { X[i][0] = lds32(a - 32 * i); X[i][1] = lds32(a - 32 * i - 16); }
                #pragma unroll
                for (int i = 0; i < 4; i++) {
                    asm volatile("mov.b32 %0, %1;" : "=r"(X[i][3]) : "r"(X[i][0]));
                    if (i < 3) asm volatile("mov.b32 %0, %1;" : "=r"(X[i + 1][2]) : "r"(X[i][1]));
                }
            };
            {
                float accB[12];
                #pragma unroll
                for (int i = 0; i < 12; i++) accB[i] = 0.0f;
                fence_regs<12>(accB);
                #pragma unroll 1
                for (int m0 = 29; m0 < 69; m0 += 8) {
                    #pragma unroll
                    for (int h = 0; h < 2; h++) {
                        load_set(A[h], tD - 32 * (m0 + 4 * h));
                        wg_fence();
                        #pragma unroll
                        for (int i = 0; i < 4; i++) wg_rs24(accB, A[h][i], uLo + 64 - 2 * (m0 + 4 * h + i));
                        wg_commit();
                        wg_wait<1>();
                    }
                }
                wg_wait<0>();
                fence_regs<12>(accB);
                #pragma unroll
                for (int i = 0; i < 4; i++) acc[i] = 0.0f;
                #pragma unroll
                for (int i = 0; i < 12; i++) asm volatile("add.f32 %0, %1, 0f00000000;" : "=f"(acc[4 + i]) : "f"(accB[i]));
                fence_regs<16>(acc);
            }
            #pragma unroll 1
            for (int m0 = -3; m0 < 29; m0 += 8) {
                #pragma unroll
                for (int h = 0; h < 2; h++) {
                    load_set(A[h], tD - 32 * (m0 + 4 * h));
                    wg_fence();
                    #pragma unroll
                    for (int i = 0; i < 4; i++) wg_rs32(acc, A[h][i], uLo - 2 * (m0 + 4 * h + i));
                    wg_commit();
                    wg_wait<1>();
                }
            }
            wg_wait<0>();
            fence_regs<16>(acc);
            PROF(6);
            {
                asm volatile("" : "+r"(sBl) :: "memory");
                const int mi = lane >> 3, r8 = lane & 7;
                const uint32_t frag = (16 * (8 * (mi >> 1) + r8) + 8 * (mi & 1)) * 2;
                const uint32_t t3 = sBl + S_TAB + c * TABN * 2 + (T3B + ((wiw & 1) ? (T3C + C3 + 1) : C3)) * 2 - (4 * g + wiw - 2 * t) * 2;
                #pragma unroll
                for (int s = 0; s < 2; s++) {
                    const uint32_t sig = swz(sBl + (s ? S_W7 : S_W9) + c * W3LEN * 2 + WPAD * 2 + frag - (s ? 16 : 32));
                    uint32_t a[4][4], R[4][2];
                    #pragma unroll
                    for (int b = 0; b < 4; b++) ldsm4t_p(a[b], sig + b * 512);
                    #pragma unroll
                    for (int i = 0; i < 4; i++) { R[i][0] = lds32_p(t3 + s * (T3S * 2) - 2 * (48 + 16 * i)); R[i][1] = lds32_p(t3 + s * (T3S * 2) - 2 * (40 + 16 * i)); }
                    #pragma unroll
                    for (int b = 0; b < 4; b++) {
                        mma_bf16_p(acc + 12, a[b][0], a[b][1], a[b][2], a[b][3], R[3 - b][0], R[3 - b][1]);
                        if (b < 2) mma_bf16_p(acc + 8, a[b][0], a[b][1], a[b][2], a[b][3], R[1 - b][0], R[1 - b][1]);
                    }
                }
            }
            __nv_bfloat16* ys = (__nv_bfloat16*)(sB + S_Y + c * 4096) + 128 * t + 16 * wiw + g;
            #pragma unroll
            for (int j = 0; j < 4; j++) {
                ys[512 * j] = __float2bfloat16_rn(acc[4 * j]);
                ys[512 * j + 64] = __float2bfloat16_rn(acc[4 * j + 1]);
                ys[512 * j + 8] = __float2bfloat16_rn(acc[4 * j + 2]);
                ys[512 * j + 72] = __float2bfloat16_rn(acc[4 * j + 3]);
            }
        }
        bar_arrive(10, 608);
        PROF(7);
        {
            mbar_wait(bars + 8 * B_ST, 0);
            PROF(9); PROFC(8);
            float qm = 0.0f;
            #pragma unroll
            for (int i = 0; i < 8; i++) qm = fmaxf(qm, s_misc[i]);
            const float vm = s_misc[17];
            const bool fast = (qm * s_misc[16] <= 60.0f * 60.0f) && (vm <= 1.0e12f) && (vm >= 1.0e-12f || vm == 0.0f);
            uint8_t* ob = g_oimg + qb * 131072 + hg * 16384 + nh * 8192 + (rowhalf * 8 + wiw * 2) * 128 + g * 16 + 4 * t;
            uint32_t cA = 0xBF00BF00u, cB = 0x00030003u;
            asm volatile("" : "+r"(cA), "+r"(cB));
            #pragma unroll 1
            for (int tile = 0; tile < 2; tile++) {
                uint32_t kLo = (((sb + SM_K) & 0x3FFFF) >> 4) | (8u << 16), vLo = (((sb + SM_V) & 0x3FFFF) >> 4) | (8u << 16), vHi = 2048;
                float o[12], s[32];
                uint32_t p[16], qq[4];
                #pragma unroll
                for (int i = 0; i < 4; i++) { qq[i] = tile ? q[1][i] : q[0][i]; asm volatile("" : "+r"(qq[i])); }
                #pragma unroll
                for (int i = 0; i < 12; i++) o[i] = 0.0f;
                #pragma unroll
                for (int i = 0; i < 32; i++) s[i] = 0.0f;
                fence_regs<12>(o);
                fence_regs<32>(s);
                if (fast) {
                    #pragma unroll 1
                    for (int c = 0; c < SEQ / (64 * AU); c++) {
                        if (AU == 4) { if (c <= 4) mbar_wait(bars + 8 * (B_KV + (c < 2 ? c : c < 4 ? 2 : 3)), 0); }
                        else { if (c <= 2) mbar_wait(bars + 8 * (B_KV + (c ? c + 1 : 0)), 0); }
                        wg_fence();
                        wg_qk(s, qq, kLo);
                        wg_commit();
                        #pragma unroll
                        for (int u = 0; u < AU; u++) {
                            wg_wait<0>();
                            fence_regs<32>(s);
                            #pragma unroll
                            for (int i = 0; i < 16; i++) {
                                if ((MUFU_MASK >> i) & 1) p[i] = exp_mufu(s[2 * i], s[2 * i + 1]);
                                else p[i] = exp_sw(s[2 * i], s[2 * i + 1], cA, cB);
                            }
                            if (AU == 8 && u == 3) mbar_wait(bars + 8 * (B_KV + 1), 0);
                            wg_fence();
                            if (u + 1 < AU) wg_qk(s, qq, kLo + (u + 1) * 128);
                            #pragma unroll
                            for (int kk = 0; kk < 4; kk++) wg_pv(o, p + 4 * kk, vLo + u * 64 + kk * 16, vHi - u * 64);
                            wg_commit();
                        }
                        kLo += 128 * AU; vLo += 64 * AU; vHi -= 64 * AU;
                    }
                    wg_wait<0>();
                } else {
                    float mx0 = -INFINITY, mx1 = -INFINITY;
                    #pragma unroll 1
                    for (int c = 0; c < SEQ / 64; c++) {
                        if (c <= 16) mbar_wait(bars + 8 * (B_KV + (c < 8 ? (c >> 2) : c < 16 ? 2 : 3)), 0);
                        wg_fence();
                        wg_qk(s, qq, kLo);
                        wg_commit();
                        wg_wait<0>();
                        fence_regs<32>(s);
                        fence_regs<12>(o);
                        float m0 = mx0, m1 = mx1;
                        #pragma unroll
                        for (int j = 0; j < 8; j++) {
                            m0 = fmaxf(m0, fmaxf(s[4 * j], s[4 * j + 1]));
                            m1 = fmaxf(m1, fmaxf(s[4 * j + 2], s[4 * j + 3]));
                        }
                        m0 = fmaxf(m0, __shfl_xor_sync(0xffffffffu, m0, 1)); m0 = fmaxf(m0, __shfl_xor_sync(0xffffffffu, m0, 2));
                        m1 = fmaxf(m1, __shfl_xor_sync(0xffffffffu, m1, 1)); m1 = fmaxf(m1, __shfl_xor_sync(0xffffffffu, m1, 2));
                        const float c0 = ex2f(mx0 - m0), c1 = ex2f(mx1 - m1);
                        mx0 = m0; mx1 = m1;
                        #pragma unroll
                        for (int j = 0; j < 3; j++) { o[4 * j] *= c0; o[4 * j + 1] *= c0; o[4 * j + 2] *= c1; o[4 * j + 3] *= c1; }
                        #pragma unroll
                        for (int j = 0; j < 8; j++) {
                            p[2 * j] = exp_mufu(s[4 * j] - m0, s[4 * j + 1] - m0);
                            p[2 * j + 1] = exp_mufu(s[4 * j + 2] - m1, s[4 * j + 3] - m1);
                        }
                        wg_fence();
                        #pragma unroll
                        for (int kk = 0; kk < 4; kk++) wg_pv(o, p + 4 * kk, vLo + kk * 16, vHi);
                        wg_commit();
                        wg_wait<0>();
                        kLo += 128; vLo += 64; vHi -= 64;
                    }
                }
                fence_regs<12>(o);
                if (tile == 0) PROFC(3);
                const float i0 = 1.0f / o[4], i1 = 1.0f / o[6];
                uint8_t* b = ob + tile * 4096;
                *(uint32_t*)(b) = pack_bf16(o[0] * i0, o[1] * i0);
                *(uint32_t*)(b + 128) = pack_bf16(o[2] * i1, o[3] * i1);
                *(uint32_t*)(b + 2048) = pack_bf16(o[8] * i0, o[9] * i0);
                *(uint32_t*)(b + 2048 + 128) = pack_bf16(o[10] * i1, o[11] * i1);
            }
        }
        PROF(10); PROFC(9);
        bar_arrive(12, 544);

        if (wg < 2) {
            float acc[32];
            #pragma unroll
            for (int i = 0; i < 32; i++) acc[i] = 0.0f;
            fence_regs<32>(acc);
            const uint64_t dA = make_desc(sb + SM_A + rowhalf * 1024, 2048, 128, 0);
            const uint64_t dB = make_desc(sb + SM_B, 16, 1024, 1);
            mbar_wait(bars + 8 * B_WO, 0);
            #pragma unroll 1
            for (int i = 0; i < 8; i++) {
                const int src = ((hg & 6) + i) & 7;
                mbar_wait(bars + 8 * (B_O + src), 0);
                wg_fence();
                #pragma unroll
                for (int kk = 0; kk < 4; kk++) wg_ss64(acc, dA + src * 1024 + kk * 256, dB + (src * 4 + kk) * 128);
                wg_commit();
            }
            wg_wait<0>();
            fence_regs<32>(acc);
            PROF(12);
            const int row = qb * 128 + rowhalf * 64 + wiw * 16 + g;
            uint4* o128 = (uint4*)(P.out + (size_t)row * 1024 + hg * 64 + 8 * t);
            #pragma unroll
            for (int rr = 0; rr < 2; rr++)
                #pragma unroll
                for (int a = 0; a < 2; a++) {
                    uint32_t v[4];
                    #pragma unroll
                    for (int j = 0; j < 4; j++) v[j] = pack_bf16(acc[16 * a + 4 * j + 2 * rr], acc[16 * a + 4 * j + 2 * rr + 1]);
                    quad_transpose(v, t);
                    o128[rr * 1024 + a * 4] = make_uint4(v[0], v[1], v[2], v[3]);
                }
        }
        PROF(13);
    }
}

typedef CUresult (*EncodeFn)(CUtensorMap*, CUtensorMapDataType, cuuint32_t, void*, const cuuint64_t*, const cuuint64_t*,
                             const cuuint32_t*, const cuuint32_t*, CUtensorMapInterleave, CUtensorMapSwizzle,
                             CUtensorMapL2promotion, CUtensorMapFloatOOBfill);

void make_map(EncodeFn fn, CUtensorMap* m, const void* ptr, uint64_t inner, uint64_t outer, uint32_t box_in, uint32_t box_out, CUtensorMapSwizzle swz) {
    cuuint64_t dims[2] = {inner, outer};
    cuuint64_t strides[1] = {inner * 2};
    cuuint32_t box[2] = {box_in, box_out};
    cuuint32_t es[2] = {1, 1};
    fn(m, CU_TENSOR_MAP_DATA_TYPE_BFLOAT16, 2, const_cast<void*>(ptr), dims, strides, box, es, CU_TENSOR_MAP_INTERLEAVE_NONE, swz,
       CU_TENSOR_MAP_L2_PROMOTION_L2_128B, CU_TENSOR_MAP_FLOAT_OOB_FILL_NONE);
}

}

extern "C" void kernel_launch(void* const* d_in, const int* in_sizes, int n_in, void* d_out, int out_size) {
    (void)in_sizes; (void)n_in; (void)out_size;
    static EncodeFn fn = nullptr;
    if (!fn) {
        void* p = nullptr;
        cudaDriverEntryPointQueryResult qr;
        cudaGetDriverEntryPoint("cuTensorMapEncodeTiled", &p, cudaEnableDefault, &qr);
        fn = (EncodeFn)p;
        cudaFuncSetAttribute(fused_kernel, cudaFuncAttributeMaxDynamicSharedMemorySize, SM_ALLOC);
    }
    CUtensorMap tx, twq, two, twk, twv, tu;
    {
        cuuint64_t dims[3] = {64, 2048, 8};
        cuuint64_t strides[2] = {1024, 128};
        cuuint32_t box[3] = {64, 128, 4};
        cuuint32_t es[3] = {1, 1, 1};
        fn(&tx, CU_TENSOR_MAP_DATA_TYPE_BFLOAT16, 3, d_in[0], dims, strides, box, es, CU_TENSOR_MAP_INTERLEAVE_NONE, CU_TENSOR_MAP_SWIZZLE_128B,
           CU_TENSOR_MAP_L2_PROMOTION_L2_128B, CU_TENSOR_MAP_FLOAT_OOB_FILL_NONE);
    }
    make_map(fn, &tu, d_in[5], 512, 2048, 8, 256, CU_TENSOR_MAP_SWIZZLE_NONE);
    make_map(fn, &twq, d_in[1], 512, 512, 64, 256, CU_TENSOR_MAP_SWIZZLE_128B);
    make_map(fn, &twk, d_in[2], 16, 512, 8, 256, CU_TENSOR_MAP_SWIZZLE_NONE);
    make_map(fn, &twv, d_in[3], 16, 512, 8, 256, CU_TENSOR_MAP_SWIZZLE_NONE);
    make_map(fn, &two, d_in[4], 512, 512, 64, 256, CU_TENSOR_MAP_SWIZZLE_128B);
    Params P;
    P.u = (const __nv_bfloat16*)d_in[5];
    P.lar = (const __nv_bfloat16*)d_in[6];
    P.aim = (const __nv_bfloat16*)d_in[7];
    P.cre = (const __nv_bfloat16*)d_in[8];
    P.cim = (const __nv_bfloat16*)d_in[9];
    P.logdt = (const __nv_bfloat16*)d_in[10];
    P.dskip = (const __nv_bfloat16*)d_in[11];
    P.out = (__nv_bfloat16*)d_out;
    fused_kernel<<<NCTA, NTHR, SM_ALLOC>>>(tx, twq, two, twk, twv, tu, P);
}
```

```cpp
#include <cuda_runtime.h>
#include <cuda_bf16.h>
#include <cuda_fp16.h>
#include <cuda.h>
#include <stdint.h>

namespace {

constexpr int SEQ = 2048;
constexpr int NCTA = 128, NTHR = 640;

constexpr int SM_A = 0;
constexpr int SM_WQ = 65536;
constexpr int SM_SLAB = SM_WQ + 32768;
constexpr int SM_K = 0, SM_V = 65536;
constexpr int SM_B = 132096;
constexpr int SM_WKV = SM_B + 65536;

constexpr int PADU = 1024, ULEN = PADU + 2048;
constexpr int WPAD = 16, W3LEN = WPAD + 1024;
constexpr int TABN = 2912;
constexpr int S_PAIR = 49152;
__host__ __device__ constexpr int offU(int c) { return (c >> 1) * S_PAIR + (c & 1) * ULEN * 2; }
__host__ __device__ constexpr int offW7(int c) { return (c >> 1) * S_PAIR + 4 * ULEN + (c & 1) * W3LEN * 2; }
__host__ __device__ constexpr int offW9(int c) { return (c >> 1) * S_PAIR + 4 * ULEN + 4 * W3LEN + (c & 1) * W3LEN * 2; }
__host__ __device__ constexpr int offT(int c) { return (c >> 1) * S_PAIR + 4 * ULEN + 8 * W3LEN + (c & 1) * TABN * 2; }
constexpr int S_QX = 32768;
constexpr int S_KC = 214016 - SM_B;
constexpr int S_Y = S_KC;
constexpr int SM_BAR = SM_B + S_KC + 16384;
constexpr int SM_TOTAL = SM_BAR + 1024;
constexpr int SM_ALLOC = SM_TOTAL + 1024;
static_assert(SM_V + 65536 + 1024 <= SM_B && SM_ALLOC <= 232448 && offT(1) + TABN * 2 <= S_QX && S_QX + 8192 <= S_PAIR && offT(3) + TABN * 2 <= S_KC && SM_WKV + 16384 <= SM_B + S_KC, "smem map");

constexpr int TD0 = 0, TD1 = 1232, CD = 1152;
constexpr int T3B = 2464, T3S = 224, T3C = 112, C3 = 136;

constexpr int rne8(int t) {
    if (t < 256) return t;
    int sh = 0;
    while ((t >> sh) >= 256) sh++;
    int q = t >> sh, rem = t & ((1 << sh) - 1), half = 1 << (sh - 1);
    if (rem > half || (rem == half && (q & 1))) q++;
    return q << sh;
}
constexpr int kcidx(int p) {
    if (p < 256) return (p >> 3) * 24 + (p & 7);
    if (p < 512) return ((p - 256) >> 3) * 24 + 8 + (((p - 256) & 7) >> 1);
    if (p < 1024) { int q = p - 512, hi = q >> 8, rem = q & 255; return (rem >> 3) * 24 + 12 + 2 * hi + ((rem & 7) >> 2); }
    if (p < 2048) { int q = p - 1024; return ((q & 255) >> 3) * 24 + 16 + (q >> 8); }
    return 20;
}
constexpr int KC_ZERO = 23;
constexpr int tab_dense(int t) { return (t >= 0 && t <= 1028) ? kcidx(rne8(t)) : KC_ZERO; }
constexpr int tab_3(int s, int lag) { return (lag >= 64 && lag <= 127) ? kcidx(s == 0 ? 16 * (lag + 1) : 16 * lag + 8) : KC_ZERO; }
struct TabMap {
    uint16_t v[TABN];
    constexpr TabMap() : v{} {
        for (int i = 0; i < TD1; i++) { v[TD0 + i] = tab_dense(CD - i); v[TD1 + i] = tab_dense(CD + 1 - i); }
        for (int s = 0; s < 2; s++)
            for (int i = 0; i < T3C; i++) { v[T3B + s * T3S + i] = tab_3(s, C3 - i); v[T3B + s * T3S + T3C + i] = tab_3(s, C3 + 1 - i); }
    }
};
__device__ const __align__(16) TabMap g_tabmap = TabMap();

__device__ __align__(1024) uint8_t g_kimg[65536];
__device__ __align__(1024) uint8_t g_vimg[65536 + 1024];
__device__ __align__(1024) uint8_t g_oimg[16 * 131072];
__device__ unsigned long long g_flag_kv[64];
__device__ unsigned g_flag_o[128];
__device__ unsigned g_epoch;
__device__ unsigned g_done;

#define PROF(i) do {} while (0)
#define PROF2(i) do {} while (0)
#define PROFC(i) do {} while (0)
#define PROF3(i) do {} while (0)

__device__ __forceinline__ uint32_t smem_u32(const void* p) { return (uint32_t)__cvta_generic_to_shared(p); }
__device__ __forceinline__ void mbar_init(uint32_t bar, uint32_t cnt) { asm volatile("mbarrier.init.shared::cta.b64 [%0], %1;" :: "r"(bar), "r"(cnt) : "memory"); }
__device__ __forceinline__ void mbar_expect_tx(uint32_t bar, uint32_t bytes) {
    asm volatile("mbarrier.arrive.expect_tx.shared::cta.b64 _, [%0], %1;" :: "r"(bar), "r"(bytes) : "memory"); }
__device__ __forceinline__ void mbar_wait(uint32_t bar, uint32_t parity) {
    uint32_t ok = 0;
    for (int it = 0; it < (1 << 22) && !ok; it++) {
        asm volatile("{ .reg .pred p; mbarrier.try_wait.parity.shared::cta.b64 p, [%1], %2; selp.u32 %0, 1, 0, p; }"
                     : "=r"(ok) : "r"(bar), "r"(parity) : "memory");
    }
}
__device__ __forceinline__ void tma_2d(uint32_t dst, const CUtensorMap* map, int c0, int c1, uint32_t bar) {
    asm volatile("cp.async.bulk.tensor.2d.shared::cluster.global.mbarrier::complete_tx::bytes [%0], [%1, {%3, %4}], [%2];"
                 :: "r"(dst), "l"((uint64_t)map), "r"(bar), "r"(c0), "r"(c1) : "memory");
}
__device__ __forceinline__ void tma_2d_mc(uint32_t dst, const CUtensorMap* map, int c0, int c1, uint32_t bar) {
    asm volatile("cp.async.bulk.tensor.2d.shared::cluster.global.mbarrier::complete_tx::bytes.multicast::cluster [%0], [%1, {%3, %4}], [%2], %5;"
                 :: "r"(dst), "l"((uint64_t)map), "r"(bar), "r"(c0), "r"(c1), "h"((uint16_t)3) : "memory");
}
__device__ __forceinline__ void bulk_g2s_mc(uint32_t dst, const void* src, uint32_t bytes, uint32_t bar) {
    asm volatile("cp.async.bulk.shared::cluster.global.mbarrier::complete_tx::bytes.multicast::cluster [%0], [%1], %2, [%3], %4;"
                 :: "r"(dst), "l"((uint64_t)src), "r"(bytes), "r"(bar), "h"((uint16_t)3) : "memory");
}
__device__ __forceinline__ void pair_arrive(uint32_t bar, uint32_t peer) {
    uint32_t ra;
    asm volatile("mapa.shared::cluster.u32 %0, %1, %2;" : "=r"(ra) : "r"(bar), "r"(peer));
    asm volatile("mbarrier.arrive.shared::cluster.b64 _, [%0];" :: "r"(ra) : "memory");
    asm volatile("mbarrier.arrive.shared::cta.b64 _, [%0];" :: "r"(bar) : "memory");
}
__device__ __forceinline__ void pair_sync(uint32_t bar, uint32_t peer) { pair_arrive(bar, peer); mbar_wait(bar, 0); }
__device__ __forceinline__ void fence_async_all() { asm volatile("fence.proxy.async.global;" ::: "memory"); }
__device__ __forceinline__ void fence_async_smem() { asm volatile("fence.proxy.async.shared::cta;" ::: "memory"); }
__device__ __forceinline__ unsigned ld_acquire(const unsigned* p) {
    unsigned v; asm volatile("ld.acquire.gpu.global.u32 %0, [%1];" : "=r"(v) : "l"(p) : "memory"); return v; }
__device__ __forceinline__ void st_release(unsigned* p, unsigned v) { asm volatile("st.release.gpu.global.u32 [%0], %1;" :: "l"(p), "r"(v) : "memory"); }
__device__ __forceinline__ void wait_flag(const unsigned* p, unsigned epoch) {
    for (int it = 0; it < (1 << 22); it++) { if (ld_acquire(p) == epoch) break; }
}
__device__ __forceinline__ unsigned long long ld_acquire64(const unsigned long long* p) {
    unsigned long long v; asm volatile("ld.acquire.gpu.global.u64 %0, [%1];" : "=l"(v) : "l"(p) : "memory"); return v; }
__device__ __forceinline__ void st_release64(unsigned long long* p, unsigned long long v) { asm volatile("st.release.gpu.global.u64 [%0], %1;" :: "l"(p), "l"(v) : "memory"); }
__device__ __forceinline__ float wait_flag64(const unsigned long long* p, unsigned epoch) {
    unsigned long long v = 0;
    for (int it = 0; it < (1 << 22); it++) { v = ld_acquire64(p); if ((unsigned)(v >> 32) == epoch) break; }
    return __uint_as_float((unsigned)v);
}
__device__ __forceinline__ void tma_3d_mc(uint32_t dst, const CUtensorMap* map, int c0, int c1, int c2, uint32_t bar) {
    asm volatile("cp.async.bulk.tensor.3d.shared::cluster.global.mbarrier::complete_tx::bytes.multicast::cluster [%0], [%1, {%3, %4, %5}], [%2], %6;"
                 :: "r"(dst), "l"((uint64_t)map), "r"(bar), "r"(c0), "r"(c1), "r"(c2), "h"((uint16_t)3) : "memory");
}
__device__ __forceinline__ void bar_sync(int id, int n) { asm volatile("bar.sync %0, %1;" :: "r"(id), "r"(n) : "memory"); }
__device__ __forceinline__ void bar_arrive(int id, int n) { asm volatile("bar.arrive %0, %1;" :: "r"(id), "r"(n) : "memory"); }
__device__ __forceinline__ void mbar_arrive(uint32_t bar) { asm volatile("mbarrier.arrive.shared::cta.b64 _, [%0];" :: "r"(bar) : "memory"); }

__device__ __forceinline__ uint64_t make_desc(uint32_t saddr, uint32_t lbo, uint32_t sbo, uint32_t swz) {
    uint64_t d = 0;
    d |= (uint64_t)((saddr & 0x3FFFF) >> 4);
    d |= (uint64_t)((lbo >> 4) & 0x3FFF) << 16;
    d |= (uint64_t)((sbo >> 4) & 0x3FFF) << 32;
    d |= (uint64_t)swz << 62;
    return d;
}
__device__ __forceinline__ void wg_fence() { asm volatile("wgmma.fence.sync.aligned;" ::: "memory"); }
__device__ __forceinline__ void wg_commit() { asm volatile("wgmma.commit_group.sync.aligned;" ::: "memory"); }
template<int N> __device__ __forceinline__ void wg_wait() { asm volatile("wgmma.wait_group.sync.aligned %0;" :: "n"(N) : "memory"); }
#define A4(d, o) "+f"(d[o + 0]), "+f"(d[o + 1]), "+f"(d[o + 2]), "+f"(d[o + 3])
#define A16(d, o) A4(d, o), A4(d, o + 4), A4(d, o + 8), A4(d, o + 12)

__device__ __forceinline__ void wg_pv(float* d, const uint32_t* a, uint32_t lo, uint32_t hi) {
    asm volatile("{ .reg .b64 dd; mov.b64 dd, {%16, %17};\n"
                 "wgmma.mma_async.sync.aligned.m64n24k16.f32.bf16.bf16 {%0,%1,%2,%3,%4,%5,%6,%7,%8,%9,%10,%11}, {%12,%13,%14,%15}, dd, 1, 1, 1, 1; }"
                 : A4(d, 0), A4(d, 4), A4(d, 8) : "r"(a[0]), "r"(a[1]), "r"(a[2]), "r"(a[3]), "r"(lo), "r"(hi));
}
__device__ __forceinline__ void wg_qk(float* d, const uint32_t* a, uint32_t lo) {
    asm volatile("{ .reg .b64 dd; mov.b64 dd, {%36, %37};\n"
                 "wgmma.mma_async.sync.aligned.m64n64k16.f32.bf16.bf16 {%0,%1,%2,%3,%4,%5,%6,%7,%8,%9,%10,%11,%12,%13,%14,%15,%16,%17,%18,%19,%20,%21,%22,%23,%24,%25,%26,%27,%28,%29,%30,%31}, {%32,%33,%34,%35}, dd, 0, 1, 1, 0; }"
                 : A16(d, 0), A16(d, 16) : "r"(a[0]), "r"(a[1]), "r"(a[2]), "r"(a[3]), "r"(lo), "r"(16));
}
__device__ __forceinline__ void wg_rs32(float* d, const uint32_t* a, uint32_t lo) {
    asm volatile("{ .reg .b64 dd; mov.b64 dd, {%20, %21};\n"
                 "wgmma.mma_async.sync.aligned.m64n32k16.f32.bf16.bf16 {%0,%1,%2,%3,%4,%5,%6,%7,%8,%9,%10,%11,%12,%13,%14,%15}, {%16,%17,%18,%19}, dd, 1, 1, 1, 0; }"
                 : A16(d, 0) : "r"(a[0]), "r"(a[1]), "r"(a[2]), "r"(a[3]), "r"(lo), "r"(0x40000040));
}
__device__ __forceinline__ void wg_rs24(float* d, const uint32_t* a, uint32_t lo) {
    asm volatile("{ .reg .b64 dd; mov.b64 dd, {%16, %17};\n"
                 "wgmma.mma_async.sync.aligned.m64n24k16.f32.bf16.bf16 {%0,%1,%2,%3,%4,%5,%6,%7,%8,%9,%10,%11}, {%12,%13,%14,%15}, dd, 1, 1, 1, 0; }"
                 : A4(d, 0), A4(d, 4), A4(d, 8) : "r"(a[0]), "r"(a[1]), "r"(a[2]), "r"(a[3]), "r"(lo), "r"(0x40000040));
}
__device__ __forceinline__ void wg_ss64(float* d, uint64_t da, uint64_t db) {
    asm volatile("wgmma.mma_async.sync.aligned.m64n64k16.f32.bf16.bf16 {%0,%1,%2,%3,%4,%5,%6,%7,%8,%9,%10,%11,%12,%13,%14,%15,%16,%17,%18,%19,%20,%21,%22,%23,%24,%25,%26,%27,%28,%29,%30,%31}, %32, %33, 1, 1, 1, 0, 1;"
                 : A16(d, 0), A16(d, 16) : "l"(da), "l"(db));
}
__device__ __forceinline__ void wg_ss16(float* d, uint64_t da, uint64_t db) {
    asm volatile("wgmma.mma_async.sync.aligned.m64n16k16.f32.bf16.bf16 {%0,%1,%2,%3,%4,%5,%6,%7}, %8, %9, 1, 1, 1, 0, 1;"
                 : A4(d, 0), A4(d, 4) : "l"(da), "l"(db));
}
template<int N> __device__ __forceinline__ void fence_regs(float* r) {
    #pragma unroll
    for (int i = 0; i < N; i++) asm volatile("" : "+f"(r[i]) :: "memory");
}
__device__ __forceinline__ void mma_f16(float* d, const uint32_t* a, uint32_t b0, uint32_t b1) {
    asm volatile("mma.sync.aligned.m16n8k16.row.col.f32.f16.f16.f32 {%0,%1,%2,%3}, {%4,%5,%6,%7}, {%8,%9}, {%0,%1,%2,%3};"
                 : "+f"(d[0]), "+f"(d[1]), "+f"(d[2]), "+f"(d[3]) : "r"(a[0]), "r"(a[1]), "r"(a[2]), "r"(a[3]), "r"(b0), "r"(b1));
}
__device__ __forceinline__ uint32_t lds32(uint32_t addr) { uint32_t v; asm volatile("ld.shared.u32 %0, [%1];" : "=r"(v) : "r"(addr) : "memory"); return v; }
__device__ __forceinline__ void mma_bf16_p(float* d, uint32_t a0, uint32_t a1, uint32_t a2, uint32_t a3, uint32_t b0, uint32_t b1) {
    asm("mma.sync.aligned.m16n8k16.row.col.f32.bf16.bf16.f32 {%0,%1,%2,%3}, {%4,%5,%6,%7}, {%8,%9}, {%0,%1,%2,%3};"
        : "+f"(d[0]), "+f"(d[1]), "+f"(d[2]), "+f"(d[3]) : "r"(a0), "r"(a1), "r"(a2), "r"(a3), "r"(b0), "r"(b1));
}
__device__ __forceinline__ void ldsm4t_p(uint32_t* r, uint32_t addr) {
    asm("ldmatrix.sync.aligned.m8n8.x4.trans.shared.b16 {%0,%1,%2,%3}, [%4];" : "=r"(r[0]), "=r"(r[1]), "=r"(r[2]), "=r"(r[3]) : "r"(addr));
}
__device__ __forceinline__ uint32_t lds32_p(uint32_t addr) { uint32_t v; asm("ld.shared.u32 %0, [%1];" : "=r"(v) : "r"(addr)); return v; }
__device__ __forceinline__ uint32_t swz(uint32_t a) { return a ^ ((a >> 3) & 16u); }
__device__ __forceinline__ uint32_t swz128(uint32_t a) { return a ^ ((a >> 3) & 0x70u); }
__device__ __forceinline__ void sts32(uint32_t addr, uint32_t v) { asm volatile("st.shared.u32 [%0], %1;" :: "r"(addr), "r"(v) : "memory"); }
__device__ __forceinline__ void sts128(uint32_t addr, uint4 v) { asm volatile("st.shared.v4.u32 [%0], {%1,%2,%3,%4};" :: "r"(addr), "r"(v.x), "r"(v.y), "r"(v.z), "r"(v.w) : "memory"); }
__device__ __forceinline__ uint4 lds128(uint32_t addr) { uint4 v; asm volatile("ld.shared.v4.u32 {%0,%1,%2,%3}, [%4];" : "=r"(v.x), "=r"(v.y), "=r"(v.z), "=r"(v.w) : "r"(addr) : "memory"); return v; }
__device__ __forceinline__ void quad_transpose(uint32_t* v, int t) {
    #pragma unroll
    for (int p = 0; p < 2; p++) {
        const uint32_t x = __shfl_xor_sync(0xffffffffu, (t & 1) ? v[2 * p] : v[2 * p + 1], 1);
        if (t & 1) v[2 * p] = x; else v[2 * p + 1] = x;
    }
    #pragma unroll
    for (int p = 0; p < 2; p++) {
        const uint32_t x = __shfl_xor_sync(0xffffffffu, (t & 2) ? v[p] : v[p + 2], 2);
        if (t & 2) v[p] = x; else v[p + 2] = x;
    }
}
__device__ __forceinline__ float ex2f(float x) { float r; asm("ex2.approx.ftz.f32 %0, %1;" : "=f"(r) : "f"(x)); return r; }
__device__ __forceinline__ uint32_t pack_bf16(float lo, float hi) { uint32_t r; asm("cvt.rn.bf16x2.f32 %0, %1, %2;" : "=r"(r) : "f"(hi), "f"(lo)); return r; }
__device__ __forceinline__ uint32_t pack_f16(float lo, float hi) { uint32_t r; asm("cvt.rn.f16x2.f32 %0, %1, %2;" : "=r"(r) : "f"(hi), "f"(lo)); return r; }
__device__ __forceinline__ float bf_lo(uint32_t v) { return __uint_as_float(v << 16); }
__device__ __forceinline__ float bf_hi(uint32_t v) { return __uint_as_float(v & 0xFFFF0000u); }
__device__ __forceinline__ float bf_round(float x) { return __bfloat162float(__float2bfloat16_rn(x)); }

__device__ __forceinline__ uint32_t exp_mufu(float x0, float x1) { return pack_bf16(ex2f(x0), ex2f(x1)); }
#define SW_MAGIC (256.0f + 127.0f - 0.598938f)
__device__ __forceinline__ uint32_t exp_sw(float x0, float x1, uint32_t cA, uint32_t cB) {
    float t0 = x0 + SW_MAGIC, t1 = x1 + SW_MAGIC;
    uint32_t L, mh, ec, r;
    asm("prmt.b32 %0, %1, %2, 0x6521;" : "=r"(L) : "r"(__float_as_uint(t0)), "r"(__float_as_uint(t1)));
    asm("lop3.b32 %0, %1, 0x007F007F, %2, 0xEA;" : "=r"(mh) : "r"(L), "r"(cA));
    asm("lop3.b32 %0, %1, 0x7F807F80, %2, 0xEA;" : "=r"(ec) : "r"(L), "r"(cB));
    asm("fma.rn.bf16x2 %0, %1, %2, %3;" : "=r"(r) : "r"(L), "r"(mh), "r"(ec));
    return r;
}
#define MUFU_MASK_V 0x0555
#define AU_V 8
constexpr uint32_t MUFU_MASK = MUFU_MASK_V;
constexpr int AU = AU_V;

struct cf { float x, y; };
__device__ __forceinline__ cf cmul(cf a, cf b) { cf r; r.x = a.x * b.x - a.y * b.y; r.y = a.x * b.y + a.y * b.x; return r; }
__device__ __forceinline__ cf cexp_p(float a2, float b, float p) {
    float e = ex2f(a2 * p);
    float ph = b * p;
    ph -= (ph + 12582912.0f) - 12582912.0f;
    float ang = ph * 6.283185307f;
    cf r; r.x = e * __cosf(ang); r.y = e * __sinf(ang);
    return r;
}
__device__ __forceinline__ uint32_t h2_cmul(uint32_t w, uint32_t wsw, uint32_t e) {
    __half2 hw = *(__half2*)&w, hs = *(__half2*)&wsw, he = *(__half2*)&e;
    __half2 r = __hfma2(hs, __high2half2(he), __hmul2(hw, __low2half2(he)));
    return *(uint32_t*)&r;
}

struct Params {
    const __nv_bfloat16 *u, *lar, *aim, *cre, *cim, *logdt, *dskip;
    __nv_bfloat16* out;
};

constexpr int B_O = 0, B_WO2 = 8, B_KV = 9, B_WO = 13, B_WQ2 = 14, B_ST = 15, B_H = 16, B_X = 18, B_U = 20, B_WQ = 21;

__device__ __forceinline__ void ssm_out_pass(const Params& P, const uint8_t* sB, int idx) {
    const int d0 = blockIdx.x * 4;
    #pragma unroll 1
    for (int pi = idx; pi < 1024; pi += 352) {
        const int l = 2 * pi;
        uint32_t r[4];
        #pragma unroll
        for (int cc = 0; cc < 4; cc++) r[cc] = *(const uint32_t*)(sB + S_Y + cc * 4096 + l * 2);
        *(uint2*)(P.out + (size_t)l * 1024 + 512 + d0) = make_uint2(__byte_perm(r[0], r[1], 0x5410), __byte_perm(r[2], r[3], 0x5410));
        *(uint2*)(P.out + (size_t)(l + 1) * 1024 + 512 + d0) = make_uint2(__byte_perm(r[0], r[1], 0x7632), __byte_perm(r[2], r[3], 0x7632));
    }
}

__device__ __forceinline__ void helper_role(const Params& P, uint8_t* sp, uint32_t sb, const CUtensorMap* tm_wo, unsigned epoch) {
    const int tid = threadIdx.x - 544;
    const int hg = blockIdx.x & 7;
    asm volatile("barrier.cluster.wait.aligned;" ::: "memory");
    if (hg < 4 && tid < 32) {
        bar_sync(3, 160);
        if (tid == 0) {
            const float* s_misc = (const float*)(sp + SM_BAR + 256);
            const float st = fmaxf(fmaxf(s_misc[20], s_misc[21]), fmaxf(s_misc[22], s_misc[23]));
            st_release64(&g_flag_kv[((blockIdx.x >> 3) * 2 + (hg & 1)) * 2 + (hg >> 1)], ((unsigned long long)epoch << 32) | __float_as_uint(st));
        }
        __syncwarp();
    }
    PROF2(2);
    bar_sync(10, 608);
    if (tid == 0) { fence_async_smem(); tma_2d(sb + SM_B + S_PAIR, tm_wo, hg * 64, 384, sb + SM_BAR + 8 * B_WO2); }
    ssm_out_pass(P, sp + SM_B, 256 + tid);
    PROF2(4);
}

__global__ void __cluster_dims__(2, 1, 1) __launch_bounds__(NTHR, 1)
fused_kernel(const __grid_constant__ CUtensorMap tm_x, const __grid_constant__ CUtensorMap tm_wq,
             const __grid_constant__ CUtensorMap tm_wo, const __grid_constant__ CUtensorMap tm_wk,
             const __grid_constant__ CUtensorMap tm_wv, const __grid_constant__ CUtensorMap tm_u, const Params P) {
    extern __shared__ uint8_t smem_raw[];
    const uint32_t sb = (smem_u32(smem_raw) + 1023u) & ~1023u;
    uint8_t* sp = smem_raw + (sb - smem_u32(smem_raw));

    const int tid = threadIdx.x, warp = tid >> 5, lane = tid & 31, wg = tid >> 7, wiw = warp & 3;
    const int g = lane >> 2, t = lane & 3;
    const int qb = blockIdx.x >> 3, hg = blockIdx.x & 7;
    const uint32_t rank = blockIdx.x & 1;
    const int rowhalf = wg & 1, nh = wg >> 1;
    const bool kv_cta = hg < 4;
    const int kv_sel = hg >> 1;
    const bool kv_wg = kv_cta && (wg == 2 + (hg & 1));

    const uint32_t bars = sb + SM_BAR;
    float* s_misc = (float*)(sp + SM_BAR + 256);
    const CUtensorMap* tm_kv = kv_sel ? &tm_wv : &tm_wk;

    PROF(0);
    unsigned short p_lar = 0, p_aim = 0, p_cre = 0, p_cim = 0, p_ldt = 0;
    if (wg < 4) {
        const int n = (blockIdx.x * 4 + wg) * 128 + (tid & 127);
        p_lar = __ldg((const unsigned short*)P.lar + n);
        p_aim = __ldg((const unsigned short*)P.aim + n);
        p_cre = __ldg((const unsigned short*)P.cre + n);
        p_cim = __ldg((const unsigned short*)P.cim + n);
        p_ldt = __ldg((const unsigned short*)P.logdt + blockIdx.x * 4 + wg);
    } else if (warp == 16) {
        PROF3(5);
        if (lane == 0) {
            asm volatile("prefetch.tensormap [%0];" :: "l"((uint64_t)&tm_x) : "memory");
            asm volatile("prefetch.tensormap [%0];" :: "l"((uint64_t)tm_kv) : "memory");
            asm volatile("prefetch.tensormap [%0];" :: "l"((uint64_t)&tm_wq) : "memory");
            asm volatile("prefetch.tensormap [%0];" :: "l"((uint64_t)&tm_u) : "memory");
            mbar_init(bars + 8 * B_X, 1);
            mbar_init(bars + 8 * B_X + 8, 1);
            mbar_init(bars + 8 * B_U, 1);
            asm volatile("fence.mbarrier_init.release.cluster;" ::: "memory");
            mbar_expect_tx(bars + 8 * B_X, 65536u + (kv_cta ? 8192u : 0u));
            mbar_expect_tx(bars + 8 * B_X + 8, 65536u + (kv_cta ? 8192u : 0u));
            mbar_expect_tx(bars + 8 * B_U, 32768u);
        }
        __syncwarp();
        PROF3(6);
    }
    asm volatile("barrier.cluster.arrive.relaxed.aligned;" ::: "memory");
    const unsigned epoch = *(volatile unsigned*)&g_epoch + 1u;
    if (warp > 16) {
        if (lane == 0) {
            for (int i = warp - 17; i < B_X; i += 3) {
                mbar_init(bars + 8 * i, i >= B_H ? 2 : 1);
                if (i <= B_WQ2) mbar_expect_tx(bars + 8 * i, i < B_KV + 2 ? 16384u : i == B_KV + 3 ? 65536u : i == B_WO ? 49152u : 32768u);
            }
            asm volatile("fence.mbarrier_init.release.cluster;" ::: "memory");
            fence_async_smem();
        } else if (warp == 19) {
            #pragma unroll
            for (int i = 0; i < 2; i++) if (lane - 1 + 31 * i < 46) asm volatile("prefetch.global.L2 [%0];" :: "l"((const char*)g_tabmap.v + (lane - 1 + 31 * i) * 128));
        }
        __syncwarp();
    }
    asm volatile("barrier.cluster.wait.aligned;" ::: "memory");
    PROF(5);
    if (warp == 16 && lane == 0) {
        tma_3d_mc(sb + (rank ? SM_A : SM_B), &tm_x, 0, qb * 128, rank * 4, bars + 8 * (B_X + rank));
        if (kv_cta) {
            #pragma unroll
            for (int i = 0; i < 4; i++) tma_2d(sb + SM_WKV + i * 4096, tm_kv, (i >> 1) * 8, (i & 1) * 256, bars + 8 * (B_X + (i & 1)));
        }
        mbar_init(bars + 8 * B_WQ, 1);
        asm volatile("fence.mbarrier_init.release.cluster;" ::: "memory");
        fence_async_smem();
        mbar_expect_tx(bars + 8 * B_WQ, 32768u);
        tma_2d(sb + SM_WQ, &tm_wq, hg * 64, 0, bars + 8 * B_WQ);
        #pragma unroll
        for (int i = 0; i < 4; i++) tma_2d_mc(sb + SM_SLAB + (rank * 4 + i) * 4096, &tm_u, (blockIdx.x >> 1) * 8, (rank * 4 + i) * 256, bars + 8 * B_U);
    }
    __syncwarp();
    asm volatile("barrier.cluster.arrive.relaxed.aligned;" ::: "memory");

    if (warp == 16) {
        if (lane == 0) asm volatile("prefetch.tensormap [%0];" :: "l"((uint64_t)&tm_wo) : "memory");
        asm volatile("barrier.cluster.wait.aligned;" ::: "memory");
        PROF3(10);
        bar_sync(13, 544);
        if (lane == 0) { fence_async_smem(); tma_2d(sb + SM_SLAB, &tm_wq, hg * 64, 256, bars + 8 * B_WQ2); }
        bar_sync(14, 288);
        if (lane == 0) pair_sync(bars + 8 * B_H, rank ^ 1);
        __syncwarp();
        PROF3(11);
        *(uint4*)(sp + SM_V + 32768 + lane * 32) = make_uint4(0x3F803F80u, 0x3F803F80u, 0x3F803F80u, 0x3F803F80u);
        *(uint4*)(sp + SM_V + 32768 + lane * 32 + 16) = make_uint4(0x3F803F80u, 0x3F803F80u, 0x3F803F80u, 0x3F803F80u);
        fence_async_smem();
        float km = wait_flag64(&g_flag_kv[2 * lane], epoch);
        float vm = wait_flag64(&g_flag_kv[2 * lane + 1], epoch);
        __syncwarp();
        PROF3(12);
        if (lane == 0) {
            fence_async_all();
            #pragma unroll
            for (int i = 0; i < 4; i++) {
                const uint32_t k0 = i == 0 ? 0 : 128u << i, nk = i == 0 ? 256 : 128u << i;
                const uint32_t bar = bars + 8 * (B_KV + i);
                if (rank == 0) bulk_g2s_mc(sb + SM_K + k0 * 32, g_kimg + k0 * 32, nk * 32, bar);
                else {
                    bulk_g2s_mc(sb + SM_V + k0 * 16, g_vimg + k0 * 16, nk * 16, bar);
                    bulk_g2s_mc(sb + SM_V + 66560 - (k0 + nk) * 16, g_vimg + 66560 - (k0 + nk) * 16, nk * 16, bar);
                }
            }
        }
        #pragma unroll
        for (int o = 16; o; o >>= 1) { km = fmaxf(km, __shfl_xor_sync(0xffffffffu, km, o)); vm = fmaxf(vm, __shfl_xor_sync(0xffffffffu, vm, o)); }
        if (lane == 0) { s_misc[16] = km; s_misc[17] = vm; mbar_arrive(bars + 8 * B_ST); }
        PROF3(13);
        bar_sync(11, 544);
        if (lane < 3) { fence_async_smem(); tma_2d(sb + SM_B + lane * 16384, &tm_wo, hg * 64, lane * 128, bars + 8 * B_WO); }
        bar_sync(12, 544);
        if (lane == 0) pair_arrive(bars + 8 * (B_H + 1), rank ^ 1);
        if (lane == 0) {
            st_release(&g_flag_o[blockIdx.x], epoch);
            mbar_wait(bars + 8 * (B_H + 1), 0);
        }
        __syncwarp();
        PROF3(14);
        if (lane < 4) {
            const int src = (2 * lane + (hg & 6) + rank) & 7;
            wait_flag(&g_flag_o[qb * 8 + src], epoch);
            fence_async_all();
            bulk_g2s_mc(sb + SM_A + src * 16384, g_oimg + qb * 131072 + src * 16384, 16384, bars + 8 * (B_O + src));
        }
        __syncwarp();
        PROF3(15);
        if (lane == 0) {
            const unsigned prev = atomicAdd(&g_done, 1u);
            if (prev == NCTA - 1) {
                g_done = 0;
                __threadfence();
                *(volatile unsigned*)&g_epoch = epoch;
            }
        }
    } else if (wg == 4) {
        helper_role(P, sp, sb, &tm_wo, epoch);
    } else {
        uint8_t* sB = sp + SM_B;
        const uint32_t sBa = sb + SM_B;
        {
            const int c = wg;
            const float dt = bf_round(expf(bf_lo(p_ldt)));
            const float are = -bf_round(expf(bf_lo(p_lar))) * dt;
            const float aim = bf_lo(p_aim) * dt;
            float cr = 2.0f * (bf_lo(p_cre) * dt);
            float ci = 2.0f * (bf_lo(p_cim) * dt);
            const float a2 = are * 1.4426950408889634f, bb = aim * 0.15915494309189535f;
            float m = fmaxf(fabsf(cr), fabsf(ci));
            #pragma unroll
            for (int o = 16; o; o >>= 1) m = fmaxf(m, __shfl_xor_sync(0xffffffffu, m, o));
            int ebits = (__float_as_uint(m) >> 23) & 0xFF;
            ebits = min(max(ebits, 2), 250);
            const float scale = __uint_as_float((uint32_t)(ebits + 1) << 23);
            const float iscale = __uint_as_float((uint32_t)(253 - ebits) << 23);
            cf cc; cc.x = cr * iscale; cc.y = ci * iscale;

            const uint32_t stg = sBa + S_KC + warp * 1024;
            uint4* stp = (uint4*)(sB + S_KC + warp * 1024 + lane * 32);
            const uint32_t fa = stg + t * 32 + g * 4;

            uint32_t af[4][2][4];
            cf E256;
            {
                const cf E8 = cexp_p(a2, bb, 8.0f);
                uint32_t w[8];
                cf cur; cur.x = 1.0f; cur.y = 0.0f;
                w[0] = pack_f16(1.0f, 0.0f);
                cur = E8; w[1] = pack_f16(cur.x, cur.y);
                #pragma unroll
                for (int i = 2; i < 8; i++) { cur = cmul(cur, E8); w[i] = pack_f16(cur.x, cur.y); }
                stp[0] = make_uint4(w[0], w[1], w[2], w[3]);
                stp[1] = make_uint4(w[4], w[5], w[6], w[7]);
                const cf E64 = cexp_p(a2, bb, 64.0f);
                const cf E128 = cmul(E64, E64), E192 = cmul(E128, E64);
                E256 = cexp_p(a2, bb, 256.0f);
                const uint32_t e1 = pack_f16(E64.x, E64.y), e2 = pack_f16(E128.x, E128.y), e3 = pack_f16(E192.x, E192.y);
                __syncwarp();
                #pragma unroll
                for (int s = 0; s < 4; s++) {
                    #pragma unroll
                    for (int hh = 0; hh < 2; hh++) {
                        const uint32_t w0 = lds32(fa + s * 256 + hh * 128);
                        const uint32_t wsw = __byte_perm(w0, 0, 0x1032) ^ 0x00008000u;
                        const int src = 8 * s + t + 4 * hh;
                        const uint32_t f1 = __shfl_sync(0xffffffffu, e1, src), f2 = __shfl_sync(0xffffffffu, e2, src), f3 = __shfl_sync(0xffffffffu, e3, src);
                        af[s][0][2 * hh] = w0;
                        af[s][0][2 * hh + 1] = h2_cmul(w0, wsw, f1);
                        af[s][1][2 * hh] = h2_cmul(w0, wsw, f2);
                        af[s][1][2 * hh + 1] = h2_cmul(w0, wsw, f3);
                    }
                }
                __syncwarp();
            }
            float acc[2][3][4];
            #pragma unroll
            for (int i = 0; i < 24; i++) (&acc[0][0][0])[i] = 0.0f;
            const cf E1 = cexp_p(a2, bb, 1.0f);
            const cf E2 = cmul(E1, E1), E4 = cmul(E2, E2);
            cf X512;
            #pragma unroll
            for (int nt = 0; nt < 3; nt++) {
                uint32_t xv[8];
                if (nt == 0) {
                    cf cur = cc;
                    xv[0] = pack_f16(cur.x, -cur.y);
                    #pragma unroll
                    for (int i = 1; i < 8; i++) { cur = cmul(cur, E1); xv[i] = pack_f16(cur.x, -cur.y); }
                } else if (nt == 1) {
                    cf cur = cmul(cc, E256);
                    X512 = cmul(cur, E256);
                    xv[0] = pack_f16(cur.x, -cur.y);
                    #pragma unroll
                    for (int i = 1; i < 4; i++) { cur = cmul(cur, E2); xv[i] = pack_f16(cur.x, -cur.y); }
                    cur = cmul(X512, E4);
                    xv[4] = pack_f16(X512.x, -X512.y); xv[5] = pack_f16(cur.x, -cur.y);
                    X512 = cmul(X512, E256);
                    cur = cmul(X512, E4);
                    xv[6] = pack_f16(X512.x, -X512.y); xv[7] = pack_f16(cur.x, -cur.y);
                } else {
                    cf cur = X512;
                    #pragma unroll
                    for (int i = 0; i < 5; i++) { cur = cmul(cur, E256); xv[i] = pack_f16(cur.x, -cur.y); }
                    xv[5] = 0; xv[6] = 0; xv[7] = 0;
                }
                stp[0] = make_uint4(xv[0], xv[1], xv[2], xv[3]);
                stp[1] = make_uint4(xv[4], xv[5], xv[6], xv[7]);
                __syncwarp();
                #pragma unroll
                for (int s = 0; s < 4; s++) {
                    const uint32_t b0 = lds32(fa + s * 256), b1 = lds32(fa + s * 256 + 128);
                    mma_f16(acc[0][nt], af[s][0], b0, b1);
                    mma_f16(acc[1][nt], af[s][1], b0, b1);
                }
                __syncwarp();
            }
            float* kc = (float*)(sB + S_KC + c * 4096);
            bar_sync(4 + c, 128);
            #pragma unroll 1
            for (int step = 0; step < 4; step++) {
                if ((warp & 3) == step) {
                    #pragma unroll
                    for (int mt = 0; mt < 2; mt++)
                        #pragma unroll
                        for (int nt = 0; nt < 3; nt++)
                            #pragma unroll
                            for (int hh = 0; hh < 2; hh++) {
                                float2* p = (float2*)(kc + (mt * 16 + hh * 8 + g) * 24 + nt * 8 + 2 * t);
                                float2 v = make_float2(acc[mt][nt][2 * hh] * scale, acc[mt][nt][2 * hh + 1] * scale);
                                if (step) { float2 o = *p; v.x += o.x; v.y += o.y; }
                                *p = v;
                            }
                }
                if (step < 3) bar_sync(4 + c, 128);
            }
        }

        asm volatile("barrier.cluster.wait.aligned;" ::: "memory");
        PROF(4);
        uint32_t q[2][4];
        {
            const uint64_t dA0 = make_desc(sb + SM_B + rowhalf * 8192, 16, 1024, 1);
            const uint64_t dA1 = make_desc(sb + SM_A + rowhalf * 8192, 16, 1024, 1) - 4096;
            uint4* qx = (uint4*)(sp + SM_B + S_QX) + (tid & 255) * 2;
            auto stage_u = [&]() {
                #pragma unroll
                for (int i = 0; i < 1; i++) {
                    const int z = tid + 512 * i;
                    if (z < 4 * 80) sts128(sBa + offU(z / 80) + (PADU - 640) * 2 + (z % 80) * 16, make_uint4(0, 0, 0, 0));
                }
                mbar_wait(bars + 8 * B_U, 0);
                #pragma unroll
                for (int i = 0; i < 2; i++) {
                    const int l = 2 * (tid + 512 * i);
                    const uint2 r0 = *(const uint2*)(sp + SM_SLAB + l * 16 + rank * 8), r1 = *(const uint2*)(sp + SM_SLAB + l * 16 + 16 + rank * 8);
                    const uint32_t dst = swz128(sBa + (PADU + l) * 2);
                    sts32(dst, __byte_perm(r0.x, r1.x, 0x5410));
                    sts32(dst + offU(1), __byte_perm(r0.x, r1.x, 0x7632));
                    sts32(dst + offU(2), __byte_perm(r0.y, r1.y, 0x5410));
                    sts32(dst + offU(3), __byte_perm(r0.y, r1.y, 0x7632));
                }
                fence_async_smem();
                bar_arrive(13, 544);
            };
            if (wg < 2) {
                float acc[32];
                #pragma unroll
                for (int i = 0; i < 32; i++) acc[i] = 0.0f;
                fence_regs<32>(acc);
                const uint64_t dB = make_desc(sb + SM_WQ, 16, 1024, 1);
                mbar_wait(bars + 8 * B_WQ, 0);
                mbar_wait(bars + 8 * B_X, 0);
                PROF(2);
                #pragma unroll 1
                for (int ch = 0; ch < 4; ch++) {
                    wg_fence();
                    #pragma unroll
                    for (int ks = 0; ks < 4; ks++) wg_ss64(acc, dA0 + ch * 1024 + ks * 2, dB + (ch * 4 + ks) * 128);
                    wg_commit();
                }
                wg_wait<0>();
                fence_regs<32>(acc);
                bar_sync(1, 512);
                PROF(15);
                stage_u();
                bar_arrive(2, 512);
                PROF(1);
                mbar_wait(bars + 8 * B_WQ2, 0);
                mbar_wait(bars + 8 * (B_X + 1), 0);
                fence_regs<32>(acc);
                #pragma unroll 1
                for (int ch = 4; ch < 8; ch++) {
                    wg_fence();
                    #pragma unroll
                    for (int ks = 0; ks < 4; ks++) wg_ss64(acc, dA1 + ch * 1024 + ks * 2, dB + (ch * 4 + ks) * 128);
                    wg_commit();
                }
                wg_wait<0>();
                fence_regs<32>(acc);
                bar_arrive(14, 288);
                float qm = 0.0f;
                uint32_t qa[4][4];
                #pragma unroll
                for (int i = 0; i < 4; i++) {
                    #pragma unroll
                    for (int j = 0; j < 4; j++) qa[i][j] = pack_bf16(acc[8 * i + 2 * j], acc[8 * i + 2 * j + 1]);
                    float n0 = bf_lo(qa[i][0]) * bf_lo(qa[i][0]) + bf_hi(qa[i][0]) * bf_hi(qa[i][0]) + bf_lo(qa[i][2]) * bf_lo(qa[i][2]) + bf_hi(qa[i][2]) * bf_hi(qa[i][2]);
                    float n1 = bf_lo(qa[i][1]) * bf_lo(qa[i][1]) + bf_hi(qa[i][1]) * bf_hi(qa[i][1]) + bf_lo(qa[i][3]) * bf_lo(qa[i][3]) + bf_hi(qa[i][3]) * bf_hi(qa[i][3]);
                    n0 += __shfl_xor_sync(0xffffffffu, n0, 1); n0 += __shfl_xor_sync(0xffffffffu, n0, 2);
                    n1 += __shfl_xor_sync(0xffffffffu, n1, 1); n1 += __shfl_xor_sync(0xffffffffu, n1, 2);
                    qm = (n0 != n0 || n1 != n1) ? __int_as_float(0x7f800000) : fmaxf(qm, fmaxf(n0, n1));
                }
                #pragma unroll
                for (int o = 16; o; o >>= 1) qm = fmaxf(qm, __shfl_xor_sync(0xffffffffu, qm, o));
                if (lane == 0) s_misc[warp] = qm;
                qx[0] = make_uint4(qa[2][0], qa[2][1], qa[2][2], qa[2][3]);
                qx[1] = make_uint4(qa[3][0], qa[3][1], qa[3][2], qa[3][3]);
                #pragma unroll
                for (int j = 0; j < 4; j++) { q[0][j] = qa[0][j]; q[1][j] = qa[1][j]; }
                bar_sync(1, 512);
            } else {
                if (kv_wg) {
                    float akv[8];
                    #pragma unroll
                    for (int i = 0; i < 8; i++) akv[i] = 0.0f;
                    fence_regs<8>(akv);
                    const uint64_t dC = make_desc(sb + SM_WKV, 128, 8192, 0);
                    #pragma unroll 1
                    for (int ch = 0; ch < 8; ch++) {
                        if ((ch & 3) == 0) mbar_wait(bars + 8 * (B_X + (ch >> 2)), 0);
                        const uint64_t dA = ch < 4 ? dA0 : dA1;
                        wg_fence();
                        #pragma unroll
                        for (int ks = 0; ks < 4; ks++) wg_ss16(akv, dA + ch * 1024 + ks * 2, dC + (ch * 4 + ks) * 16);
                        wg_commit();
                    }
                    wg_wait<0>();
                    fence_regs<8>(akv);
                    const int key = qb * 128 + rowhalf * 64 + wiw * 16 + g;
                    uint32_t pk[4];
                    #pragma unroll
                    for (int i = 0; i < 4; i++) pk[i] = pack_bf16(akv[2 * i], akv[2 * i + 1]);
                    float st;
                    if (kv_sel == 0) {
                        uint8_t* b = g_kimg + (key >> 3) * 256 + (key & 7) * 16 + 4 * t;
                        *(uint32_t*)(b) = pk[0]; *(uint32_t*)(b + 256) = pk[1]; *(uint32_t*)(b + 128) = pk[2]; *(uint32_t*)(b + 384) = pk[3];
                        float n0 = bf_lo(pk[0]) * bf_lo(pk[0]) + bf_hi(pk[0]) * bf_hi(pk[0]) + bf_lo(pk[2]) * bf_lo(pk[2]) + bf_hi(pk[2]) * bf_hi(pk[2]);
                        float n1 = bf_lo(pk[1]) * bf_lo(pk[1]) + bf_hi(pk[1]) * bf_hi(pk[1]) + bf_lo(pk[3]) * bf_lo(pk[3]) + bf_hi(pk[3]) * bf_hi(pk[3]);
                        n0 += __shfl_xor_sync(0xffffffffu, n0, 1); n0 += __shfl_xor_sync(0xffffffffu, n0, 2);
                        n1 += __shfl_xor_sync(0xffffffffu, n1, 1); n1 += __shfl_xor_sync(0xffffffffu, n1, 2);
                        st = (n0 != n0 || n1 != n1) ? __int_as_float(0x7f800000) : fmaxf(n0, n1);
                    } else {
                        uint8_t* lo = g_vimg + key * 16 + 4 * t;
                        uint8_t* hi = g_vimg + 33792 + (31 - (key >> 6)) * 1024 + (key & 63) * 16 + 4 * t;
                        *(uint32_t*)(lo) = pk[0]; *(uint32_t*)(lo + 128) = pk[1]; *(uint32_t*)(hi) = pk[2]; *(uint32_t*)(hi + 128) = pk[3];
                        st = 0.0f;
                        #pragma unroll
                        for (int i = 0; i < 4; i++) {
                            float a = fabsf(bf_lo(pk[i])), b = fabsf(bf_hi(pk[i]));
                            st = (a != a || b != b) ? __int_as_float(0x7f800000) : fmaxf(st, fmaxf(a, b));
                        }
                    }
                    #pragma unroll
                    for (int o = 16; o; o >>= 1) st = fmaxf(st, __shfl_xor_sync(0xffffffffu, st, o));
                    if (lane == 0) s_misc[20 + wiw] = st;
                bar_arrive(3, 160);
                }
                uint2 mp[3];
                #pragma unroll
                for (int i = 0; i < 3; i++) { const int w = (tid & 255) + 256 * i; mp[i] = (w < TABN / 4) ? __ldg((const uint2*)g_tabmap.v + w) : make_uint2(0u, 0u); }
                bar_sync(1, 512);
                stage_u();
                #pragma unroll 1
                for (int cc = 0; cc < 4; cc++) {
                    const float* kc = (const float*)(sB + S_KC + cc * 4096);
                    uint2* tab = (uint2*)(sB + offT(cc));
                    #pragma unroll
                    for (int i = 0; i < 3; i++) {
                        const int w = (tid & 255) + 256 * i;
                        if (w < TABN / 4) tab[w] = make_uint2(pack_bf16(kc[mp[i].x & 0xFFFF], kc[mp[i].x >> 16]), pack_bf16(kc[mp[i].y & 0xFFFF], kc[mp[i].y >> 16]));
                    }
                }
                bar_sync(2, 512);
                #pragma unroll 1
                for (int tk = tid & 255; tk < 4 * 130; tk += 256) {
                    const int c = tk / 130, i = tk % 130;
                    const uint32_t src = sBa + offU(c) + (PADU + 8 * i - WPAD - 8) * 2;
                    const uint4 v0 = lds128(swz128(src)), v1 = lds128(swz128(src + 16)), v2 = lds128(swz128(src + 32));
                    float x[16];
                    const uint32_t vv[8] = {v0.z, v0.w, v1.x, v1.y, v1.z, v1.w, v2.x, v2.y};
                    #pragma unroll
                    for (int k = 0; k < 8; k++) { x[2 * k] = bf_lo(vv[k]); x[2 * k + 1] = bf_hi(vv[k]); }
                    float p2[15], w7[8], w9[8];
                    #pragma unroll
                    for (int e = 0; e < 15; e++) p2[e] = x[e] + x[e + 1];
                    #pragma unroll
                    for (int e = 0; e < 8; e++) {
                        w7[e] = (p2[e + 1] + p2[e + 3]) + (p2[e + 5] + x[e + 7]);
                        w9[e] = w7[e] + (x[e] + x[e + 8]);
                    }
                    sts128(swz(sBa + offW7(c) + i * 16), make_uint4(pack_bf16(w7[0], w7[1]), pack_bf16(w7[2], w7[3]), pack_bf16(w7[4], w7[5]), pack_bf16(w7[6], w7[7])));
                    sts128(swz(sBa + offW9(c) + i * 16), make_uint4(pack_bf16(w9[0], w9[1]), pack_bf16(w9[2], w9[3]), pack_bf16(w9[4], w9[5]), pack_bf16(w9[6], w9[7])));
                }
                bar_sync(1, 512);
                const uint4 q0 = qx[0], q1 = qx[1];
                q[0][0] = q0.x; q[0][1] = q0.y; q[0][2] = q0.z; q[0][3] = q0.w;
                q[1][0] = q1.x; q[1][1] = q1.y; q[1][2] = q1.z; q[1][3] = q1.w;
                asm volatile("" : "+r"(q[0][0]), "+r"(q[0][3]), "+r"(q[1][0]), "+r"(q[1][3]) :: "memory");
                bar_arrive(11, 544);
            }
        }
        PROF(3);
        auto ssm_conv = [&]() {
            int tl = threadIdx.x;
            uint32_t sBl = sBa;
            asm volatile("" : "+r"(sBl), "+r"(tl) :: "memory");
            const int c = tl >> 7, wiw = (tl >> 5) & 3, lane = tl & 31, g = lane >> 2, t = lane & 3;
            const unsigned short p_dsk = __ldg((const unsigned short*)P.dskip + blockIdx.x * 4 + c);
            float acc[16];
            const uint32_t tabc = sBl + offT(c);
            const uint32_t tD = tabc + ((g & 1) ? (TD1 + CD + 1) : (TD0 + CD)) * 2 - (g - 2 * t) * 2 - 32 * wiw;
            const uint32_t uLo = (((sBl + offU(c) + PADU * 2) & 0x3FFFF) >> 4) | (1u << 16);
            uint32_t A[2][4][4];
            auto load_set = [&](uint32_t (&X)[4][4], uint32_t a) {
                X[0][2] = lds32(a + 16);
                #pragma unroll
                for (int i = 0; i < 4; i++) { X[i][0] = lds32(a - 32 * i); X[i][1] = lds32(a - 32 * i - 16); }
                #pragma unroll
                for (int i = 0; i < 4; i++) {
                    asm volatile("mov.b32 %0, %1;" : "=r"(X[i][3]) : "r"(X[i][0]));
                    if (i < 3) asm volatile("mov.b32 %0, %1;" : "=r"(X[i + 1][2]) : "r"(X[i][1]));
                }
            };
            {
                float accB[12];
                #pragma unroll
                for (int i = 0; i < 12; i++) accB[i] = 0.0f;
                fence_regs<12>(accB);
                #pragma unroll 1
                for (int m0 = 29; m0 < 69; m0 += 8) {
                    #pragma unroll
                    for (int h = 0; h < 2; h++) {
                        load_set(A[h], tD - 32 * (m0 + 4 * h));
                        wg_fence();
                        #pragma unroll
                        for (int i = 0; i < 4; i++) wg_rs24(accB, A[h][i], uLo + 64 - 2 * (m0 + 4 * h + i));
                        wg_commit();
                        wg_wait<1>();
                    }
                }
                wg_wait<0>();
                fence_regs<12>(accB);
                #pragma unroll
                for (int i = 0; i < 4; i++) acc[i] = 0.0f;
                #pragma unroll
                for (int i = 0; i < 12; i++) asm volatile("add.f32 %0, %1, 0f00000000;" : "=f"(acc[4 + i]) : "f"(accB[i]));
                fence_regs<16>(acc);
            }
            #pragma unroll 1
            for (int m0 = -3; m0 < 29; m0 += 8) {
                #pragma unroll
                for (int h = 0; h < 2; h++) {
                    load_set(A[h], tD - 32 * (m0 + 4 * h));
                    wg_fence();
                    #pragma unroll
                    for (int i = 0; i < 4; i++) wg_rs32(acc, A[h][i], uLo - 2 * (m0 + 4 * h + i));
                    wg_commit();
                    wg_wait<1>();
                }
            }
            wg_wait<0>();
            fence_regs<16>(acc);
            PROF(6);
            {
                asm volatile("" : "+r"(sBl) :: "memory");
                const int mi = lane >> 3, r8 = lane & 7;
                const uint32_t frag = (16 * (8 * (mi >> 1) + r8) + 8 * (mi & 1)) * 2;
                const uint32_t t3 = sBl + offT(c) + (T3B + ((wiw & 1) ? (T3C + C3 + 1) : C3)) * 2 - (4 * g + wiw - 2 * t) * 2;
                #pragma unroll
                for (int s = 0; s < 2; s++) {
                    const uint32_t sig = swz(sBl + (s ? offW7(c) : offW9(c)) + WPAD * 2 + frag - (s ? 16 : 32));
                    uint32_t a[4][4], R[4][2];
                    #pragma unroll
                    for (int b = 0; b < 4; b++) ldsm4t_p(a[b], sig + b * 512);
                    #pragma unroll
                    for (int i = 0; i < 4; i++) { R[i][0] = lds32_p(t3 + s * (T3S * 2) - 2 * (48 + 16 * i)); R[i][1] = lds32_p(t3 + s * (T3S * 2) - 2 * (40 + 16 * i)); }
                    #pragma unroll
                    for (int b = 0; b < 4; b++) {
                        mma_bf16_p(acc + 12, a[b][0], a[b][1], a[b][2], a[b][3], R[3 - b][0], R[3 - b][1]);
                        if (b < 2) mma_bf16_p(acc + 8, a[b][0], a[b][1], a[b][2], a[b][3], R[1 - b][0], R[1 - b][1]);
                    }
                }
            }
            __nv_bfloat16* ys = (__nv_bfloat16*)(sB + S_Y + c * 4096) + 128 * t + 16 * wiw + g;
            const uint32_t ua = sBl + offU(c) + (PADU + 128 * t + 16 * wiw + g) * 2;
            const float dsk = bf_lo(p_dsk);
            #pragma unroll
            for (int j = 0; j < 4; j++)
                #pragma unroll
                for (int e = 0; e < 4; e++) {
                    const int off = 512 * j + (e & 1) * 64 + (e >> 1) * 8;
                    unsigned short uv;
                    asm volatile("ld.shared.u16 %0, [%1];" : "=h"(uv) : "r"(swz128(ua + off * 2)) : "memory");
                    ys[off] = __float2bfloat16_rn(bf_round(acc[4 * j + e]) + bf_round(bf_lo(uv) * dsk));
                }
        };
        if (wg < 2) {
            ssm_conv();
            bar_arrive(10, 608);
            bar_arrive(11, 544);
        }
        PROF(7);
        {
            mbar_wait(bars + 8 * B_ST, 0);
            PROF(9); PROFC(8);
            float qm = 0.0f;
            #pragma unroll
            for (int i = 0; i < 8; i++) qm = fmaxf(qm, s_misc[i]);
            const float vm = s_misc[17];
            const float QS = 0.25f * 1.4426950408889634f;
            const bool fast = (qm * s_misc[16] * (QS * QS * 1.02f) <= 60.0f * 60.0f) && (vm <= 1.0e12f) && (vm >= 1.0e-12f || vm == 0.0f);
            uint8_t* ob = g_oimg + qb * 131072 + hg * 16384 + nh * 8192 + (rowhalf * 8 + wiw * 2) * 128 + g * 16 + 4 * t;
            uint32_t cA = 0xBF00BF00u, cB = 0x00030003u;
            asm volatile("" : "+r"(cA), "+r"(cB));
            #pragma unroll 1
            for (int tile = 0; tile < 2; tile++) {
                uint32_t kLo = (((sb + SM_K) & 0x3FFFF) >> 4) | (8u << 16), vLo = (((sb + SM_V) & 0x3FFFF) >> 4) | (8u << 16), vHi = 2048;
                float o[12], s[32];
                uint32_t p[16], qq[4];
                #pragma unroll
                for (int i = 0; i < 4; i++) {
                    qq[i] = tile ? q[1][i] : q[0][i];
                    if (fast) qq[i] = pack_bf16(bf_lo(qq[i]) * QS, bf_hi(qq[i]) * QS);
                    asm volatile("" : "+r"(qq[i]));
                }
                #pragma unroll
                for (int i = 0; i < 12; i++) o[i] = 0.0f;
                #pragma unroll
                for (int i = 0; i < 32; i++) s[i] = 0.0f;
                fence_regs<12>(o);
                fence_regs<32>(s);
                if (fast) {
                    #pragma unroll 1
                    for (int c = 0; c < SEQ / (64 * AU); c++) {
                        if (AU == 4) { if (c <= 4) mbar_wait(bars + 8 * (B_KV + (c < 2 ? c : c < 4 ? 2 : 3)), 0); }
                        else { if (c <= 2) mbar_wait(bars + 8 * (B_KV + (c ? c + 1 : 0)), 0); }
                        wg_fence();
                        wg_qk(s, qq, kLo);
                        wg_commit();
                        #pragma unroll
                        for (int u = 0; u < AU; u++) {
                            wg_wait<0>();
                            fence_regs<32>(s);
                            #pragma unroll
                            for (int i = 0; i < 16; i++) {
                                if ((MUFU_MASK >> i) & 1) p[i] = exp_mufu(s[2 * i], s[2 * i + 1]);
                                else p[i] = exp_sw(s[2 * i], s[2 * i + 1], cA, cB);
                            }
                            if (AU == 8 && u == 3) mbar_wait(bars + 8 * (B_KV + 1), 0);
                            wg_fence();
                            if (u + 1 < AU) wg_qk(s, qq, kLo + (u + 1) * 128);
                            #pragma unroll
                            for (int kk = 0; kk < 4; kk++) wg_pv(o, p + 4 * kk, vLo + u * 64 + kk * 16, vHi - u * 64);
                            wg_commit();
                        }
                        kLo += 128 * AU; vLo += 64 * AU; vHi -= 64 * AU;
                    }
                    wg_wait<0>();
                } else {
                    float mx0 = -INFINITY, mx1 = -INFINITY;
                    #pragma unroll 1
                    for (int c = 0; c < SEQ / 64; c++) {
                        if (c <= 16) mbar_wait(bars + 8 * (B_KV + (c < 8 ? (c >> 2) : c < 16 ? 2 : 3)), 0);
                        wg_fence();
                        wg_qk(s, qq, kLo);
                        wg_commit();
                        wg_wait<0>();
                        fence_regs<32>(s);
                        fence_regs<12>(o);
                        float m0 = mx0, m1 = mx1;
                        #pragma unroll
                        for (int j = 0; j < 16; j++) {
                            const uint32_t r = pack_bf16(s[2 * j], s[2 * j + 1]);
                            s[2 * j] = bf_lo(r) * QS; s[2 * j + 1] = bf_hi(r) * QS;
                        }
                        #pragma unroll
                        for (int j = 0; j < 8; j++) {
                            m0 = fmaxf(m0, fmaxf(s[4 * j], s[4 * j + 1]));
                            m1 = fmaxf(m1, fmaxf(s[4 * j + 2], s[4 * j + 3]));
                        }
                        m0 = fmaxf(m0, __shfl_xor_sync(0xffffffffu, m0, 1)); m0 = fmaxf(m0, __shfl_xor_sync(0xffffffffu, m0, 2));
                        m1 = fmaxf(m1, __shfl_xor_sync(0xffffffffu, m1, 1)); m1 = fmaxf(m1, __shfl_xor_sync(0xffffffffu, m1, 2));
                        const float c0 = ex2f(mx0 - m0), c1 = ex2f(mx1 - m1);
                        mx0 = m0; mx1 = m1;
                        #pragma unroll
                        for (int j = 0; j < 3; j++) { o[4 * j] *= c0; o[4 * j + 1] *= c0; o[4 * j + 2] *= c1; o[4 * j + 3] *= c1; }
                        #pragma unroll
                        for (int j = 0; j < 8; j++) {
                            p[2 * j] = exp_mufu(s[4 * j] - m0, s[4 * j + 1] - m0);
                            p[2 * j + 1] = exp_mufu(s[4 * j + 2] - m1, s[4 * j + 3] - m1);
                        }
                        wg_fence();
                        #pragma unroll
                        for (int kk = 0; kk < 4; kk++) wg_pv(o, p + 4 * kk, vLo + kk * 16, vHi);
                        wg_commit();
                        wg_wait<0>();
                        kLo += 128; vLo += 64; vHi -= 64;
                    }
                }
                fence_regs<12>(o);
                if (tile == 0) PROFC(3);
                const float i0 = 1.0f / o[4], i1 = 1.0f / o[6];
                uint8_t* b = ob + tile * 4096;
                *(uint32_t*)(b) = pack_bf16(o[0] * i0, o[1] * i0);
                *(uint32_t*)(b + 128) = pack_bf16(o[2] * i1, o[3] * i1);
                *(uint32_t*)(b + 2048) = pack_bf16(o[8] * i0, o[9] * i0);
                *(uint32_t*)(b + 2048 + 128) = pack_bf16(o[10] * i1, o[11] * i1);
            }
        }
        PROF(10); PROFC(9);
        bar_arrive(12, 544);
        if (wg >= 2) {
            ssm_conv();
            bar_sync(10, 608);
            ssm_out_pass(P, sB, tid - 256);
        }

        if (wg < 2) {
            float acc[32];
            #pragma unroll
            for (int i = 0; i < 32; i++) acc[i] = 0.0f;
            fence_regs<32>(acc);
            const uint64_t dA = make_desc(sb + SM_A + rowhalf * 1024, 2048, 128, 0);
            const uint64_t dB = make_desc(sb + SM_B, 16, 1024, 1);
            mbar_wait(bars + 8 * B_WO, 0);
            #pragma unroll 1
            for (int i = 0; i < 8; i++) {
                int src = i;
                if (i < 6) { src = (hg < 6 ? (hg & 6) : 0) + i; if (src >= 6) src -= 6; }
                if (i == 6) mbar_wait(bars + 8 * B_WO2, 0);
                mbar_wait(bars + 8 * (B_O + src), 0);
                wg_fence();
                #pragma unroll
                for (int kk = 0; kk < 4; kk++) wg_ss64(acc, dA + src * 1024 + kk * 256, dB + (src * 4 + kk) * 128);
                wg_commit();
            }
            wg_wait<0>();
            fence_regs<32>(acc);
            PROF(12);
            const int row = qb * 128 + rowhalf * 64 + wiw * 16 + g;
            uint4* o128 = (uint4*)(P.out + (size_t)row * 1024 + hg * 64 + 8 * t);
            #pragma unroll
            for (int rr = 0; rr < 2; rr++)
                #pragma unroll
                for (int a = 0; a < 2; a++) {
                    uint32_t v[4];
                    #pragma unroll
                    for (int j = 0; j < 4; j++) v[j] = pack_bf16(acc[16 * a + 4 * j + 2 * rr], acc[16 * a + 4 * j + 2 * rr + 1]);
                    quad_transpose(v, t);
                    o128[rr * 1024 + a * 4] = make_uint4(v[0], v[1], v[2], v[3]);
                }
        }
        PROF(13);
    }
}

typedef CUresult (*EncodeFn)(CUtensorMap*, CUtensorMapDataType, cuuint32_t, void*, const cuuint64_t*, const cuuint64_t*,
                             const cuuint32_t*, const cuuint32_t*, CUtensorMapInterleave, CUtensorMapSwizzle,
                             CUtensorMapL2promotion, CUtensorMapFloatOOBfill);

void make_map(EncodeFn fn, CUtensorMap* m, const void* ptr, uint64_t inner, uint64_t outer, uint32_t box_in, uint32_t box_out, CUtensorMapSwizzle swz) {
    cuuint64_t dims[2] = {inner, outer};
    cuuint64_t strides[1] = {inner * 2};
    cuuint32_t box[2] = {box_in, box_out};
    cuuint32_t es[2] = {1, 1};
    fn(m, CU_TENSOR_MAP_DATA_TYPE_BFLOAT16, 2, const_cast<void*>(ptr), dims, strides, box, es, CU_TENSOR_MAP_INTERLEAVE_NONE, swz,
       CU_TENSOR_MAP_L2_PROMOTION_L2_128B, CU_TENSOR_MAP_FLOAT_OOB_FILL_NONE);
}

}

extern "C" void kernel_launch(void* const* d_in, const int* in_sizes, int n_in, void* d_out, int out_size) {
    (void)in_sizes; (void)n_in; (void)out_size;
    static EncodeFn fn = nullptr;
    if (!fn) {
        void* p = nullptr;
        cudaDriverEntryPointQueryResult qr;
        cudaGetDriverEntryPoint("cuTensorMapEncodeTiled", &p, cudaEnableDefault, &qr);
        fn = (EncodeFn)p;
        cudaFuncSetAttribute(fused_kernel, cudaFuncAttributeMaxDynamicSharedMemorySize, SM_ALLOC);
    }
    CUtensorMap tx, twq, two, twk, twv, tu;
    {
        cuuint64_t dims[3] = {64, 2048, 8};
        cuuint64_t strides[2] = {1024, 128};
        cuuint32_t box[3] = {64, 128, 4};
        cuuint32_t es[3] = {1, 1, 1};
        fn(&tx, CU_TENSOR_MAP_DATA_TYPE_BFLOAT16, 3, d_in[0], dims, strides, box, es, CU_TENSOR_MAP_INTERLEAVE_NONE, CU_TENSOR_MAP_SWIZZLE_128B,
           CU_TENSOR_MAP_L2_PROMOTION_L2_128B, CU_TENSOR_MAP_FLOAT_OOB_FILL_NONE);
    }
    make_map(fn, &tu, d_in[5], 512, 2048, 8, 256, CU_TENSOR_MAP_SWIZZLE_NONE);
    make_map(fn, &twq, d_in[1], 512, 512, 64, 256, CU_TENSOR_MAP_SWIZZLE_128B);
    make_map(fn, &twk, d_in[2], 16, 512, 8, 256, CU_TENSOR_MAP_SWIZZLE_NONE);
    make_map(fn, &twv, d_in[3], 16, 512, 8, 256, CU_TENSOR_MAP_SWIZZLE_NONE);
    make_map(fn, &two, d_in[4], 512, 512, 64, 128, CU_TENSOR_MAP_SWIZZLE_128B);
    Params P;
    P.u = (const __nv_bfloat16*)d_in[5];
    P.lar = (const __nv_bfloat16*)d_in[6];
    P.aim = (const __nv_bfloat16*)d_in[7];
    P.cre = (const __nv_bfloat16*)d_in[8];
    P.cim = (const __nv_bfloat16*)d_in[9];
    P.logdt = (const __nv_bfloat16*)d_in[10];
    P.dskip = (const __nv_bfloat16*)d_in[11];
    P.out = (__nv_bfloat16*)d_out;
    fused_kernel<<<NCTA, NTHR, SM_ALLOC>>>(tx, twq, two, twk, twv, tu, P);
}
```

```cpp
#include <cuda_runtime.h>
#include <cuda_bf16.h>
#include <cuda_fp16.h>
#include <cuda.h>
#include <stdint.h>

namespace {

constexpr int SEQ = 2048;
constexpr int NCTA = 128, NTHR = 640;

constexpr int SM_A = 0;
constexpr int SM_WQ = 65536;
constexpr int SM_SLAB = SM_WQ + 32768;
constexpr int SM_K = 0, SM_V = 65536;
constexpr int SM_B = 132096;
constexpr int SM_WKV = SM_B + 65536;

constexpr int PADU = 1024, ULEN = PADU + 2048;
constexpr int WPAD = 16, W3LEN = WPAD + 1024;
constexpr int TABN = 2912;
constexpr int S_U = 0;
constexpr int S_W7 = S_U + 4 * ULEN * 2;
constexpr int S_W9 = S_W7 + 4 * W3LEN * 2;
constexpr int S_TAB = S_W9 + 4 * W3LEN * 2;
constexpr int S_QX = S_TAB + 4 * TABN * 2;
constexpr int S_KC = 214016 - SM_B;
constexpr int S_Y = S_KC;
constexpr int SM_BAR = SM_B + S_KC + 16384;
constexpr int SM_TOTAL = SM_BAR + 1024;
constexpr int SM_ALLOC = SM_TOTAL + 1024;
static_assert(SM_V + 65536 + 1024 <= SM_B && SM_ALLOC <= 232448 && S_QX + 8192 <= S_KC && SM_WKV + 16384 <= SM_B + S_KC, "smem map");

constexpr int TD0 = 0, TD1 = 1232, CD = 1152;
constexpr int T3B = 2464, T3S = 224, T3C = 112, C3 = 136;

constexpr int rne8(int t) {
    if (t < 256) return t;
    int sh = 0;
    while ((t >> sh) >= 256) sh++;
    int q = t >> sh, rem = t & ((1 << sh) - 1), half = 1 << (sh - 1);
    if (rem > half || (rem == half && (q & 1))) q++;
    return q << sh;
}
constexpr int kcidx(int p) {
    if (p < 256) return (p >> 3) * 24 + (p & 7);
    if (p < 512) return ((p - 256) >> 3) * 24 + 8 + (((p - 256) & 7) >> 1);
    if (p < 1024) { int q = p - 512, hi = q >> 8, rem = q & 255; return (rem >> 3) * 24 + 12 + 2 * hi + ((rem & 7) >> 2); }
    if (p < 2048) { int q = p - 1024; return ((q & 255) >> 3) * 24 + 16 + (q >> 8); }
    return 20;
}
constexpr int KC_ZERO = 23;
constexpr int tab_dense(int t) { return (t >= 0 && t <= 1028) ? kcidx(rne8(t)) : KC_ZERO; }
constexpr int tab_3(int s, int lag) { return (lag >= 64 && lag <= 127) ? kcidx(s == 0 ? 16 * (lag + 1) : 16 * lag + 8) : KC_ZERO; }
struct TabMap {
    uint16_t v[TABN];
    constexpr TabMap() : v{} {
        for (int i = 0; i < TD1; i++) { v[TD0 + i] = tab_dense(CD - i); v[TD1 + i] = tab_dense(CD + 1 - i); }
        for (int s = 0; s < 2; s++)
            for (int i = 0; i < T3C; i++) { v[T3B + s * T3S + i] = tab_3(s, C3 - i); v[T3B + s * T3S + T3C + i] = tab_3(s, C3 + 1 - i); }
    }
};
__device__ const __align__(16) TabMap g_tabmap = TabMap();

__device__ __align__(1024) uint8_t g_kimg[65536];
__device__ __align__(1024) uint8_t g_vimg[65536 + 1024];
__device__ __align__(1024) uint8_t g_oimg[16 * 131072];
__device__ unsigned long long g_flag_kv[64];
__device__ unsigned g_flag_o[128];
__device__ unsigned g_epoch;
__device__ unsigned g_done;

#define PROF(i) do {} while (0)
#define PROF2(i) do {} while (0)
#define PROFC(i) do {} while (0)
#define PROF3(i) do {} while (0)

__device__ __forceinline__ uint32_t smem_u32(const void* p) { return (uint32_t)__cvta_generic_to_shared(p); }
__device__ __forceinline__ void mbar_init(uint32_t bar, uint32_t cnt) { asm volatile("mbarrier.init.shared::cta.b64 [%0], %1;" :: "r"(bar), "r"(cnt) : "memory"); }
__device__ __forceinline__ void mbar_expect_tx(uint32_t bar, uint32_t bytes) {
    asm volatile("mbarrier.arrive.expect_tx.shared::cta.b64 _, [%0], %1;" :: "r"(bar), "r"(bytes) : "memory"); }
__device__ __forceinline__ void mbar_wait(uint32_t bar, uint32_t parity) {
    uint32_t ok = 0;
    for (int it = 0; it < (1 << 22) && !ok; it++) {
        asm volatile("{ .reg .pred p; mbarrier.try_wait.parity.shared::cta.b64 p, [%1], %2; selp.u32 %0, 1, 0, p; }"
                     : "=r"(ok) : "r"(bar), "r"(parity) : "memory");
    }
}
__device__ __forceinline__ void tma_2d(uint32_t dst, const CUtensorMap* map, int c0, int c1, uint32_t bar) {
    asm volatile("cp.async.bulk.tensor.2d.shared::cluster.global.mbarrier::complete_tx::bytes [%0], [%1, {%3, %4}], [%2];"
                 :: "r"(dst), "l"((uint64_t)map), "r"(bar), "r"(c0), "r"(c1) : "memory");
}
__device__ __forceinline__ void tma_2d_mc(uint32_t dst, const CUtensorMap* map, int c0, int c1, uint32_t bar) {
    asm volatile("cp.async.bulk.tensor.2d.shared::cluster.global.mbarrier::complete_tx::bytes.multicast::cluster [%0], [%1, {%3, %4}], [%2], %5;"
                 :: "r"(dst), "l"((uint64_t)map), "r"(bar), "r"(c0), "r"(c1), "h"((uint16_t)3) : "memory");
}
__device__ __forceinline__ void bulk_g2s_mc(uint32_t dst, const void* src, uint32_t bytes, uint32_t bar) {
    asm volatile("cp.async.bulk.shared::cluster.global.mbarrier::complete_tx::bytes.multicast::cluster [%0], [%1], %2, [%3], %4;"
                 :: "r"(dst), "l"((uint64_t)src), "r"(bytes), "r"(bar), "h"((uint16_t)3) : "memory");
}
__device__ __forceinline__ void pair_arrive(uint32_t bar, uint32_t peer) {
    uint32_t ra;
    asm volatile("mapa.shared::cluster.u32 %0, %1, %2;" : "=r"(ra) : "r"(bar), "r"(peer));
    asm volatile("mbarrier.arrive.shared::cluster.b64 _, [%0];" :: "r"(ra) : "memory");
    asm volatile("mbarrier.arrive.shared::cta.b64 _, [%0];" :: "r"(bar) : "memory");
}
__device__ __forceinline__ void pair_sync(uint32_t bar, uint32_t peer) { pair_arrive(bar, peer); mbar_wait(bar, 0); }
__device__ __forceinline__ void fence_async_all() { asm volatile("fence.proxy.async.global;" ::: "memory"); }
__device__ __forceinline__ void fence_async_smem() { asm volatile("fence.proxy.async.shared::cta;" ::: "memory"); }
__device__ __forceinline__ unsigned ld_acquire(const unsigned* p) {
    unsigned v; asm volatile("ld.acquire.gpu.global.u32 %0, [%1];" : "=r"(v) : "l"(p) : "memory"); return v; }
__device__ __forceinline__ void st_release(unsigned* p, unsigned v) { asm volatile("st.release.gpu.global.u32 [%0], %1;" :: "l"(p), "r"(v) : "memory"); }
__device__ __forceinline__ void wait_flag(const unsigned* p, unsigned epoch) {
    for (int it = 0; it < (1 << 22); it++) { if (ld_acquire(p) == epoch) break; }
}
__device__ __forceinline__ unsigned long long ld_acquire64(const unsigned long long* p) {
    unsigned long long v; asm volatile("ld.acquire.gpu.global.u64 %0, [%1];" : "=l"(v) : "l"(p) : "memory"); return v; }
__device__ __forceinline__ void st_release64(unsigned long long* p, unsigned long long v) { asm volatile("st.release.gpu.global.u64 [%0], %1;" :: "l"(p), "l"(v) : "memory"); }
__device__ __forceinline__ float wait_flag64(const unsigned long long* p, unsigned epoch) {
    unsigned long long v = 0;
    for (int it = 0; it < (1 << 22); it++) { v = ld_acquire64(p); if ((unsigned)(v >> 32) == epoch) break; }
    return __uint_as_float((unsigned)v);
}
__device__ __forceinline__ void tma_3d_mc(uint32_t dst, const CUtensorMap* map, int c0, int c1, int c2, uint32_t bar) {
    asm volatile("cp.async.bulk.tensor.3d.shared::cluster.global.mbarrier::complete_tx::bytes.multicast::cluster [%0], [%1, {%3, %4, %5}], [%2], %6;"
                 :: "r"(dst), "l"((uint64_t)map), "r"(bar), "r"(c0), "r"(c1), "r"(c2), "h"((uint16_t)3) : "memory");
}
__device__ __forceinline__ void bar_sync(int id, int n) { asm volatile("bar.sync %0, %1;" :: "r"(id), "r"(n) : "memory"); }
__device__ __forceinline__ void bar_arrive(int id, int n) { asm volatile("bar.arrive %0, %1;" :: "r"(id), "r"(n) : "memory"); }
__device__ __forceinline__ void mbar_arrive(uint32_t bar) { asm volatile("mbarrier.arrive.shared::cta.b64 _, [%0];" :: "r"(bar) : "memory"); }

__device__ __forceinline__ uint64_t make_desc(uint32_t saddr, uint32_t lbo, uint32_t sbo, uint32_t swz) {
    uint64_t d = 0;
    d |= (uint64_t)((saddr & 0x3FFFF) >> 4);
    d |= (uint64_t)((lbo >> 4) & 0x3FFF) << 16;
    d |= (uint64_t)((sbo >> 4) & 0x3FFF) << 32;
    d |= (uint64_t)swz << 62;
    return d;
}
__device__ __forceinline__ void wg_fence() { asm volatile("wgmma.fence.sync.aligned;" ::: "memory"); }
__device__ __forceinline__ void wg_commit() { asm volatile("wgmma.commit_group.sync.aligned;" ::: "memory"); }
template<int N> __device__ __forceinline__ void wg_wait() { asm volatile("wgmma.wait_group.sync.aligned %0;" :: "n"(N) : "memory"); }
#define A4(d, o) "+f"(d[o + 0]), "+f"(d[o + 1]), "+f"(d[o + 2]), "+f"(d[o + 3])
#define A16(d, o) A4(d, o), A4(d, o + 4), A4(d, o + 8), A4(d, o + 12)

__device__ __forceinline__ void wg_pv(float* d, const uint32_t* a, uint32_t lo, uint32_t hi) {
    asm volatile("{ .reg .b64 dd; mov.b64 dd, {%16, %17};\n"
                 "wgmma.mma_async.sync.aligned.m64n24k16.f32.bf16.bf16 {%0,%1,%2,%3,%4,%5,%6,%7,%8,%9,%10,%11}, {%12,%13,%14,%15}, dd, 1, 1, 1, 1; }"
                 : A4(d, 0), A4(d, 4), A4(d, 8) : "r"(a[0]), "r"(a[1]), "r"(a[2]), "r"(a[3]), "r"(lo), "r"(hi));
}
__device__ __forceinline__ void wg_qk(float* d, const uint32_t* a, uint32_t lo) {
    asm volatile("{ .reg .b64 dd; mov.b64 dd, {%36, %37};\n"
                 "wgmma.mma_async.sync.aligned.m64n64k16.f32.bf16.bf16 {%0,%1,%2,%3,%4,%5,%6,%7,%8,%9,%10,%11,%12,%13,%14,%15,%16,%17,%18,%19,%20,%21,%22,%23,%24,%25,%26,%27,%28,%29,%30,%31}, {%32,%33,%34,%35}, dd, 0, 1, 1, 0; }"
                 : A16(d, 0), A16(d, 16) : "r"(a[0]), "r"(a[1]), "r"(a[2]), "r"(a[3]), "r"(lo), "r"(16));
}
__device__ __forceinline__ void wg_rs32(float* d, const uint32_t* a, uint32_t lo) {
    asm volatile("{ .reg .b64 dd; mov.b64 dd, {%20, %21};\n"
                 "wgmma.mma_async.sync.aligned.m64n32k16.f32.bf16.bf16 {%0,%1,%2,%3,%4,%5,%6,%7,%8,%9,%10,%11,%12,%13,%14,%15}, {%16,%17,%18,%19}, dd, 1, 1, 1, 0; }"
                 : A16(d, 0) : "r"(a[0]), "r"(a[1]), "r"(a[2]), "r"(a[3]), "r"(lo), "r"(0x40000040));
}
__device__ __forceinline__ void wg_rs24(float* d, const uint32_t* a, uint32_t lo) {
    asm volatile("{ .reg .b64 dd; mov.b64 dd, {%16, %17};\n"
                 "wgmma.mma_async.sync.aligned.m64n24k16.f32.bf16.bf16 {%0,%1,%2,%3,%4,%5,%6,%7,%8,%9,%10,%11}, {%12,%13,%14,%15}, dd, 1, 1, 1, 0; }"
                 : A4(d, 0), A4(d, 4), A4(d, 8) : "r"(a[0]), "r"(a[1]), "r"(a[2]), "r"(a[3]), "r"(lo), "r"(0x40000040));
}
__device__ __forceinline__ void wg_ss64(float* d, uint64_t da, uint64_t db) {
    asm volatile("wgmma.mma_async.sync.aligned.m64n64k16.f32.bf16.bf16 {%0,%1,%2,%3,%4,%5,%6,%7,%8,%9,%10,%11,%12,%13,%14,%15,%16,%17,%18,%19,%20,%21,%22,%23,%24,%25,%26,%27,%28,%29,%30,%31}, %32, %33, 1, 1, 1, 0, 1;"
                 : A16(d, 0), A16(d, 16) : "l"(da), "l"(db));
}
__device__ __forceinline__ void wg_ss16(float* d, uint64_t da, uint64_t db) {
    asm volatile("wgmma.mma_async.sync.aligned.m64n16k16.f32.bf16.bf16 {%0,%1,%2,%3,%4,%5,%6,%7}, %8, %9, 1, 1, 1, 0, 1;"
                 : A4(d, 0), A4(d, 4) : "l"(da), "l"(db));
}
template<int N> __device__ __forceinline__ void fence_regs(float* r) {
    #pragma unroll
    for (int i = 0; i < N; i++) asm volatile("" : "+f"(r[i]) :: "memory");
}
__device__ __forceinline__ void mma_f16(float* d, const uint32_t* a, uint32_t b0, uint32_t b1) {
    asm volatile("mma.sync.aligned.m16n8k16.row.col.f32.f16.f16.f32 {%0,%1,%2,%3}, {%4,%5,%6,%7}, {%8,%9}, {%0,%1,%2,%3};"
                 : "+f"(d[0]), "+f"(d[1]), "+f"(d[2]), "+f"(d[3]) : "r"(a[0]), "r"(a[1]), "r"(a[2]), "r"(a[3]), "r"(b0), "r"(b1));
}
__device__ __forceinline__ uint32_t lds32(uint32_t addr) { uint32_t v; asm volatile("ld.shared.u32 %0, [%1];" : "=r"(v) : "r"(addr) : "memory"); return v; }
__device__ __forceinline__ void mma_bf16_p(float* d, uint32_t a0, uint32_t a1, uint32_t a2, uint32_t a3, uint32_t b0, uint32_t b1) {
    asm("mma.sync.aligned.m16n8k16.row.col.f32.bf16.bf16.f32 {%0,%1,%2,%3}, {%4,%5,%6,%7}, {%8,%9}, {%0,%1,%2,%3};"
        : "+f"(d[0]), "+f"(d[1]), "+f"(d[2]), "+f"(d[3]) : "r"(a0), "r"(a1), "r"(a2), "r"(a3), "r"(b0), "r"(b1));
}
__device__ __forceinline__ void ldsm4t_p(uint32_t* r, uint32_t addr) {
    asm("ldmatrix.sync.aligned.m8n8.x4.trans.shared.b16 {%0,%1,%2,%3}, [%4];" : "=r"(r[0]), "=r"(r[1]), "=r"(r[2]), "=r"(r[3]) : "r"(addr));
}
__device__ __forceinline__ uint32_t lds32_p(uint32_t addr) { uint32_t v; asm("ld.shared.u32 %0, [%1];" : "=r"(v) : "r"(addr)); return v; }
__device__ __forceinline__ uint32_t swz(uint32_t a) { return a ^ ((a >> 3) & 16u); }
__device__ __forceinline__ uint32_t swz128(uint32_t a) { return a ^ ((a >> 3) & 0x70u); }
__device__ __forceinline__ void sts32(uint32_t addr, uint32_t v) { asm volatile("st.shared.u32 [%0], %1;" :: "r"(addr), "r"(v) : "memory"); }
__device__ __forceinline__ void sts128(uint32_t addr, uint4 v) { asm volatile("st.shared.v4.u32 [%0], {%1,%2,%3,%4};" :: "r"(addr), "r"(v.x), "r"(v.y), "r"(v.z), "r"(v.w) : "memory"); }
__device__ __forceinline__ uint4 lds128(uint32_t addr) { uint4 v; asm volatile("ld.shared.v4.u32 {%0,%1,%2,%3}, [%4];" : "=r"(v.x), "=r"(v.y), "=r"(v.z), "=r"(v.w) : "r"(addr) : "memory"); return v; }
__device__ __forceinline__ void quad_transpose(uint32_t* v, int t) {
    #pragma unroll
    for (int p = 0; p < 2; p++) {
        const uint32_t x = __shfl_xor_sync(0xffffffffu, (t & 1) ? v[2 * p] : v[2 * p + 1], 1);
        if (t & 1) v[2 * p] = x; else v[2 * p + 1] = x;
    }
    #pragma unroll
    for (int p = 0; p < 2; p++) {
        const uint32_t x = __shfl_xor_sync(0xffffffffu, (t & 2) ? v[p] : v[p + 2], 2);
        if (t & 2) v[p] = x; else v[p + 2] = x;
    }
}
__device__ __forceinline__ float ex2f(float x) { float r; asm("ex2.approx.ftz.f32 %0, %1;" : "=f"(r) : "f"(x)); return r; }
__device__ __forceinline__ uint32_t pack_bf16(float lo, float hi) { uint32_t r; asm("cvt.rn.bf16x2.f32 %0, %1, %2;" : "=r"(r) : "f"(hi), "f"(lo)); return r; }
__device__ __forceinline__ uint32_t pack_f16(float lo, float hi) { uint32_t r; asm("cvt.rn.f16x2.f32 %0, %1, %2;" : "=r"(r) : "f"(hi), "f"(lo)); return r; }
__device__ __forceinline__ float bf_lo(uint32_t v) { return __uint_as_float(v << 16); }
__device__ __forceinline__ float bf_hi(uint32_t v) { return __uint_as_float(v & 0xFFFF0000u); }
__device__ __forceinline__ float bf_round(float x) { return __bfloat162float(__float2bfloat16_rn(x)); }

__device__ __forceinline__ uint32_t exp_mufu(float x0, float x1) { return pack_bf16(ex2f(x0), ex2f(x1)); }
#define SW_MAGIC (256.0f + 127.0f - 0.598938f)
__device__ __forceinline__ uint32_t exp_sw(float x0, float x1, uint32_t cA, uint32_t cB) {
    float t0 = x0 + SW_MAGIC, t1 = x1 + SW_MAGIC;
    uint32_t L, mh, ec, r;
    asm("prmt.b32 %0, %1, %2, 0x6521;" : "=r"(L) : "r"(__float_as_uint(t0)), "r"(__float_as_uint(t1)));
    asm("lop3.b32 %0, %1, 0x007F007F, %2, 0xEA;" : "=r"(mh) : "r"(L), "r"(cA));
    asm("lop3.b32 %0, %1, 0x7F807F80, %2, 0xEA;" : "=r"(ec) : "r"(L), "r"(cB));
    asm("fma.rn.bf16x2 %0, %1, %2, %3;" : "=r"(r) : "r"(L), "r"(mh), "r"(ec));
    return r;
}
#define MUFU_MASK_V 0x0555
#define AU_V 8
constexpr uint32_t MUFU_MASK = MUFU_MASK_V;
constexpr int AU = AU_V;

struct cf { float x, y; };
__device__ __forceinline__ cf cmul(cf a, cf b) { cf r; r.x = a.x * b.x - a.y * b.y; r.y = a.x * b.y + a.y * b.x; return r; }
__device__ __forceinline__ cf cexp_p(float a2, float b, float p) {
    float e = ex2f(a2 * p);
    float ph = b * p;
    ph -= (ph + 12582912.0f) - 12582912.0f;
    float ang = ph * 6.283185307f;
    cf r; r.x = e * __cosf(ang); r.y = e * __sinf(ang);
    return r;
}
__device__ __forceinline__ uint32_t h2_cmul(uint32_t w, uint32_t wsw, uint32_t e) {
    __half2 hw = *(__half2*)&w, hs = *(__half2*)&wsw, he = *(__half2*)&e;
    __half2 r = __hfma2(hs, __high2half2(he), __hmul2(hw, __low2half2(he)));
    return *(uint32_t*)&r;
}

struct Params {
    const __nv_bfloat16 *u, *lar, *aim, *cre, *cim, *logdt, *dskip;
    __nv_bfloat16* out;
};

constexpr int B_O = 0, B_KV = 8, B_WO = 12, B_WQ2 = 13, B_ST = 14, B_H = 15, B_X = 17, B_U = 19, B_WQ = 20;

__device__ __forceinline__ void helper_role(const Params& P, uint8_t* sp, uint32_t sb, unsigned epoch) {
    const uint32_t sBa = sb + SM_B;
    const int tid = threadIdx.x - 544;
    const int d0 = blockIdx.x * 4;
    uint8_t* sB = sp + SM_B;
    const uint2 dsk = __ldg((const uint2*)(P.dskip + d0));
    asm volatile("barrier.cluster.wait.aligned;" ::: "memory");
    {
        const int hg = blockIdx.x & 7;
        if (hg < 4 && tid < 32) {
            bar_sync(3, 160);
            if (tid == 0) {
                const float* s_misc = (const float*)(sp + SM_BAR + 256);
                const float st = fmaxf(fmaxf(s_misc[20], s_misc[21]), fmaxf(s_misc[22], s_misc[23]));
                st_release64(&g_flag_kv[((blockIdx.x >> 3) * 2 + (hg & 1)) * 2 + (hg >> 1)], ((unsigned long long)epoch << 32) | __float_as_uint(st));
            }
            __syncwarp();
        }
    }
    PROF2(2);
    bar_sync(10, 608);
    {
        uint32_t dd[4] = {__byte_perm(dsk.x, 0, 0x1010), __byte_perm(dsk.x, 0, 0x3232), __byte_perm(dsk.y, 0, 0x1010), __byte_perm(dsk.y, 0, 0x3232)};
        #pragma unroll 2
        for (int pi = tid; pi < 1024; pi += 96) {
            const int l = 2 * pi;
            uint32_t r[4];
            #pragma unroll
            for (int cc = 0; cc < 4; cc++) {
                const uint32_t y2 = *(const uint32_t*)(sB + S_Y + cc * 4096 + l * 2);
                const uint32_t u2 = lds32(swz128(sBa + S_U + cc * ULEN * 2 + (PADU + l) * 2));
                __nv_bfloat162 pr = __hmul2(*(const __nv_bfloat162*)&u2, *(const __nv_bfloat162*)&dd[cc]);
                __nv_bfloat162 sm = __hadd2(*(const __nv_bfloat162*)&y2, pr);
                r[cc] = *(uint32_t*)&sm;
            }
            *(uint2*)(P.out + (size_t)l * 1024 + 512 + d0) = make_uint2(__byte_perm(r[0], r[1], 0x5410), __byte_perm(r[2], r[3], 0x5410));
            *(uint2*)(P.out + (size_t)(l + 1) * 1024 + 512 + d0) = make_uint2(__byte_perm(r[0], r[1], 0x7632), __byte_perm(r[2], r[3], 0x7632));
        }
    }
    bar_arrive(11, 128);
    PROF2(4);
}

__global__ void __cluster_dims__(2, 1, 1) __launch_bounds__(NTHR, 1)
fused_kernel(const __grid_constant__ CUtensorMap tm_x, const __grid_constant__ CUtensorMap tm_wq,
             const __grid_constant__ CUtensorMap tm_wo, const __grid_constant__ CUtensorMap tm_wk,
             const __grid_constant__ CUtensorMap tm_wv, const __grid_constant__ CUtensorMap tm_u, const Params P) {
    extern __shared__ uint8_t smem_raw[];
    const uint32_t sb = (smem_u32(smem_raw) + 1023u) & ~1023u;
    uint8_t* sp = smem_raw + (sb - smem_u32(smem_raw));

    const int tid = threadIdx.x, warp = tid >> 5, lane = tid & 31, wg = tid >> 7, wiw = warp & 3;
    const int g = lane >> 2, t = lane & 3;
    const int qb = blockIdx.x >> 3, hg = blockIdx.x & 7;
    const uint32_t rank = blockIdx.x & 1;
    const int rowhalf = wg & 1, nh = wg >> 1;
    const bool kv_cta = hg < 4;
    const int kv_sel = hg >> 1;
    const bool kv_wg = kv_cta && (wg == 2 + (hg & 1));

    const uint32_t bars = sb + SM_BAR;
    float* s_misc = (float*)(sp + SM_BAR + 256);
    const CUtensorMap* tm_kv = kv_sel ? &tm_wv : &tm_wk;

    PROF(0);
    unsigned short p_lar = 0, p_aim = 0, p_cre = 0, p_cim = 0, p_ldt = 0;
    if (wg < 4) {
        const int n = (blockIdx.x * 4 + wg) * 128 + (tid & 127);
        p_lar = __ldg((const unsigned short*)P.lar + n);
        p_aim = __ldg((const unsigned short*)P.aim + n);
        p_cre = __ldg((const unsigned short*)P.cre + n);
        p_cim = __ldg((const unsigned short*)P.cim + n);
        p_ldt = __ldg((const unsigned short*)P.logdt + blockIdx.x * 4 + wg);
    } else if (warp == 16) {
        PROF3(5);
        if (lane == 0) {
            asm volatile("prefetch.tensormap [%0];" :: "l"((uint64_t)&tm_x) : "memory");
            asm volatile("prefetch.tensormap [%0];" :: "l"((uint64_t)tm_kv) : "memory");
            asm volatile("prefetch.tensormap [%0];" :: "l"((uint64_t)&tm_wq) : "memory");
            asm volatile("prefetch.tensormap [%0];" :: "l"((uint64_t)&tm_u) : "memory");
            mbar_init(bars + 8 * B_X, 1);
            mbar_init(bars + 8 * B_X + 8, 1);
            mbar_init(bars + 8 * B_U, 1);
            asm volatile("fence.mbarrier_init.release.cluster;" ::: "memory");
            mbar_expect_tx(bars + 8 * B_X, 65536u + (kv_cta ? 8192u : 0u));
            mbar_expect_tx(bars + 8 * B_X + 8, 65536u + (kv_cta ? 8192u : 0u));
            mbar_expect_tx(bars + 8 * B_U, 32768u);
        }
        __syncwarp();
        PROF3(6);
    }
    asm volatile("barrier.cluster.arrive.relaxed.aligned;" ::: "memory");
    const unsigned epoch = *(volatile unsigned*)&g_epoch + 1u;
    if (warp > 16) {
        if (lane == 0) {
            for (int i = warp - 17; i < B_X; i += 3) {
                mbar_init(bars + 8 * i, i >= B_H ? 2 : 1);
                if (i <= B_WQ2) mbar_expect_tx(bars + 8 * i, i < B_KV + 2 ? 16384u : i == B_KV + 2 ? 32768u : i <= B_WO ? 65536u : 32768u);
            }
            asm volatile("fence.mbarrier_init.release.cluster;" ::: "memory");
            fence_async_smem();
        } else if (warp == 19) {
            #pragma unroll
            for (int i = 0; i < 2; i++) if (lane - 1 + 31 * i < 46) asm volatile("prefetch.global.L2 [%0];" :: "l"((const char*)g_tabmap.v + (lane - 1 + 31 * i) * 128));
        }
        __syncwarp();
    }
    asm volatile("barrier.cluster.wait.aligned;" ::: "memory");
    PROF(5);
    if (warp == 16 && lane == 0) {
        tma_3d_mc(sb + (rank ? SM_A : SM_B), &tm_x, 0, qb * 128, rank * 4, bars + 8 * (B_X + rank));
        if (kv_cta) {
            #pragma unroll
            for (int i = 0; i < 4; i++) tma_2d(sb + SM_WKV + i * 4096, tm_kv, (i >> 1) * 8, (i & 1) * 256, bars + 8 * (B_X + (i & 1)));
        }
        mbar_init(bars + 8 * B_WQ, 1);
        asm volatile("fence.mbarrier_init.release.cluster;" ::: "memory");
        fence_async_smem();
        mbar_expect_tx(bars + 8 * B_WQ, 32768u);
        tma_2d(sb + SM_WQ, &tm_wq, hg * 64, 0, bars + 8 * B_WQ);
        #pragma unroll
        for (int i = 0; i < 4; i++) tma_2d_mc(sb + SM_SLAB + (rank * 4 + i) * 4096, &tm_u, (blockIdx.x >> 1) * 8, (rank * 4 + i) * 256, bars + 8 * B_U);
    }
    __syncwarp();
    asm volatile("barrier.cluster.arrive.relaxed.aligned;" ::: "memory");

    if (warp == 16) {
        if (lane == 0) asm volatile("prefetch.tensormap [%0];" :: "l"((uint64_t)&tm_wo) : "memory");
        asm volatile("barrier.cluster.wait.aligned;" ::: "memory");
        PROF3(10);
        bar_sync(13, 544);
        if (lane == 0) { fence_async_smem(); tma_2d(sb + SM_SLAB, &tm_wq, hg * 64, 256, bars + 8 * B_WQ2); }
        bar_sync(14, 288);
        if (lane == 0) pair_sync(bars + 8 * B_H, rank ^ 1);
        __syncwarp();
        PROF3(11);
        *(uint4*)(sp + SM_V + 32768 + lane * 32) = make_uint4(0x3F803F80u, 0x3F803F80u, 0x3F803F80u, 0x3F803F80u);
        *(uint4*)(sp + SM_V + 32768 + lane * 32 + 16) = make_uint4(0x3F803F80u, 0x3F803F80u, 0x3F803F80u, 0x3F803F80u);
        fence_async_smem();
        float km = wait_flag64(&g_flag_kv[2 * lane], epoch);
        float vm = wait_flag64(&g_flag_kv[2 * lane + 1], epoch);
        __syncwarp();
        PROF3(12);
        if (lane == 0) {
            fence_async_all();
            #pragma unroll
            for (int i = 0; i < 4; i++) {
                const uint32_t k0 = i == 0 ? 0 : 128u << i, nk = i == 0 ? 256 : 128u << i;
                const uint32_t bar = bars + 8 * (B_KV + i);
                if (rank == 0) bulk_g2s_mc(sb + SM_K + k0 * 32, g_kimg + k0 * 32, nk * 32, bar);
                else {
                    bulk_g2s_mc(sb + SM_V + k0 * 16, g_vimg + k0 * 16, nk * 16, bar);
                    bulk_g2s_mc(sb + SM_V + 66560 - (k0 + nk) * 16, g_vimg + 66560 - (k0 + nk) * 16, nk * 16, bar);
                }
            }
        }
        #pragma unroll
        for (int o = 16; o; o >>= 1) { km = fmaxf(km, __shfl_xor_sync(0xffffffffu, km, o)); vm = fmaxf(vm, __shfl_xor_sync(0xffffffffu, vm, o)); }
        if (lane == 0) { s_misc[16] = km; s_misc[17] = vm; mbar_arrive(bars + 8 * B_ST); }
        PROF3(13);
        bar_sync(11, 128);
        if (lane < 2) { fence_async_smem(); tma_2d(sb + SM_B + lane * 32768, &tm_wo, hg * 64, lane * 256, bars + 8 * B_WO); }
        bar_sync(12, 544);
        if (lane == 0) pair_arrive(bars + 8 * (B_H + 1), rank ^ 1);
        if (lane == 0) {
            st_release(&g_flag_o[blockIdx.x], epoch);
            mbar_wait(bars + 8 * (B_H + 1), 0);
        }
        __syncwarp();
        PROF3(14);
        if (lane < 4) {
            const int src = (2 * lane + (hg & 6) + rank) & 7;
            wait_flag(&g_flag_o[qb * 8 + src], epoch);
            fence_async_all();
            bulk_g2s_mc(sb + SM_A + src * 16384, g_oimg + qb * 131072 + src * 16384, 16384, bars + 8 * (B_O + src));
        }
        __syncwarp();
        PROF3(15);
        if (lane == 0) {
            const unsigned prev = atomicAdd(&g_done, 1u);
            if (prev == NCTA - 1) {
                g_done = 0;
                __threadfence();
                *(volatile unsigned*)&g_epoch = epoch;
            }
        }
    } else if (wg == 4) {
        helper_role(P, sp, sb, epoch);
    } else {
        uint8_t* sB = sp + SM_B;
        const uint32_t sBa = sb + SM_B;
        {
            const int c = wg;
            const float dt = bf_round(expf(bf_lo(p_ldt)));
            const float are = -bf_round(expf(bf_lo(p_lar))) * dt;
            const float aim = bf_lo(p_aim) * dt;
            float cr = 2.0f * (bf_lo(p_cre) * dt);
            float ci = 2.0f * (bf_lo(p_cim) * dt);
            const float a2 = are * 1.4426950408889634f, bb = aim * 0.15915494309189535f;
            float m = fmaxf(fabsf(cr), fabsf(ci));
            #pragma unroll
            for (int o = 16; o; o >>= 1) m = fmaxf(m, __shfl_xor_sync(0xffffffffu, m, o));
            int ebits = (__float_as_uint(m) >> 23) & 0xFF;
            ebits = min(max(ebits, 2), 250);
            const float scale = __uint_as_float((uint32_t)(ebits + 1) << 23);
            const float iscale = __uint_as_float((uint32_t)(253 - ebits) << 23);
            cf cc; cc.x = cr * iscale; cc.y = ci * iscale;

            const uint32_t stg = sBa + S_KC + warp * 1024;
            uint4* stp = (uint4*)(sB + S_KC + warp * 1024 + lane * 32);
            const uint32_t fa = stg + t * 32 + g * 4;

            uint32_t af[4][2][4];
            cf E256;
            {
                const cf E8 = cexp_p(a2, bb, 8.0f);
                uint32_t w[8];
                cf cur; cur.x = 1.0f; cur.y = 0.0f;
                w[0] = pack_f16(1.0f, 0.0f);
                cur = E8; w[1] = pack_f16(cur.x, cur.y);
                #pragma unroll
                for (int i = 2; i < 8; i++) { cur = cmul(cur, E8); w[i] = pack_f16(cur.x, cur.y); }
                stp[0] = make_uint4(w[0], w[1], w[2], w[3]);
                stp[1] = make_uint4(w[4], w[5], w[6], w[7]);
                const cf E64 = cexp_p(a2, bb, 64.0f);
                const cf E128 = cmul(E64, E64), E192 = cmul(E128, E64);
                E256 = cexp_p(a2, bb, 256.0f);
                const uint32_t e1 = pack_f16(E64.x, E64.y), e2 = pack_f16(E128.x, E128.y), e3 = pack_f16(E192.x, E192.y);
                __syncwarp();
                #pragma unroll
                for (int s = 0; s < 4; s++) {
                    #pragma unroll
                    for (int hh = 0; hh < 2; hh++) {
                        const uint32_t w0 = lds32(fa + s * 256 + hh * 128);
                        const uint32_t wsw = __byte_perm(w0, 0, 0x1032) ^ 0x00008000u;
                        const int src = 8 * s + t + 4 * hh;
                        const uint32_t f1 = __shfl_sync(0xffffffffu, e1, src), f2 = __shfl_sync(0xffffffffu, e2, src), f3 = __shfl_sync(0xffffffffu, e3, src);
                        af[s][0][2 * hh] = w0;
                        af[s][0][2 * hh + 1] = h2_cmul(w0, wsw, f1);
                        af[s][1][2 * hh] = h2_cmul(w0, wsw, f2);
                        af[s][1][2 * hh + 1] = h2_cmul(w0, wsw, f3);
                    }
                }
                __syncwarp();
            }
            float acc[2][3][4];
            #pragma unroll
            for (int i = 0; i < 24; i++) (&acc[0][0][0])[i] = 0.0f;
            const cf E1 = cexp_p(a2, bb, 1.0f);
            const cf E2 = cmul(E1, E1), E4 = cmul(E2, E2);
            cf X512;
            #pragma unroll
            for (int nt = 0; nt < 3; nt++) {
                uint32_t xv[8];
                if (nt == 0) {
                    cf cur = cc;
                    xv[0] = pack_f16(cur.x, -cur.y);
                    #pragma unroll
                    for (int i = 1; i < 8; i++) { cur = cmul(cur, E1); xv[i] = pack_f16(cur.x, -cur.y); }
                } else if (nt == 1) {
                    cf cur = cmul(cc, E256);
                    X512 = cmul(cur, E256);
                    xv[0] = pack_f16(cur.x, -cur.y);
                    #pragma unroll
                    for (int i = 1; i < 4; i++) { cur = cmul(cur, E2); xv[i] = pack_f16(cur.x, -cur.y); }
                    cur = cmul(X512, E4);
                    xv[4] = pack_f16(X512.x, -X512.y); xv[5] = pack_f16(cur.x, -cur.y);
                    X512 = cmul(X512, E256);
                    cur = cmul(X512, E4);
                    xv[6] = pack_f16(X512.x, -X512.y); xv[7] = pack_f16(cur.x, -cur.y);
                } else {
                    cf cur = X512;
                    #pragma unroll
                    for (int i = 0; i < 5; i++) { cur = cmul(cur, E256); xv[i] = pack_f16(cur.x, -cur.y); }
                    xv[5] = 0; xv[6] = 0; xv[7] = 0;
                }
                stp[0] = make_uint4(xv[0], xv[1], xv[2], xv[3]);
                stp[1] = make_uint4(xv[4], xv[5], xv[6], xv[7]);
                __syncwarp();
                #pragma unroll
                for (int s = 0; s < 4; s++) {
                    const uint32_t b0 = lds32(fa + s * 256), b1 = lds32(fa + s * 256 + 128);
                    mma_f16(acc[0][nt], af[s][0], b0, b1);
                    mma_f16(acc[1][nt], af[s][1], b0, b1);
                }
                __syncwarp();
            }
            float* kc = (float*)(sB + S_KC + c * 4096);
            bar_sync(4 + c, 128);
            #pragma unroll 1
            for (int step = 0; step < 4; step++) {
                if ((warp & 3) == step) {
                    #pragma unroll
                    for (int mt = 0; mt < 2; mt++)
                        #pragma unroll
                        for (int nt = 0; nt < 3; nt++)
                            #pragma unroll
                            for (int hh = 0; hh < 2; hh++) {
                                float2* p = (float2*)(kc + (mt * 16 + hh * 8 + g) * 24 + nt * 8 + 2 * t);
                                float2 v = make_float2(acc[mt][nt][2 * hh] * scale, acc[mt][nt][2 * hh + 1] * scale);
                                if (step) { float2 o = *p; v.x += o.x; v.y += o.y; }
                                *p = v;
                            }
                }
                if (step < 3) bar_sync(4 + c, 128);
            }
        }

        asm volatile("barrier.cluster.wait.aligned;" ::: "memory");
        PROF(4);
        uint32_t q[2][4];
        {
            const uint64_t dA0 = make_desc(sb + SM_B + rowhalf * 8192, 16, 1024, 1);
            const uint64_t dA1 = make_desc(sb + SM_A + rowhalf * 8192, 16, 1024, 1) - 4096;
            uint4* qx = (uint4*)(sp + SM_B + S_QX) + (tid & 255) * 2;
            auto stage_u = [&]() {
                #pragma unroll
                for (int i = 0; i < 1; i++) {
                    const int z = tid + 512 * i;
                    if (z < 4 * 80) sts128(sBa + S_U + (z / 80) * ULEN * 2 + (PADU - 640) * 2 + (z % 80) * 16, make_uint4(0, 0, 0, 0));
                }
                mbar_wait(bars + 8 * B_U, 0);
                #pragma unroll
                for (int i = 0; i < 2; i++) {
                    const int l = 2 * (tid + 512 * i);
                    const uint2 r0 = *(const uint2*)(sp + SM_SLAB + l * 16 + rank * 8), r1 = *(const uint2*)(sp + SM_SLAB + l * 16 + 16 + rank * 8);
                    const uint32_t dst = swz128(sBa + S_U + (PADU + l) * 2);
                    sts32(dst, __byte_perm(r0.x, r1.x, 0x5410));
                    sts32(dst + ULEN * 2, __byte_perm(r0.x, r1.x, 0x7632));
                    sts32(dst + ULEN * 4, __byte_perm(r0.y, r1.y, 0x5410));
                    sts32(dst + ULEN * 6, __byte_perm(r0.y, r1.y, 0x7632));
                }
                fence_async_smem();
                bar_arrive(13, 544);
            };
            if (wg < 2) {
                float acc[32];
                #pragma unroll
                for (int i = 0; i < 32; i++) acc[i] = 0.0f;
                fence_regs<32>(acc);
                const uint64_t dB = make_desc(sb + SM_WQ, 16, 1024, 1);
                mbar_wait(bars + 8 * B_WQ, 0);
                mbar_wait(bars + 8 * B_X, 0);
                PROF(2);
                #pragma unroll 1
                for (int ch = 0; ch < 4; ch++) {
                    wg_fence();
                    #pragma unroll
                    for (int ks = 0; ks < 4; ks++) wg_ss64(acc, dA0 + ch * 1024 + ks * 2, dB + (ch * 4 + ks) * 128);
                    wg_commit();
                }
                wg_wait<0>();
                fence_regs<32>(acc);
                bar_sync(1, 512);
                PROF(15);
                stage_u();
                bar_arrive(2, 512);
                PROF(1);
                mbar_wait(bars + 8 * B_WQ2, 0);
                mbar_wait(bars + 8 * (B_X + 1), 0);
                fence_regs<32>(acc);
                #pragma unroll 1
                for (int ch = 4; ch < 8; ch++) {
                    wg_fence();
                    #pragma unroll
                    for (int ks = 0; ks < 4; ks++) wg_ss64(acc, dA1 + ch * 1024 + ks * 2, dB + (ch * 4 + ks) * 128);
                    wg_commit();
                }
                wg_wait<0>();
                fence_regs<32>(acc);
                bar_arrive(14, 288);
                float qm = 0.0f;
                uint32_t qa[4][4];
                #pragma unroll
                for (int i = 0; i < 4; i++) {
                    #pragma unroll
                    for (int j = 0; j < 4; j++) qa[i][j] = pack_bf16(acc[8 * i + 2 * j], acc[8 * i + 2 * j + 1]);
                    float n0 = bf_lo(qa[i][0]) * bf_lo(qa[i][0]) + bf_hi(qa[i][0]) * bf_hi(qa[i][0]) + bf_lo(qa[i][2]) * bf_lo(qa[i][2]) + bf_hi(qa[i][2]) * bf_hi(qa[i][2]);
                    float n1 = bf_lo(qa[i][1]) * bf_lo(qa[i][1]) + bf_hi(qa[i][1]) * bf_hi(qa[i][1]) + bf_lo(qa[i][3]) * bf_lo(qa[i][3]) + bf_hi(qa[i][3]) * bf_hi(qa[i][3]);
                    n0 += __shfl_xor_sync(0xffffffffu, n0, 1); n0 += __shfl_xor_sync(0xffffffffu, n0, 2);
                    n1 += __shfl_xor_sync(0xffffffffu, n1, 1); n1 += __shfl_xor_sync(0xffffffffu, n1, 2);
                    qm = (n0 != n0 || n1 != n1) ? __int_as_float(0x7f800000) : fmaxf(qm, fmaxf(n0, n1));
                }
                #pragma unroll
                for (int o = 16; o; o >>= 1) qm = fmaxf(qm, __shfl_xor_sync(0xffffffffu, qm, o));
                if (lane == 0) s_misc[warp] = qm;
                qx[0] = make_uint4(qa[2][0], qa[2][1], qa[2][2], qa[2][3]);
                qx[1] = make_uint4(qa[3][0], qa[3][1], qa[3][2], qa[3][3]);
                #pragma unroll
                for (int j = 0; j < 4; j++) { q[0][j] = qa[0][j]; q[1][j] = qa[1][j]; }
                bar_sync(1, 512);
            } else {
                if (kv_wg) {
                    float akv[8];
                    #pragma unroll
                    for (int i = 0; i < 8; i++) akv[i] = 0.0f;
                    fence_regs<8>(akv);
                    const uint64_t dC = make_desc(sb + SM_WKV, 128, 8192, 0);
                    #pragma unroll 1
                    for (int ch = 0; ch < 8; ch++) {
                        if ((ch & 3) == 0) mbar_wait(bars + 8 * (B_X + (ch >> 2)), 0);
                        const uint64_t dA = ch < 4 ? dA0 : dA1;
                        wg_fence();
                        #pragma unroll
                        for (int ks = 0; ks < 4; ks++) wg_ss16(akv, dA + ch * 1024 + ks * 2, dC + (ch * 4 + ks) * 16);
                        wg_commit();
                    }
                    wg_wait<0>();
                    fence_regs<8>(akv);
                    const int key = qb * 128 + rowhalf * 64 + wiw * 16 + g;
                    uint32_t pk[4];
                    #pragma unroll
                    for (int i = 0; i < 4; i++) pk[i] = pack_bf16(akv[2 * i], akv[2 * i + 1]);
                    float st;
                    if (kv_sel == 0) {
                        uint8_t* b = g_kimg + (key >> 3) * 256 + (key & 7) * 16 + 4 * t;
                        *(uint32_t*)(b) = pk[0]; *(uint32_t*)(b + 256) = pk[1]; *(uint32_t*)(b + 128) = pk[2]; *(uint32_t*)(b + 384) = pk[3];
                        float n0 = bf_lo(pk[0]) * bf_lo(pk[0]) + bf_hi(pk[0]) * bf_hi(pk[0]) + bf_lo(pk[2]) * bf_lo(pk[2]) + bf_hi(pk[2]) * bf_hi(pk[2]);
                        float n1 = bf_lo(pk[1]) * bf_lo(pk[1]) + bf_hi(pk[1]) * bf_hi(pk[1]) + bf_lo(pk[3]) * bf_lo(pk[3]) + bf_hi(pk[3]) * bf_hi(pk[3]);
                        n0 += __shfl_xor_sync(0xffffffffu, n0, 1); n0 += __shfl_xor_sync(0xffffffffu, n0, 2);
                        n1 += __shfl_xor_sync(0xffffffffu, n1, 1); n1 += __shfl_xor_sync(0xffffffffu, n1, 2);
                        st = (n0 != n0 || n1 != n1) ? __int_as_float(0x7f800000) : fmaxf(n0, n1);
                    } else {
                        uint8_t* lo = g_vimg + key * 16 + 4 * t;
                        uint8_t* hi = g_vimg + 33792 + (31 - (key >> 6)) * 1024 + (key & 63) * 16 + 4 * t;
                        *(uint32_t*)(lo) = pk[0]; *(uint32_t*)(lo + 128) = pk[1]; *(uint32_t*)(hi) = pk[2]; *(uint32_t*)(hi + 128) = pk[3];
                        st = 0.0f;
                        #pragma unroll
                        for (int i = 0; i < 4; i++) {
                            float a = fabsf(bf_lo(pk[i])), b = fabsf(bf_hi(pk[i]));
                            st = (a != a || b != b) ? __int_as_float(0x7f800000) : fmaxf(st, fmaxf(a, b));
                        }
                    }
                    #pragma unroll
                    for (int o = 16; o; o >>= 1) st = fmaxf(st, __shfl_xor_sync(0xffffffffu, st, o));
                    if (lane == 0) s_misc[20 + wiw] = st;
                bar_arrive(3, 160);
                }
                uint2 mp[3];
                #pragma unroll
                for (int i = 0; i < 3; i++) { const int w = (tid & 255) + 256 * i; mp[i] = (w < TABN / 4) ? __ldg((const uint2*)g_tabmap.v + w) : make_uint2(0u, 0u); }
                bar_sync(1, 512);
                stage_u();
                #pragma unroll 1
                for (int cc = 0; cc < 4; cc++) {
                    const float* kc = (const float*)(sB + S_KC + cc * 4096);
                    uint2* tab = (uint2*)(sB + S_TAB + cc * TABN * 2);
                    #pragma unroll
                    for (int i = 0; i < 3; i++) {
                        const int w = (tid & 255) + 256 * i;
                        if (w < TABN / 4) tab[w] = make_uint2(pack_bf16(kc[mp[i].x & 0xFFFF], kc[mp[i].x >> 16]), pack_bf16(kc[mp[i].y & 0xFFFF], kc[mp[i].y >> 16]));
                    }
                }
                bar_sync(2, 512);
                #pragma unroll 1
                for (int tk = tid & 255; tk < 4 * 130; tk += 256) {
                    const int c = tk / 130, i = tk % 130;
                    const uint32_t src = sBa + S_U + c * ULEN * 2 + (PADU + 8 * i - WPAD - 8) * 2;
                    const uint4 v0 = lds128(swz128(src)), v1 = lds128(swz128(src + 16)), v2 = lds128(swz128(src + 32));
                    float x[16];
                    const uint32_t vv[8] = {v0.z, v0.w, v1.x, v1.y, v1.z, v1.w, v2.x, v2.y};
                    #pragma unroll
                    for (int k = 0; k < 8; k++) { x[2 * k] = bf_lo(vv[k]); x[2 * k + 1] = bf_hi(vv[k]); }
                    float p2[15], w7[8], w9[8];
                    #pragma unroll
                    for (int e = 0; e < 15; e++) p2[e] = x[e] + x[e + 1];
                    #pragma unroll
                    for (int e = 0; e < 8; e++) {
                        w7[e] = (p2[e + 1] + p2[e + 3]) + (p2[e + 5] + x[e + 7]);
                        w9[e] = w7[e] + (x[e] + x[e + 8]);
                    }
                    sts128(swz(sBa + S_W7 + c * W3LEN * 2 + i * 16), make_uint4(pack_bf16(w7[0], w7[1]), pack_bf16(w7[2], w7[3]), pack_bf16(w7[4], w7[5]), pack_bf16(w7[6], w7[7])));
                    sts128(swz(sBa + S_W9 + c * W3LEN * 2 + i * 16), make_uint4(pack_bf16(w9[0], w9[1]), pack_bf16(w9[2], w9[3]), pack_bf16(w9[4], w9[5]), pack_bf16(w9[6], w9[7])));
                }
                bar_sync(1, 512);
                const uint4 q0 = qx[0], q1 = qx[1];
                q[0][0] = q0.x; q[0][1] = q0.y; q[0][2] = q0.z; q[0][3] = q0.w;
                q[1][0] = q1.x; q[1][1] = q1.y; q[1][2] = q1.z; q[1][3] = q1.w;
            }
        }
        PROF(3);
        {
            const int c = wg;
            uint32_t sBl = sBa;
            asm volatile("" : "+r"(sBl) :: "memory");
            float acc[16];
            const uint32_t tabc = sBl + S_TAB + c * TABN * 2;
            const uint32_t tD = tabc + ((g & 1) ? (TD1 + CD + 1) : (TD0 + CD)) * 2 - (g - 2 * t) * 2 - 32 * wiw;
            const uint32_t uLo = (((sBl + S_U + c * ULEN * 2 + PADU * 2) & 0x3FFFF) >> 4) | (1u << 16);
            uint32_t A[2][4][4];
            auto load_set = [&](uint32_t (&X)[4][4], uint32_t a) {
                X[0][2] = lds32(a + 16);
                #pragma unroll
                for (int i = 0; i < 4; i++) { X[i][0] = lds32(a - 32 * i); X[i][1] = lds32(a - 32 * i - 16); }
                #pragma unroll
                for (int i = 0; i < 4; i++) {
                    asm volatile("mov.b32 %0, %1;" : "=r"(X[i][3]) : "r"(X[i][0]));
                    if (i < 3) asm volatile("mov.b32 %0, %1;" : "=r"(X[i + 1][2]) : "r"(X[i][1]));
                }
            };
            {
                float accB[12];
                #pragma unroll
                for (int i = 0; i < 12; i++) accB[i] = 0.0f;
                fence_regs<12>(accB);
                #pragma unroll 1
                for (int m0 = 29; m0 < 69; m0 += 8) {
                    #pragma unroll
                    for (int h = 0; h < 2; h++) {
                        load_set(A[h], tD - 32 * (m0 + 4 * h));
                        wg_fence();
                        #pragma unroll
                        for (int i = 0; i < 4; i++) wg_rs24(accB, A[h][i], uLo + 64 - 2 * (m0 + 4 * h + i));
                        wg_commit();
                        wg_wait<1>();
                    }
                }
                wg_wait<0>();
                fence_regs<12>(accB);
                #pragma unroll
                for (int i = 0; i < 4; i++) acc[i] = 0.0f;
                #pragma unroll
                for (int i = 0; i < 12; i++) asm volatile("add.f32 %0, %1, 0f00000000;" : "=f"(acc[4 + i]) : "f"(accB[i]));
                fence_regs<16>(acc);
            }
            #pragma unroll 1
            for (int m0 = -3; m0 < 29; m0 += 8) {
                #pragma unroll
                for (int h = 0; h < 2; h++) {
                    load_set(A[h], tD - 32 * (m0 + 4 * h));
                    wg_fence();
                    #pragma unroll
                    for (int i = 0; i < 4; i++) wg_rs32(acc, A[h][i], uLo - 2 * (m0 + 4 * h + i));
                    wg_commit();
                    wg_wait<1>();
                }
            }
            wg_wait<0>();
            fence_regs<16>(acc);
            PROF(6);
            {
                asm volatile("" : "+r"(sBl) :: "memory");
                const int mi = lane >> 3, r8 = lane & 7;
                const uint32_t frag = (16 * (8 * (mi >> 1) + r8) + 8 * (mi & 1)) * 2;
                const uint32_t t3 = sBl + S_TAB + c * TABN * 2 + (T3B + ((wiw & 1) ? (T3C + C3 + 1) : C3)) * 2 - (4 * g + wiw - 2 * t) * 2;
                #pragma unroll
                for (int s = 0; s < 2; s++) {
                    const uint32_t sig = swz(sBl + (s ? S_W7 : S_W9) + c * W3LEN * 2 + WPAD * 2 + frag - (s ? 16 : 32));
                    uint32_t a[4][4], R[4][2];
                    #pragma unroll
                    for (int b = 0; b < 4; b++) ldsm4t_p(a[b], sig + b * 512);
                    #pragma unroll
                    for (int i = 0; i < 4; i++) { R[i][0] = lds32_p(t3 + s * (T3S * 2) - 2 * (48 + 16 * i)); R[i][1] = lds32_p(t3 + s * (T3S * 2) - 2 * (40 + 16 * i)); }
                    #pragma unroll
                    for (int b = 0; b < 4; b++) {
                        mma_bf16_p(acc + 12, a[b][0], a[b][1], a[b][2], a[b][3], R[3 - b][0], R[3 - b][1]);
                        if (b < 2) mma_bf16_p(acc + 8, a[b][0], a[b][1], a[b][2], a[b][3], R[1 - b][0], R[1 - b][1]);
                    }
                }
            }
            __nv_bfloat16* ys = (__nv_bfloat16*)(sB + S_Y + c * 4096) + 128 * t + 16 * wiw + g;
            #pragma unroll
            for (int j = 0; j < 4; j++) {
                ys[512 * j] = __float2bfloat16_rn(acc[4 * j]);
                ys[512 * j + 64] = __float2bfloat16_rn(acc[4 * j + 1]);
                ys[512 * j + 8] = __float2bfloat16_rn(acc[4 * j + 2]);
                ys[512 * j + 72] = __float2bfloat16_rn(acc[4 * j + 3]);
            }
        }
        bar_arrive(10, 608);
        PROF(7);
        {
            mbar_wait(bars + 8 * B_ST, 0);
            PROF(9); PROFC(8);
            float qm = 0.0f;
            #pragma unroll
            for (int i = 0; i < 8; i++) qm = fmaxf(qm, s_misc[i]);
            const float vm = s_misc[17];
            const float QS = 0.25f * 1.4426950408889634f;
            const bool fast = (qm * s_misc[16] * (QS * QS * 1.02f) <= 60.0f * 60.0f) && (vm <= 1.0e12f) && (vm >= 1.0e-12f || vm == 0.0f);
            uint8_t* ob = g_oimg + qb * 131072 + hg * 16384 + nh * 8192 + (rowhalf * 8 + wiw * 2) * 128 + g * 16 + 4 * t;
            uint32_t cA = 0xBF00BF00u, cB = 0x00030003u;
            asm volatile("" : "+r"(cA), "+r"(cB));
            #pragma unroll 1
            for (int tile = 0; tile < 2; tile++) {
                uint32_t kLo = (((sb + SM_K) & 0x3FFFF) >> 4) | (8u << 16), vLo = (((sb + SM_V) & 0x3FFFF) >> 4) | (8u << 16), vHi = 2048;
                float o[12], s[32];
                uint32_t p[16], qq[4];
                #pragma unroll
                for (int i = 0; i < 4; i++) {
                    qq[i] = tile ? q[1][i] : q[0][i];
                    if (fast) qq[i] = pack_bf16(bf_lo(qq[i]) * QS, bf_hi(qq[i]) * QS);
                    asm volatile("" : "+r"(qq[i]));
                }
                #pragma unroll
                for (int i = 0; i < 12; i++) o[i] = 0.0f;
                #pragma unroll
                for (int i = 0; i < 32; i++) s[i] = 0.0f;
                fence_regs<12>(o);
                fence_regs<32>(s);
                if (fast) {
                    #pragma unroll 1
                    for (int c = 0; c < SEQ / (64 * AU); c++) {
                        if (AU == 4) { if (c <= 4) mbar_wait(bars + 8 * (B_KV + (c < 2 ? c : c < 4 ? 2 : 3)), 0); }
                        else { if (c <= 2) mbar_wait(bars + 8 * (B_KV + (c ? c + 1 : 0)), 0); }
                        wg_fence();
                        wg_qk(s, qq, kLo);
                        wg_commit();
                        #pragma unroll
                        for (int u = 0; u < AU; u++) {
                            wg_wait<0>();
                            fence_regs<32>(s);
                            #pragma unroll
                            for (int i = 0; i < 16; i++) {
                                if ((MUFU_MASK >> i) & 1) p[i] = exp_mufu(s[2 * i], s[2 * i + 1]);
                                else p[i] = exp_sw(s[2 * i], s[2 * i + 1], cA, cB);
                            }
                            if (AU == 8 && u == 3) mbar_wait(bars + 8 * (B_KV + 1), 0);
                            wg_fence();
                            if (u + 1 < AU) wg_qk(s, qq, kLo + (u + 1) * 128);
                            #pragma unroll
                            for (int kk = 0; kk < 4; kk++) wg_pv(o, p + 4 * kk, vLo + u * 64 + kk * 16, vHi - u * 64);
                            wg_commit();
                        }
                        kLo += 128 * AU; vLo += 64 * AU; vHi -= 64 * AU;
                    }
                    wg_wait<0>();
                } else {
                    float mx0 = -INFINITY, mx1 = -INFINITY;
                    #pragma unroll 1
                    for (int c = 0; c < SEQ / 64; c++) {
                        if (c <= 16) mbar_wait(bars + 8 * (B_KV + (c < 8 ? (c >> 2) : c < 16 ? 2 : 3)), 0);
                        wg_fence();
                        wg_qk(s, qq, kLo);
                        wg_commit();
                        wg_wait<0>();
                        fence_regs<32>(s);
                        fence_regs<12>(o);
                        float m0 = mx0, m1 = mx1;
                        #pragma unroll
                        for (int j = 0; j < 16; j++) {
                            const uint32_t r = pack_bf16(s[2 * j], s[2 * j + 1]);
                            s[2 * j] = bf_lo(r) * QS; s[2 * j + 1] = bf_hi(r) * QS;
                        }
                        #pragma unroll
                        for (int j = 0; j < 8; j++) {
                            m0 = fmaxf(m0, fmaxf(s[4 * j], s[4 * j + 1]));
                            m1 = fmaxf(m1, fmaxf(s[4 * j + 2], s[4 * j + 3]));
                        }
                        m0 = fmaxf(m0, __shfl_xor_sync(0xffffffffu, m0, 1)); m0 = fmaxf(m0, __shfl_xor_sync(0xffffffffu, m0, 2));
                        m1 = fmaxf(m1, __shfl_xor_sync(0xffffffffu, m1, 1)); m1 = fmaxf(m1, __shfl_xor_sync(0xffffffffu, m1, 2));
                        const float c0 = ex2f(mx0 - m0), c1 = ex2f(mx1 - m1);
                        mx0 = m0; mx1 = m1;
                        #pragma unroll
                        for (int j = 0; j < 3; j++) { o[4 * j] *= c0; o[4 * j + 1] *= c0; o[4 * j + 2] *= c1; o[4 * j + 3] *= c1; }
                        #pragma unroll
                        for (int j = 0; j < 8; j++) {
                            p[2 * j] = exp_mufu(s[4 * j] - m0, s[4 * j + 1] - m0);
                            p[2 * j + 1] = exp_mufu(s[4 * j + 2] - m1, s[4 * j + 3] - m1);
                        }
                        wg_fence();
                        #pragma unroll
                        for (int kk = 0; kk < 4; kk++) wg_pv(o, p + 4 * kk, vLo + kk * 16, vHi);
                        wg_commit();
                        wg_wait<0>();
                        kLo += 128; vLo += 64; vHi -= 64;
                    }
                }
                fence_regs<12>(o);
                if (tile == 0) PROFC(3);
                const float i0 = 1.0f / o[4], i1 = 1.0f / o[6];
                uint8_t* b = ob + tile * 4096;
                *(uint32_t*)(b) = pack_bf16(o[0] * i0, o[1] * i0);
                *(uint32_t*)(b + 128) = pack_bf16(o[2] * i1, o[3] * i1);
                *(uint32_t*)(b + 2048) = pack_bf16(o[8] * i0, o[9] * i0);
                *(uint32_t*)(b + 2048 + 128) = pack_bf16(o[10] * i1, o[11] * i1);
            }
        }
        PROF(10); PROFC(9);
        bar_arrive(12, 544);

        if (wg < 2) {
            float acc[32];
            #pragma unroll
            for (int i = 0; i < 32; i++) acc[i] = 0.0f;
            fence_regs<32>(acc);
            const uint64_t dA = make_desc(sb + SM_A + rowhalf * 1024, 2048, 128, 0);
            const uint64_t dB = make_desc(sb + SM_B, 16, 1024, 1);
            mbar_wait(bars + 8 * B_WO, 0);
            #pragma unroll 1
            for (int i = 0; i < 8; i++) {
                const int src = ((hg & 6) + i) & 7;
                mbar_wait(bars + 8 * (B_O + src), 0);
                wg_fence();
                #pragma unroll
                for (int kk = 0; kk < 4; kk++) wg_ss64(acc, dA + src * 1024 + kk * 256, dB + (src * 4 + kk) * 128);
                wg_commit();
            }
            wg_wait<0>();
            fence_regs<32>(acc);
            PROF(12);
            const int row = qb * 128 + rowhalf * 64 + wiw * 16 + g;
            uint4* o128 = (uint4*)(P.out + (size_t)row * 1024 + hg * 64 + 8 * t);
            #pragma unroll
            for (int rr = 0; rr < 2; rr++)
                #pragma unroll
                for (int a = 0; a < 2; a++) {
                    uint32_t v[4];
                    #pragma unroll
                    for (int j = 0; j < 4; j++) v[j] = pack_bf16(acc[16 * a + 4 * j + 2 * rr], acc[16 * a + 4 * j + 2 * rr + 1]);
                    quad_transpose(v, t);
                    o128[rr * 1024 + a * 4] = make_uint4(v[0], v[1], v[2], v[3]);
                }
        }
        PROF(13);
    }
}

typedef CUresult (*EncodeFn)(CUtensorMap*, CUtensorMapDataType, cuuint32_t, void*, const cuuint64_t*, const cuuint64_t*,
                             const cuuint32_t*, const cuuint32_t*, CUtensorMapInterleave, CUtensorMapSwizzle,
                             CUtensorMapL2promotion, CUtensorMapFloatOOBfill);

void make_map(EncodeFn fn, CUtensorMap* m, const void* ptr, uint64_t inner, uint64_t outer, uint32_t box_in, uint32_t box_out, CUtensorMapSwizzle swz) {
    cuuint64_t dims[2] = {inner, outer};
    cuuint64_t strides[1] = {inner * 2};
    cuuint32_t box[2] = {box_in, box_out};
    cuuint32_t es[2] = {1, 1};
    fn(m, CU_TENSOR_MAP_DATA_TYPE_BFLOAT16, 2, const_cast<void*>(ptr), dims, strides, box, es, CU_TENSOR_MAP_INTERLEAVE_NONE, swz,
       CU_TENSOR_MAP_L2_PROMOTION_L2_128B, CU_TENSOR_MAP_FLOAT_OOB_FILL_NONE);
}

}

extern "C" void kernel_launch(void* const* d_in, const int* in_sizes, int n_in, void* d_out, int out_size) {
    (void)in_sizes; (void)n_in; (void)out_size;
    static EncodeFn fn = nullptr;
    if (!fn) {
        void* p = nullptr;
        cudaDriverEntryPointQueryResult qr;
        cudaGetDriverEntryPoint("cuTensorMapEncodeTiled", &p, cudaEnableDefault, &qr);
        fn = (EncodeFn)p;
        cudaFuncSetAttribute(fused_kernel, cudaFuncAttributeMaxDynamicSharedMemorySize, SM_ALLOC);
    }
    CUtensorMap tx, twq, two, twk, twv, tu;
    {
        cuuint64_t dims[3] = {64, 2048, 8};
        cuuint64_t strides[2] = {1024, 128};
        cuuint32_t box[3] = {64, 128, 4};
        cuuint32_t es[3] = {1, 1, 1};
        fn(&tx, CU_TENSOR_MAP_DATA_TYPE_BFLOAT16, 3, d_in[0], dims, strides, box, es, CU_TENSOR_MAP_INTERLEAVE_NONE, CU_TENSOR_MAP_SWIZZLE_128B,
           CU_TENSOR_MAP_L2_PROMOTION_L2_128B, CU_TENSOR_MAP_FLOAT_OOB_FILL_NONE);
    }
    make_map(fn, &tu, d_in[5], 512, 2048, 8, 256, CU_TENSOR_MAP_SWIZZLE_NONE);
    make_map(fn, &twq, d_in[1], 512, 512, 64, 256, CU_TENSOR_MAP_SWIZZLE_128B);
    make_map(fn, &twk, d_in[2], 16, 512, 8, 256, CU_TENSOR_MAP_SWIZZLE_NONE);
    make_map(fn, &twv, d_in[3], 16, 512, 8, 256, CU_TENSOR_MAP_SWIZZLE_NONE);
    make_map(fn, &two, d_in[4], 512, 512, 64, 256, CU_TENSOR_MAP_SWIZZLE_128B);
    Params P;
    P.u = (const __nv_bfloat16*)d_in[5];
    P.lar = (const __nv_bfloat16*)d_in[6];
    P.aim = (const __nv_bfloat16*)d_in[7];
    P.cre = (const __nv_bfloat16*)d_in[8];
    P.cim = (const __nv_bfloat16*)d_in[9];
    P.logdt = (const __nv_bfloat16*)d_in[10];
    P.dskip = (const __nv_bfloat16*)d_in[11];
    P.out = (__nv_bfloat16*)d_out;
    fused_kernel<<<NCTA, NTHR, SM_ALLOC>>>(tx, twq, two, twk, twv, tu, P);
}
```
